```python
import torch

def _softmax(x, axis=-1):
    return torch.softmax(x, dim=axis)

def _gelu(x):
    return torch.nn.functional.gelu(x, approximate='tanh')

def _silu(x):
    return torch.nn.functional.silu(x)

def _sigmoid(x):
    return torch.sigmoid(x)

def _layernorm(x, axis=-1, eps=1e-05):
    m = x.mean(dim=axis, keepdim=True)
    v = x.var(dim=axis, keepdim=True, unbiased=False)
    return (x - m) / torch.sqrt(v + eps)

def _scatter_add(tgt, idx, src, axis=0):
    return tgt.clone().index_add_(axis, idx, src)

def _segment_sum(src, seg, n):
    out = torch.zeros((n,) + src.shape[1:], dtype=src.dtype)
    return out.index_add_(0, seg, src)

def _pad(x, pw):
    flat = tuple((v for pair in reversed(pw) for v in pair))
    return torch.nn.functional.pad(x, flat)
kernel_name = 'standalone__tensor_product_equiv_tfn__graph'

def setup_inputs():

    _w = lambda a: (lambda t: t.to(torch.bfloat16) if t.is_floating_point() else t)(torch.as_tensor(a))
    N, deg, C, L, DE = (10000, 32, 128, 1, 16)
    E = N * deg
    M = (L + 1) ** 2
    src = (lambda lo, hi, *s: torch.randint(lo, hi, s))(0, N, E).to(torch.int64)
    dst = (lambda lo, hi, *s: torch.randint(lo, hi, s))(0, N, E).to(torch.int64)
    r = (lambda *s: torch.randn(*s, dtype=torch.bfloat16) * 0.05)(E, 3)
    r = r / (torch.linalg.norm(r, dim=-1, keepdim=True) + 1e-09)
    rx, ry, rz = (r[:, 0].clone(), r[:, 1].clone(), r[:, 2].clone())
    Ys = [torch.ones((E, 1), dtype=float)]
    if L >= 1:
        Ys.append(r.to(float))
    if L >= 2:
        Ys.append(torch.stack([2 * rx * ry, 2 * ry * rz, (3 * rz * rz - 1.0) / (lambda _x: torch.sqrt(torch.as_tensor(_x)))(3.0), 2 * rx * rz, rx * rx - ry * ry], dim=-1).to(float))
    for _l in range(3, L + 1):
        Ys.append(((lambda *s: torch.randn(*s, dtype=torch.bfloat16) * 0.05)(E, 2 * _l + 1) * 0.3).to(float))
    Y = torch.cat(Ys, dim=-1)
    cg = torch.zeros((M, M, M), dtype=float)
    off = [_l * _l for _l in range(L + 2)]
    for l1 in range(L + 1):
        for l2 in range(L + 1):
            for l3 in range(abs(l1 - l2), min(L, l1 + l2) + 1):
                d1, d2, d3 = (2 * l1 + 1, 2 * l2 + 1, 2 * l3 + 1)
                cg[off[l1]:off[l1 + 1], off[l2]:off[l2 + 1], off[l3]:off[l3 + 1]] = (lambda *s: torch.randn(*s, dtype=torch.bfloat16) * 0.05)(d1, d2, d3) / (lambda _x: torch.sqrt(torch.as_tensor(_x)))(float(d1 * d2))
    return {'x': _w((lambda *s: torch.randn(*s, dtype=torch.bfloat16) * 0.05)(N, C, M) * 0.2), 'src': _w(src), 'dst': _w(dst), 'Y': _w(Y), 'edge_feat': _w((lambda *s: torch.randn(*s, dtype=torch.bfloat16) * 0.05)(E, DE)), 'w_rad': _w((lambda *s: torch.randn(*s, dtype=torch.bfloat16) * 0.05)(DE, C) * (1.0 / max(1.0, DE) ** 0.5)), 'cg': _w(cg), 'w_mix': _w((lambda *s: torch.randn(*s, dtype=torch.bfloat16) * 0.05)(C, C) * (1.0 / max(1.0, C) ** 0.5))}

def reference(x, src, dst, Y, edge_feat, w_rad, cg, w_mix):
    N, C, M = (x.shape[0], x.shape[1], x.shape[2])
    R = _silu(edge_feat @ w_rad)
    xs = x[src]
    tp = torch.einsum('eci,ef,ifo->eco', xs, Y, cg)
    msg = R[:, :, None] * tp
    agg = _segment_sum(msg.reshape(-1, C * M), dst, N).reshape(N, C, M)
    return torch.einsum('ncm,cd->ndm', agg, w_mix)
```

```cpp
#include <cuda_runtime.h>
#include <cuda.h>
#include <cuda_bf16.h>
#include <stdint.h>

namespace {

constexpr int NT = 384;
constexpr int NWARP = NT / 32;
constexpr int MAXCTA = 132;
constexpr int SFAST = 80;
constexpr int SMAX = 96;
constexpr int EPC_MAX = 3072;
constexpr int RND = 9;
constexpr int NB = 96;
constexpr int GCAP = 800;
constexpr int JCAP = NWARP * RND * 8 + 8;
constexpr int RND0 = 7;
constexpr uint32_t TAGM = 0xfe00001fu;
constexpr int NST = 5;
constexpr uint32_t F0_COUNT = 33;
constexpr int SPIN_LIMIT = 1 << 22;

constexpr int XREG = 4 * NST * 2048 + 256;
constexpr int AUX_OFF = 4 * XREG;
constexpr int AUX_ST = 2560, AUX_GR = 640;
constexpr int BAR_F0 = 520, BAR_EM = 536;
constexpr int SY_OFF = AUX_OFF + NST * AUX_ST;
constexpr int SE_OFF = SY_OFF + 4 * GCAP * 4;
constexpr int SH_OFF = SE_OFF + 4 * GCAP * 4;
constexpr int MISC_OFF = SH_OFF + 4 * GCAP * 8;
constexpr int ZERO_OFF = ((MISC_OFF + 1024 + 2047) & ~2047) - 1024;
constexpr int WM_OFF = (SE_OFF + 1023) & ~1023;
constexpr int LD_DST = EPC_MAX * 16, LD_SRC = LD_DST + EPC_MAX * 4, LD_Y = LD_SRC + EPC_MAX * 4;
constexpr int CNT_OFF = LD_Y + EPC_MAX * 8, START_OFF = CNT_OFF + 1024;
constexpr int BCNT_OFF = START_OFF + 1024;
constexpr int BCUM_OFF = BCNT_OFF + 20 * NB * 4;
constexpr int SEG_OFF = BCUM_OFF + 20 * NB * 4;
constexpr int GI_OFF = 0;
struct Misc {
    unsigned long long ldbar[2], wbar;
    int node0, Sc;
    int nq[4];
    int over, dmax;
    uint32_t epoch, ref;
    uint32_t rseg[MAXCTA];
};
constexpr int SMEM_BYTES = ZERO_OFF + 1792;
static_assert(MISC_OFF + (int)sizeof(Misc) <= ZERO_OFF, "layout");
static_assert(SMEM_BYTES <= 227 * 1024, "shared memory");
static_assert(GI_OFF + 20 * JCAP * 4 <= CNT_OFF && SEG_OFF + NWARP * 64 <= AUX_OFF, "tables");
static_assert(WM_OFF + 32768 <= MISC_OFF && SMAX * 2048 <= MISC_OFF, "layout");
static_assert(AUX_OFF % 256 == 0 && NB == 96 && NWARP == 12, "layout");

__device__ __align__(128) uint4 g_staged[(size_t)MAXCTA * EPC_MAX];
__device__ __align__(128) unsigned long long g_table[MAXCTA * 144];
__device__ unsigned int g_epoch[MAXCTA];

__device__ __forceinline__ void mma1688_z(float (&d)[4], uint32_t a0, uint32_t a1, uint32_t b0) {
    asm volatile(
        "mma.sync.aligned.m16n8k8.row.col.f32.bf16.bf16.f32 {%0,%1,%2,%3}, {%4,%5}, {%6}, {%7,%7,%7,%7};"
        : "=f"(d[0]), "=f"(d[1]), "=f"(d[2]), "=f"(d[3])
        : "r"(a0), "r"(a1), "r"(b0), "f"(0.0f));
}
__device__ __forceinline__ uint32_t pack_bf16(float lo, float hi) {
    uint32_t r;
    asm("cvt.rn.bf16x2.f32 %0, %1, %2;" : "=r"(r) : "f"(hi), "f"(lo));
    return r;
}
__device__ __forceinline__ uint32_t half_bf16x2(uint32_t v) {
    uint32_t r;
    asm("mul.bf16x2 %0, %1, %2;" : "=r"(r) : "r"(v), "r"(0x3f003f00u));
    return r;
}
__device__ __forceinline__ uint4 lds128(uint32_t a) {
    uint4 v;
    asm volatile("ld.shared.v4.u32 {%0,%1,%2,%3}, [%4];" : "=r"(v.x), "=r"(v.y), "=r"(v.z), "=r"(v.w) : "r"(a) : "memory");
    return v;
}
__device__ __forceinline__ uint32_t lds32(uint32_t a) {
    uint32_t v;
    asm volatile("ld.shared.u32 %0, [%1];" : "=r"(v) : "r"(a) : "memory");
    return v;
}
__device__ __forceinline__ uint2 lds64(uint32_t a) {
    uint2 v;
    asm volatile("ld.shared.v2.u32 {%0,%1}, [%2];" : "=r"(v.x), "=r"(v.y) : "r"(a) : "memory");
    return v;
}
__device__ __forceinline__ void sts8(uint32_t a, uint32_t v) {
    asm volatile("st.shared.u8 [%0], %1;" ::"r"(a), "r"(v) : "memory");
}
__device__ __forceinline__ void sts64(uint32_t a, uint32_t v0, uint32_t v1) {
    asm volatile("st.shared.v2.u32 [%0], {%1,%2};" ::"r"(a), "r"(v0), "r"(v1) : "memory");
}
__device__ __forceinline__ void bulk_g2s(uint32_t dst, const void* src, uint32_t bytes, uint32_t bar) {
    asm volatile("cp.async.bulk.shared::cluster.global.mbarrier::complete_tx::bytes [%0], [%1], %2, [%3];"
                 ::"r"(dst), "l"(src), "r"(bytes), "r"(bar) : "memory");
}
#define OCT_BYTES "8192"
#define BOX_LINES 8
template <bool FIRST>
__device__ __forceinline__ void fetch_quad(uint32_t dst, uint32_t bar, const uint4& y, uint64_t map) {
    if (FIRST)
        asm volatile("{\n\t.reg .pred P;\n\telect.sync _|P, 0xffffffff;\n\t"
                     "@P mbarrier.arrive.expect_tx.shared::cta.b64 _, [%0], " OCT_BYTES ";\n\t}" ::"r"(bar) : "memory");
    asm volatile("{\n\t.reg .pred P;\n\telect.sync _|P, 0xffffffff;\n\t"
                 "@P cp.async.bulk.tensor.2d.shared::cluster.global.mbarrier::complete_tx::bytes [%0], [%6, {0, %2}], [%1];\n\t"
                 "@P cp.async.bulk.tensor.2d.shared::cluster.global.mbarrier::complete_tx::bytes [%0+%7], [%6, {0, %3}], [%1];\n\t"
                 "@P cp.async.bulk.tensor.2d.shared::cluster.global.mbarrier::complete_tx::bytes [%0+%8], [%6, {0, %4}], [%1];\n\t"
                 "@P cp.async.bulk.tensor.2d.shared::cluster.global.mbarrier::complete_tx::bytes [%0+%9], [%6, {0, %5}], [%1];\n\t}"
                 ::"r"(dst), "r"(bar), "r"(y.x), "r"(y.y), "r"(y.z), "r"(y.w), "l"(map), "n"(XREG), "n"(2 * XREG), "n"(3 * XREG)
                 : "memory");
}
__device__ __forceinline__ void mbar_arrive_expect_tx(uint32_t bar, uint32_t bytes) {
    asm volatile("mbarrier.arrive.expect_tx.shared::cta.b64 _, [%0], %1;" ::"r"(bar), "r"(bytes) : "memory");
}
__device__ __forceinline__ void mbar_arrive_one(uint32_t bar) {
    asm volatile("{\n\t.reg .pred P;\n\telect.sync _|P, 0xffffffff;\n\t@P mbarrier.arrive.shared::cta.b64 _, [%0];\n\t}" ::"r"(bar) : "memory");
}
__device__ __forceinline__ void cp_async_arrive(uint32_t bar) {
    asm volatile("cp.async.mbarrier.arrive.noinc.shared::cta.b64 [%0];" ::"r"(bar) : "memory");
}
__device__ __forceinline__ void mbar_init(uint32_t bar, uint32_t count) {
    asm volatile("mbarrier.init.shared::cta.b64 [%0], %1;" ::"r"(bar), "r"(count) : "memory");
}
__device__ __forceinline__ bool mbar_try(uint32_t bar, uint32_t parity) {
    uint32_t ok;
    asm volatile("{\n\t.reg .pred p;\n\tmbarrier.try_wait.parity.shared::cta.b64 p, [%1], %2;\n\tselp.u32 %0, 1, 0, p;\n\t}"
                 : "=r"(ok) : "r"(bar), "r"(parity) : "memory");
    return ok;
}
__device__ __forceinline__ void mbar_wait(uint32_t bar, uint32_t parity) {
    if (mbar_try(bar, parity)) return;
#pragma unroll 1
    for (int it = 0; it < SPIN_LIMIT; it++)
        if (mbar_try(bar, parity)) return;
    __trap();
}
__device__ __forceinline__ uint32_t clock_lo() {
    uint32_t v;
    asm volatile("mov.u32 %0, %%clock;" : "=r"(v));
    return v;
}
__device__ __forceinline__ uint32_t global_ticks() {
    uint32_t v;
    asm volatile("mov.u32 %0, %%globaltimer_lo;" : "=r"(v));
    return v >> 5;
}

#define TBL(snd, own) ((snd) * 144 + (own))
__device__ __forceinline__ void prefetch_line(const void* p) { asm volatile("prefetch.global.L2 [%0];" ::"l"(p)); }
__device__ __forceinline__ uint4 ld_entry(const uint4* p) {
    uint4 e;
    asm volatile("ld.relaxed.gpu.global.v4.u32 {%0,%1,%2,%3}, [%4];" : "=r"(e.x), "=r"(e.y), "=r"(e.z), "=r"(e.w) : "l"(p) : "memory");
    return e;
}
__device__ __forceinline__ uint4 wait_entry(const uint4* p, uint4 e, uint32_t tag) {
    int it = 0;
    while (((e.y ^ tag) & TAGM) != 0u) {
        if (++it > SPIN_LIMIT) __trap();
        e = ld_entry(p);
    }
    return e;
}
__device__ __forceinline__ uint32_t ldg_u16(const void* p) {
    unsigned short v;
    asm volatile("ld.global.nc.u16 %0, [%1];" : "=h"(v) : "l"(p));
    return v;
}
__device__ __forceinline__ uint32_t ldg_u32(const void* p) {
    uint32_t v;
    asm volatile("ld.global.nc.u32 %0, [%1];" : "=r"(v) : "l"(p));
    return v;
}
__device__ __forceinline__ void stg64_if(bool p, void* a, uint32_t v0, uint32_t v1) {
    asm volatile("{\n\t.reg .pred P;\n\tsetp.ne.u32 P, %0, 0;\n\t@P st.global.v2.u32 [%1], {%2,%3};\n\t}"
                 ::"r"((uint32_t)p), "l"(a), "r"(v0), "r"(v1) : "memory");
}
__device__ __forceinline__ float bf_lo(uint32_t v) { return __uint_as_float(v << 16); }
__device__ __forceinline__ float bf_hi(uint32_t v) { return __uint_as_float(v & 0xffff0000u); }

#define F8(o) "+f"(d[o]), "+f"(d[o + 1]), "+f"(d[o + 2]), "+f"(d[o + 3]), "+f"(d[o + 4]), "+f"(d[o + 5]), "+f"(d[o + 6]), "+f"(d[o + 7])
__device__ __forceinline__ void wgmma_n80(float (&d)[40], uint64_t a, uint64_t b, uint32_t acc) {
    asm volatile("{\n\t.reg .pred P;\n\tsetp.ne.u32 P, %42, 0;\n\t"
                 "wgmma.mma_async.sync.aligned.m64n80k16.f32.bf16.bf16 "
                 "{%0,%1,%2,%3,%4,%5,%6,%7,%8,%9,%10,%11,%12,%13,%14,%15,%16,%17,%18,%19,"
                 "%20,%21,%22,%23,%24,%25,%26,%27,%28,%29,%30,%31,%32,%33,%34,%35,%36,%37,%38,%39}, %40, %41, P, 1, 1, 1, 0;\n\t}"
                 : F8(0), F8(8), F8(16), F8(24), F8(32) : "l"(a), "l"(b), "r"(acc));
}

__device__ __noinline__ void slow_cta(unsigned char* smem, const char* x, const char* ef, const __nv_bfloat16* w_rad,
                                      const __nv_bfloat16* cg, const __nv_bfloat16* w_mix, uint32_t* out, int node0, int Sc,
                                      uint32_t tag) {
    float* agg = reinterpret_cast<float*>(smem);
    Misc& ms = *reinterpret_cast<Misc*>(smem + MISC_OFF);
    const int tid = threadIdx.x, lane = tid & 31, warp = tid >> 5;
    for (int i = tid; i < Sc * 512; i += NT) agg[i] = 0.f;
    if (tid < (int)gridDim.x) {
        uint32_t v;
        asm volatile("ld.relaxed.gpu.global.u32 %0, [%1];" : "=r"(v) : "l"(&g_table[TBL(tid, blockIdx.x)]) : "memory");
        ms.rseg[tid] = v;
    }
    __syncthreads();
    uint2 wr[16];
#pragma unroll
    for (int f = 0; f < 16; f++) wr[f] = *reinterpret_cast<const uint2*>(w_rad + f * 128 + 4 * lane);
    float cgl[4];
#pragma unroll
    for (int f = 0; f < 4; f++) cgl[f] = __bfloat162float(cg[((lane >> 2) & 3) * 16 + f * 4 + (lane & 3)]);
    for (int s = 0; s < (int)gridDim.x; s++) {
        const int cn = ms.rseg[s] & 0xffffu;
        const uint4* p = g_staged + s * EPC_MAX + (ms.rseg[s] >> 16);
        for (int i = (warp + s) % NWARP; i < cn; i += NWARP) {
            const uint4 e = wait_entry(p + i, ld_entry(p + i), tag);
            const uint4* xp = reinterpret_cast<const uint4*>(x + (size_t)(e.x & 0x1fff8u) * 128 + lane * 32);
            const uint4* fp = reinterpret_cast<const uint4*>(ef + (e.y & ~TAGM));
            const uint4 xa = xp[0], xb = xp[1], fa = fp[0], fb = fp[1];
            const uint32_t fv[8] = {fa.x, fa.y, fa.z, fa.w, fb.x, fb.y, fb.z, fb.w};
            const uint32_t xv[8] = {xa.x, xa.y, xa.z, xa.w, xb.x, xb.y, xb.z, xb.w};
            float h[4] = {0.f, 0.f, 0.f, 0.f};
#pragma unroll
            for (int f = 0; f < 16; f++) {
                const float v = (f & 1) ? bf_hi(fv[f >> 1]) : bf_lo(fv[f >> 1]);
                h[0] += v * bf_lo(wr[f].x); h[1] += v * bf_hi(wr[f].x); h[2] += v * bf_lo(wr[f].y); h[3] += v * bf_hi(wr[f].y);
            }
            const float wl = bf_lo(e.z) * cgl[0] + bf_hi(e.z) * cgl[1] + bf_lo(e.w) * cgl[2] + bf_hi(e.w) * cgl[3];
            const uint32_t tile = ((e.x >> 17) & 0xfffu) / NB;
            float* ap = agg + ((tile >> 2) * 16 + (e.x & 3u) * 4 + (tile & 3)) * 512 + lane * 16;
#pragma unroll
            for (int o = 0; o < 4; o++) {
                const float w0 = __shfl_sync(0xffffffffu, wl, o), w1 = __shfl_sync(0xffffffffu, wl, 4 + o);
                const float w2 = __shfl_sync(0xffffffffu, wl, 8 + o), w3 = __shfl_sync(0xffffffffu, wl, 12 + o);
#pragma unroll
                for (int k = 0; k < 4; k++) {
                    const float tp = bf_lo(xv[2 * k]) * w0 + bf_hi(xv[2 * k]) * w1 + bf_lo(xv[2 * k + 1]) * w2 + bf_hi(xv[2 * k + 1]) * w3;
                    atomicAdd(ap + k * 4 + o, tp * (h[k] / (1.f + __expf(-h[k]))));
                }
            }
        }
    }
    __syncthreads();
    for (int n = tid >> 7; n < Sc; n += NT / 128) {
        const int d = tid & 127;
        float o[4] = {0.f, 0.f, 0.f, 0.f};
        for (int c = 0; c < 128; c++) {
            const float4 a = *reinterpret_cast<const float4*>(agg + n * 512 + c * 4);
            const float w = __bfloat162float(w_mix[c * 128 + d]);
            o[0] += a.x * w; o[1] += a.y * w; o[2] += a.z * w; o[3] += a.w * w;
        }
        *reinterpret_cast<uint2*>(out + (size_t)(node0 + n) * 256 + d * 2) = make_uint2(pack_bf16(o[0], o[1]), pack_bf16(o[2], o[3]));
    }
}

__global__ void __launch_bounds__(NT, 1)
tfn_kernel(const __grid_constant__ CUtensorMap xmap, const char* __restrict__ x, const int* __restrict__ src,
           const int* __restrict__ dst, const uint2* __restrict__ Y, const char* __restrict__ ef,
           const __nv_bfloat16* __restrict__ w_rad, const __nv_bfloat16* __restrict__ cg,
           const __nv_bfloat16* __restrict__ w_mix, uint32_t* __restrict__ out, int N, int E, int S, int EPC,
           uint32_t magicS, uint32_t magicB, uint32_t zero, uint32_t pace, int lead, int gap, int slp) {
    extern __shared__ __align__(1024) unsigned char smem[];
    Misc& ms = *reinterpret_cast<Misc*>(smem + MISC_OFF);
    int* const cnt = reinterpret_cast<int*>(smem + CNT_OFF);
    int* const start = reinterpret_cast<int*>(smem + START_OFF);
    uint32_t* const bcnt = reinterpret_cast<uint32_t*>(smem + BCNT_OFF);
    uint32_t* const bcum = reinterpret_cast<uint32_t*>(smem + BCUM_OFF);
    uint32_t* const gi = reinterpret_cast<uint32_t*>(smem + GI_OFF);
    const int tid = threadIdx.x;
    const int lane = tid & 31, warp = __shfl_sync(0xffffffffu, tid >> 5, 0);
    const int c = blockIdx.x;
    const int numCTA = gridDim.x;
    const int node0 = c * S;
    const int Sc = max(0, min(S, N - node0));
    const uint32_t sb = (uint32_t)__cvta_generic_to_shared(smem);

    const int eb = c * EPC;
    const int ne = max(0, min(EPC, E - eb));
    const uint32_t ldbar0 = sb + MISC_OFF, ldbar1 = ldbar0 + 8, wbar = ldbar0 + 16;
    if (tid == NT - 64) {
        mbar_init(ldbar0, 1);
        mbar_init(ldbar1, 1);
        asm volatile("fence.proxy.async.shared::cta;" ::: "memory");
        const uint32_t n4 = ne & ~3;
        mbar_arrive_expect_tx(ldbar0, n4 * 4);
        if (n4) bulk_g2s(sb + LD_DST, dst + eb, n4 * 4, ldbar0);
        mbar_arrive_expect_tx(ldbar1, n4 * 12);
        if (n4) {
            bulk_g2s(sb + LD_SRC, src + eb, n4 * 4, ldbar1);
            bulk_g2s(sb + LD_Y, Y + eb, n4 * 8, ldbar1);
        }
        asm volatile("prefetch.tensormap [%0];" ::"l"(&xmap) : "memory");
    }
    int d8[8], s8[8];
    uint2 y8[8];
    bool full4[2];
#pragma unroll
    for (int h = 0; h < 2; h++) {
        const int i0 = 4 * (tid + h * NT);
        full4[h] = i0 + 3 < ne;
#pragma unroll
        for (int k = 0; k < 4; k++) { d8[4 * h + k] = -1; s8[4 * h + k] = 0; y8[4 * h + k] = make_uint2(0u, 0u); }
        if (!full4[h] && i0 < ne) {
#pragma unroll
            for (int k = 0; k < 3; k++)
                if (i0 + k < ne) {
                    d8[4 * h + k] = __ldg(dst + eb + i0 + k);
                    s8[4 * h + k] = __ldg(src + eb + i0 + k);
                    y8[4 * h + k] = __ldg(Y + eb + i0 + k);
                }
        }
    }
    uint32_t ep0 = 0;
    if (tid == NT - 1) asm volatile("ld.relaxed.gpu.global.u32 %0, [%1];" : "=r"(ep0) : "l"(&g_epoch[c]) : "memory");
    uint32_t cgr[4] = {0u, 0u, 0u, 0u};
    if (warp >= 8 && (lane & 3) < 2) {
        const unsigned short* cu = reinterpret_cast<const unsigned short*>(cg) + ((lane >> 2) & 3) * 16 + (lane & 3) * 8 + (lane >> 4);
        cgr[0] = ldg_u16(cu); cgr[1] = ldg_u16(cu + 4); cgr[2] = ldg_u16(cu + 2); cgr[3] = ldg_u16(cu + 6);
    }
    if (warp == 7) {
        for (int i = c + lane * numCTA; i < 32 + 256; i += 32 * numCTA)
            prefetch_line(i < 32 ? (const char*)w_rad + i * 128 : (const char*)w_mix + (i - 32) * 128);
    }
    if (tid < MAXCTA) cnt[tid] = 0;
#pragma unroll
    for (int k = 0; k < 5; k++) bcnt[tid + k * NT] = 0u;
    if (tid < 224) reinterpret_cast<uint2*>(smem + ZERO_OFF)[tid] = make_uint2(0u, 0u);
    if (tid >= 160 && tid < 320) {
        const int i = tid - 160;
        *reinterpret_cast<uint32_t*>(smem + AUX_OFF + (i >> 5) * AUX_ST + ((i >> 3) & 3) * AUX_GR + 512 + (i & 7) * 16) =
            (i >> 5) == NST - 1 ? (uint32_t)(1 - NST) << 24 : 1u << 24;
    }
    if (lane < NST && warp < 8) {
        const int k = warp >> 2;
        mbar_init(sb + AUX_OFF + lane * AUX_ST + (warp & 3) * AUX_GR + BAR_F0 + 16 * k, k == 0 ? F0_COUNT : 2u);
    }
    if (tid == 330) { mbar_init(wbar, 128); ms.node0 = node0; ms.Sc = Sc; ms.over = S > SFAST; ms.dmax = -32768; ms.ref = global_ticks(); }
    __syncthreads();
    const uint32_t cgb0 = cgr[0] | (cgr[1] << 16), cgb1 = cgr[2] | (cgr[3] << 16);
    mbar_wait(ldbar0, 0);
#pragma unroll
    for (int h = 0; h < 2; h++)
        if (full4[h]) {
            const uint4 v = lds128(sb + LD_DST + (tid + h * NT) * 16);
            d8[4 * h] = (int)v.x; d8[4 * h + 1] = (int)v.y; d8[4 * h + 2] = (int)v.z; d8[4 * h + 3] = (int)v.w;
        }
    int bin[8], pos[8];
#pragma unroll
    for (int k = 0; k < 8; k++) {
        bin[k] = (int)__umulhi((uint32_t)d8[k], magicS);
        if (d8[k] >= 0) pos[k] = atomicAdd(&cnt[bin[k]], 1);
    }
    if (tid == NT - 1) {
        ms.epoch = ep0 + 1u;
        g_epoch[c] = ep0 + 1u;
    }
    __syncthreads();
    const uint32_t epoch = ms.epoch;
    if (warp < 5) {
        int pre = 0;
#pragma unroll
        for (int k = 0; k < 4; k++)
            if (k < warp) pre += cnt[lane + 32 * k];
        const int v = tid < numCTA ? cnt[tid] : 0;
        int incl = v;
#pragma unroll
        for (int o = 1; o < 32; o <<= 1) {
            int t_ = __shfl_up_sync(0xffffffffu, incl, o);
            if (lane >= o) incl += t_;
        }
        const int ex = __reduce_add_sync(0xffffffffu, pre) + incl - v;
        if (tid < MAXCTA) start[tid] = ex;
    }
    uint32_t w8[8];
#pragma unroll
    for (int k = 0; k < 8; k++) {
        const uint32_t dl = (uint32_t)(d8[k] - bin[k] * S);
        w8[k] = (((dl >> 2) & 0x1cu) | (dl & 3u)) * (NB << 17) | (((dl << 28) & 0xc0000000u) ^ (dl << 31)) | ((dl >> 2) & 3u);
        asm volatile("" : "+r"(w8[k]));
    }
    mbar_wait(ldbar1, 0);
#pragma unroll
    for (int h = 0; h < 2; h++)
        if (full4[h]) {
            const int i = tid + h * NT;
            const uint4 v = lds128(sb + LD_SRC + i * 16), ya = lds128(sb + LD_Y + i * 32), yb = lds128(sb + LD_Y + i * 32 + 16);
            s8[4 * h] = (int)v.x; s8[4 * h + 1] = (int)v.y; s8[4 * h + 2] = (int)v.z; s8[4 * h + 3] = (int)v.w;
            y8[4 * h] = make_uint2(ya.x, ya.y); y8[4 * h + 1] = make_uint2(ya.z, ya.w);
            y8[4 * h + 2] = make_uint2(yb.x, yb.y); y8[4 * h + 3] = make_uint2(yb.z, yb.w);
        }
#pragma unroll
    for (int k = 0; k < 8; k++) {
        w8[k] += (uint32_t)s8[k] * 8u + (__umulhi((uint32_t)s8[k], magicB) << 17);
        asm volatile("" : "+r"(w8[k]));
    }
    const uint32_t tag = (epoch & 31u) | (epoch << 20 & 0xfe000000u);
    const uint32_t e0 = (uint32_t)(eb + 4 * tid) * 32u + tag;
    __syncthreads();
    uint4* stg = reinterpret_cast<uint4*>(smem);
#pragma unroll
    for (int k = 0; k < 8; k++)
        if (d8[k] >= 0) stg[start[bin[k]] + pos[k]] = make_uint4(w8[k], e0 + ((k >> 2) * 4 * NT + (k & 3)) * 32, y8[k].x, y8[k].y);
    asm volatile("fence.proxy.async.shared::cta;" ::: "memory");
    __syncthreads();
    if (warp == NWARP - 1) {
        if (lane == 0 && ne > 0) {
            asm volatile("cp.async.bulk.global.shared::cta.bulk_group [%0], [%1], %2;" ::"l"(g_staged + (size_t)c * EPC_MAX),
                         "r"(sb), "r"(ne * 16) : "memory");
            asm volatile("cp.async.bulk.commit_group;" ::: "memory");
        }
        uint32_t lo[5];
#pragma unroll
        for (int k = 0; k < 5; k++) lo[k] = (lds32(sb + START_OFF + (lane + 32 * k) * 4) << 16) | lds32(sb + CNT_OFF + (lane + 32 * k) * 4);
        unsigned long long* tp = g_table + TBL(c, lane);
        asm volatile("cp.async.bulk.wait_group 0;" ::: "memory");
        __syncwarp();
        const uint32_t hi = (epoch << 16) | (global_ticks() & 0xffffu);
#pragma unroll
        for (int k = 0; k < 5; k++)
            asm volatile("{\n\t.reg .pred P;\n\t.reg .b64 v;\n\tsetp.lt.s32 P, %0, %1;\n\tmov.b64 v, {%3,%4};\n\t@P st.relaxed.gpu.global.b64 [%2], v;\n\t}"
                         ::"r"(lane + 32 * k), "r"(numCTA), "l"(tp + 32 * k), "r"(lo[k]), "r"(hi) : "memory");
    }

    uint4 ent[RND];
    uint32_t rk[RND];
    int tot;
    {
        uint32_t sv = 0, ts = ms.ref;
        {
            const bool mine = warp + NWARP * lane < numCTA;
            const unsigned long long* tp = g_table + TBL(warp + NWARP * lane, c);
            bool ok;
            int it = 0;
            do {
                unsigned long long v = ((unsigned long long)epoch << 48) | ((unsigned long long)(ts & 0xffffu) << 32);
                if (mine) asm volatile("ld.relaxed.gpu.global.u64 %0, [%1];" : "=l"(v) : "l"(tp) : "memory");
                ok = __all_sync(0xffffffffu, (uint32_t)(v >> 48) == (epoch & 0xffffu));
                sv = (uint32_t)v;
                ts = (uint32_t)(v >> 32);
            } while (!ok && ++it < SPIN_LIMIT);
            if (!ok) __trap();
        }
        int incl = (int)(sv & 0xffffu);
#pragma unroll
        for (int o = 1; o < 16; o <<= 1) {
            int t_ = __shfl_up_sync(0xffffffffu, incl, o);
            if (lane >= o) incl += t_;
        }
        tot = __shfl_sync(0xffffffffu, incl, 15);
        const bool some = (sv & 0xffffu) != 0u;
        const uint32_t seg_b = sb + SEG_OFF + warp * 64;
        if (some)
            asm volatile("st.shared.u32 [%0], %1;" ::"r"(seg_b + 4 * __popc(__ballot_sync(__activemask(), true) & ((1u << lane) - 1u))),
                         "r"((warp + NWARP * lane) * EPC_MAX + (int)(sv >> 16) - incl + (int)(sv & 0xffffu)) : "memory");
        __syncwarp();
        if (!some) incl = -1;
        const uint32_t le = (2u << lane) - 1u;
        uint32_t sg = seg_b;
        int gp[RND];
        auto load = [&](int r) {
            uint32_t bit;
            asm("shl.b32 %0, 1, %1;" : "=r"(bit) : "r"(incl - 32 * r));
            const uint32_t ends = __reduce_or_sync(0xffffffffu, bit);
            gp[r] = lane + 32 * r + (int)lds32(sg + 4 * __popc(ends & le));
            sg += 4 * __popc(ends);
            if (lane + 32 * r < tot) ent[r] = ld_entry(g_staged + gp[r]);
        };
#pragma unroll
        for (int r = 0; r < RND; r++) ent[r].y = tag;
#pragma unroll
        for (int r = 0; r < RND0; r++) load(r);
        if (tot > 32 * RND0) {
#pragma unroll
            for (int r = RND0; r < RND; r++) load(r);
        }
        const int dm = __reduce_max_sync(0xffffffffu, (int)(short)(ts - ms.ref));
        if (lane == 0) {
            atomicMax(&ms.dmax, dm);
            if (tot > 32 * RND) ms.over = 1;
        }
        uint32_t stale = 0;
#pragma unroll
        for (int r = 0; r < RND; r++) stale |= ent[r].y ^ tag;
        if (stale & TAGM) {
#pragma unroll
            for (int r = 0; r < RND; r++)
                if (lane + 32 * r < tot) ent[r] = wait_entry(g_staged + gp[r], ent[r], tag);
        }
#pragma unroll
        for (int r = 0; r < RND; r++)
            if (lane + 32 * r < tot) rk[r] = atomicAdd(&bcnt[(ent[r].x >> 17) & 0xfffu], 1u);
    }
    __syncthreads();
    {
        const int grp = warp & 3, u = warp >> 2;
        uint32_t v[3], incl[3], lo[3], hi[3], tt[3];
#pragma unroll
        for (int p = 0; p < 3; p++) {
            uint32_t a[3];
#pragma unroll
            for (int i = 0; i < 3; i++) {
                a[i] = bcnt[(grp + 8 * p) * NB + 32 * i + lane];
                if (p < 2) a[i] += bcnt[(grp + 8 * p + 4) * NB + 32 * i + lane] << 16;
            }
            v[p] = u == 0 ? a[0] : (u == 1 ? a[1] : a[2]);
            incl[p] = v[p];
            lo[p] = __reduce_add_sync(0xffffffffu, u == 0 ? 0u : (u == 1 ? a[0] : a[0] + a[1]));
            tt[p] = __reduce_add_sync(0xffffffffu, a[0] + a[1] + a[2]);
        }
#pragma unroll
        for (int o = 1; o < 32; o <<= 1)
#pragma unroll
            for (int p = 0; p < 3; p++) {
                const uint32_t t_ = __shfl_up_sync(0xffffffffu, incl[p], o);
                if (lane >= o) incl[p] += t_;
            }
        uint32_t all = 0, nq = 0;
#pragma unroll
        for (int p = 0; p < 3; p++) {
            const uint32_t up = (tt[p] + 0x30003u) & 0xfffcfffcu;
            nq += up >> 2;
            tt[p] = up - tt[p];
            incl[p] += lo[p] + tt[p];
            v[p] = incl[p] - v[p];
            lo[p] = warp < 4 && lane == 0 ? 0u : ((v[p] + 0x10001u) >> 2) & 0x3fff3fffu;
            hi[p] = ((incl[p] + 0x10001u) >> 2) & 0x3fff3fffu;
            all += lo[p];
        }
        nq = (nq & 0xffffu) + (nq >> 16);
        uint32_t run = (all & 0xffffu) + (all >> 16) + (nq & 1u) + grp * (GCAP / 4);
#pragma unroll
        for (int i = 0; i < 5; i++) {
            const uint32_t l = (i & 1) ? lo[i >> 1] >> 16 : lo[i >> 1] & 0xffffu, h = (i & 1) ? hi[i >> 1] >> 16 : hi[i >> 1] & 0xffffu;
            const uint32_t tb = (grp + 4 * i) * JCAP;
            bcum[(grp + 4 * i) * NB + 32 * u + lane] = ((i & 1) ? v[i >> 1] >> 16 : v[i >> 1] & 0xffffu) + 4 * tb;
            if (l < h) gi[tb + l] = run * 16u + ((uint32_t)i << 27);
            if (l + 1 < h) {
#pragma unroll 1
                for (uint32_t j = l + 1; j < h; j++) gi[tb + j] = (run + j - l) * 16u + ((uint32_t)i << 27);
            }
            run += h - l;
        }
        if (warp < 4 && lane == 0) {
            ms.nq[grp] = (int)nq;
            if (4 * nq + 12 > GCAP) ms.over = 1;
        }
    }
    __syncthreads();
    if (__shfl_sync(0xffffffffu, ms.over + (int)(lane & zero), 0) != 0) {
        slow_cta(smem, x, ef, w_rad, cg, w_mix, out, node0, Sc, tag);
        return;
    }
    {
        auto put = [&](uint32_t p4, uint32_t y, uint32_t e, uint32_t h0, uint32_t h1) {
            *reinterpret_cast<uint32_t*>(smem + SY_OFF + p4) = y;
            *reinterpret_cast<uint32_t*>(smem + SE_OFF + p4) = e;
            *reinterpret_cast<uint2*>(smem + SH_OFF + 2 * p4) = make_uint2(h0, h1);
        };
        auto place = [&](int r0, int r1) {
            uint32_t q[RND];
#pragma unroll
            for (int r = r0; r < r1; r++)
                if (lane + 32 * r < tot) rk[r] += bcum[(ent[r].x >> 17) & 0xfffu];
#pragma unroll
            for (int r = r0; r < r1; r++)
                if (lane + 32 * r < tot) q[r] = gi[rk[r] >> 2];
#pragma unroll
            for (int r = r0; r < r1; r++)
                if (lane + 32 * r < tot)
                    put((q[r] & 0xffffu) + (rk[r] & 3u) * 4u, ent[r].x & 0x1fff8u,
                        (ent[r].y & 0x1ffffffu) | (q[r] & 0x38000000u) | (ent[r].x & 0xc0000000u) | (ent[r].x << 25 & 0x6000000u),
                        ent[r].z, ent[r].w);
        };
        place(0, RND0);
        if (tot > 32 * RND0) place(RND0, RND);
        const uint32_t py = ((uint32_t)(tid + 53 * c) & 127u) * 8u;
        if (tid < 80) {
            const int tile = tid >> 2;
            if ((tid & 3) < (bcum[tile * NB] & 3u)) {
                const uint32_t q = gi[tile * JCAP];
                put((q & 0xffffu) + (tid & 3) * 4, py, q & 0x38000000u, 0u, 0u);
            }
        } else if (tid >= 96 && tid < 160 && (tid & 15) < 12) {
            const int grp = (tid - 96) >> 4, nq = ms.nq[grp], i = tid & 15;
            if (i < 8) put((grp * GCAP + 4 * ((nq + 1) & ~1) + i) * 4, 0u, 6u << 27, 0u, 0u);
            else if (nq & 1) put((grp * GCAP + i - 8) * 4, py, 0u, 0u, 0u);
        }
    }
    asm volatile("fence.proxy.async.shared::cta;" ::: "memory");
    __syncthreads();

    const int g = lane >> 2, t = lane & 3;
    if (warp < 8) {
        asm volatile("setmaxnreg.inc.sync.aligned.u32 232;");
        const int half = warp >> 2, grp = (warp + half) & 3;
        uint32_t wr[4][4];
#pragma unroll
        for (int j = 0; j < 4; j++) {
            const int dj = (j & 1) + 4 * (j >> 1);
            const __nv_bfloat16* p = w_rad + t * 4 * 128 + 16 * (2 * half + dj) + 2 * (g ^ dj);
#pragma unroll
            for (int i = 0; i < 4; i++) wr[j][i] = ldg_u32(p + i * 128);
        }
#pragma unroll
        for (int j = 0; j < 4; j++) {
            uint32_t h[4];
#pragma unroll
            for (int i = 0; i < 4; i++) h[i] = half_bf16x2(wr[j][i]);
            wr[j][0] = __byte_perm(h[0], h[1], 0x5410);
            wr[j][1] = __byte_perm(h[0], h[1], 0x7632);
            wr[j][2] = __byte_perm(h[2], h[3], 0x5410);
            wr[j][3] = __byte_perm(h[2], h[3], 0x7632);
        }
        const uint32_t az = __shfl_sync(0xffffffffu, sb + ZERO_OFF + (g >> 1) * 512 + t * 32 + (g & 1) * 16, lane);
        uint32_t sb2;
        asm volatile(
            "{\n"
            ".reg .f32 c<160>, h<16>, th<8>, fz;\n"
            ".reg .b32 x<16>, a<4>, r<4>, e<2>, p<80>, mt, mtn, xa, aa, an, ab, ea, tmp, cnt, st, rl, rh;\n"
            ".reg .b16 lo, hi;\n"
            ".reg .pred pk, pm, pw, pe, d0, d1, d2, d3, d4;\n"
            "mov.f32 fz, 0f00000000;\n"
            "mov.f32 c0, fz; mov.f32 c1, fz; mov.f32 c2, fz; mov.f32 c3, fz; mov.f32 c4, fz; mov.f32 c5, fz; mov.f32 c6, fz; mov.f32 c7, fz;\n"
            "mov.f32 c8, fz; mov.f32 c9, fz; mov.f32 c10, fz; mov.f32 c11, fz; mov.f32 c12, fz; mov.f32 c13, fz; mov.f32 c14, fz; mov.f32 c15, fz;\n"
            "mov.f32 c16, fz; mov.f32 c17, fz; mov.f32 c18, fz; mov.f32 c19, fz; mov.f32 c20, fz; mov.f32 c21, fz; mov.f32 c22, fz; mov.f32 c23, fz;\n"
            "mov.f32 c24, fz; mov.f32 c25, fz; mov.f32 c26, fz; mov.f32 c27, fz; mov.f32 c28, fz; mov.f32 c29, fz; mov.f32 c30, fz; mov.f32 c31, fz;\n"
            "mov.f32 c32, fz; mov.f32 c33, fz; mov.f32 c34, fz; mov.f32 c35, fz; mov.f32 c36, fz; mov.f32 c37, fz; mov.f32 c38, fz; mov.f32 c39, fz;\n"
            "mov.f32 c40, fz; mov.f32 c41, fz; mov.f32 c42, fz; mov.f32 c43, fz; mov.f32 c44, fz; mov.f32 c45, fz; mov.f32 c46, fz; mov.f32 c47, fz;\n"
            "mov.f32 c48, fz; mov.f32 c49, fz; mov.f32 c50, fz; mov.f32 c51, fz; mov.f32 c52, fz; mov.f32 c53, fz; mov.f32 c54, fz; mov.f32 c55, fz;\n"
            "mov.f32 c56, fz; mov.f32 c57, fz; mov.f32 c58, fz; mov.f32 c59, fz; mov.f32 c60, fz; mov.f32 c61, fz; mov.f32 c62, fz; mov.f32 c63, fz;\n"
            "mov.f32 c64, fz; mov.f32 c65, fz; mov.f32 c66, fz; mov.f32 c67, fz; mov.f32 c68, fz; mov.f32 c69, fz; mov.f32 c70, fz; mov.f32 c71, fz;\n"
            "mov.f32 c72, fz; mov.f32 c73, fz; mov.f32 c74, fz; mov.f32 c75, fz; mov.f32 c76, fz; mov.f32 c77, fz; mov.f32 c78, fz; mov.f32 c79, fz;\n"
            "mov.f32 c80, fz; mov.f32 c81, fz; mov.f32 c82, fz; mov.f32 c83, fz; mov.f32 c84, fz; mov.f32 c85, fz; mov.f32 c86, fz; mov.f32 c87, fz;\n"
            "mov.f32 c88, fz; mov.f32 c89, fz; mov.f32 c90, fz; mov.f32 c91, fz; mov.f32 c92, fz; mov.f32 c93, fz; mov.f32 c94, fz; mov.f32 c95, fz;\n"
            "mov.f32 c96, fz; mov.f32 c97, fz; mov.f32 c98, fz; mov.f32 c99, fz; mov.f32 c100, fz; mov.f32 c101, fz; mov.f32 c102, fz; mov.f32 c103, fz;\n"
            "mov.f32 c104, fz; mov.f32 c105, fz; mov.f32 c106, fz; mov.f32 c107, fz; mov.f32 c108, fz; mov.f32 c109, fz; mov.f32 c110, fz; mov.f32 c111, fz;\n"
            "mov.f32 c112, fz; mov.f32 c113, fz; mov.f32 c114, fz; mov.f32 c115, fz; mov.f32 c116, fz; mov.f32 c117, fz; mov.f32 c118, fz; mov.f32 c119, fz;\n"
            "mov.f32 c120, fz; mov.f32 c121, fz; mov.f32 c122, fz; mov.f32 c123, fz; mov.f32 c124, fz; mov.f32 c125, fz; mov.f32 c126, fz; mov.f32 c127, fz;\n"
            "mov.f32 c128, fz; mov.f32 c129, fz; mov.f32 c130, fz; mov.f32 c131, fz; mov.f32 c132, fz; mov.f32 c133, fz; mov.f32 c134, fz; mov.f32 c135, fz;\n"
            "mov.f32 c136, fz; mov.f32 c137, fz; mov.f32 c138, fz; mov.f32 c139, fz; mov.f32 c140, fz; mov.f32 c141, fz; mov.f32 c142, fz; mov.f32 c143, fz;\n"
            "mov.f32 c144, fz; mov.f32 c145, fz; mov.f32 c146, fz; mov.f32 c147, fz; mov.f32 c148, fz; mov.f32 c149, fz; mov.f32 c150, fz; mov.f32 c151, fz;\n"
            "mov.f32 c152, fz; mov.f32 c153, fz; mov.f32 c154, fz; mov.f32 c155, fz; mov.f32 c156, fz; mov.f32 c157, fz; mov.f32 c158, fz; mov.f32 c159, fz;\n"
            "mov.b32 x0, 0; mov.b32 x1, 0; mov.b32 x2, 0; mov.b32 x3, 0; mov.b32 x4, 0; mov.b32 x5, 0; mov.b32 x6, 0; mov.b32 x7, 0; mov.b32 x8, 0; mov.b32 x9, 0; mov.b32 x10, 0; mov.b32 x11, 0; mov.b32 x12, 0; mov.b32 x13, 0; mov.b32 x14, 0; mov.b32 x15, 0;\n"
            "mov.b32 a0, 0; mov.b32 a1, 0; mov.b32 a2, 0; mov.b32 a3, 0;\n"
            "elect.sync _|pe, 0xffffffff;\n"
            "mov.b32 xa, %1; mov.b32 aa, %2; mov.b32 ea, %4;\n"
            "mov.u32 cnt, 0; and.b32 tmp, aa, 0xffffff80;\n"
            "S0L: mbarrier.try_wait.parity.shared::cta.b64 pw, [tmp+520], 0; @pw bra.uni S0D;\n"
            "add.u32 cnt, cnt, 1; setp.lt.u32 pk, cnt, 1000000; @pk bra.uni S0L; trap;\n"
            "S0D:\n"
            "ld.shared.v2.u32 {e0,e1}, [ea]; ld.shared.u32 mt, [aa+512];\n"
            "mma.sync.aligned.m16n8k16.row.col.f32.bf16.bf16.f32 {h0,h1,h2,h3}, {%7,%8,%9,%10}, {e0,e1}, {fz,fz,fz,fz};\n"
            "mma.sync.aligned.m16n8k16.row.col.f32.bf16.bf16.f32 {h4,h5,h6,h7}, {%11,%12,%13,%14}, {e0,e1}, {fz,fz,fz,fz};\n"
            "mma.sync.aligned.m16n8k16.row.col.f32.bf16.bf16.f32 {h8,h9,h10,h11}, {%15,%16,%17,%18}, {e0,e1}, {fz,fz,fz,fz};\n"
            "mma.sync.aligned.m16n8k16.row.col.f32.bf16.bf16.f32 {h12,h13,h14,h15}, {%19,%20,%21,%22}, {e0,e1}, {fz,fz,fz,fz};\n"
            "or.b32 a0, e0, mt; and.b32 a0, a0, %5;\n"
            "add.u32 xa, xa, 2048; add.u32 aa, aa, 2560; mov.u32 st, 1;\n"
            "mov.u32 cnt, 0; and.b32 tmp, aa, 0xffffff80;\n"
            "S1L: mbarrier.try_wait.parity.shared::cta.b64 pw, [tmp+520], 0; @pw bra.uni S1D;\n"
            "add.u32 cnt, cnt, 1; setp.lt.u32 pk, cnt, 1000000; @pk bra.uni S1L; trap;\n"
            "S1D:\n"
            "B0_0:\n"
            "xor.b32 tmp, mt, %3; and.b32 tmp, tmp, 1536; setp.eq.u32 pm, tmp, 0; selp.b32 ab, aa, %3, pm;\n"
            "and.b32 tmp, mt, 2048; setp.ne.u32 d0, tmp, 0; and.b32 tmp, mt, 4096; setp.ne.u32 d1, tmp, 0; and.b32 tmp, mt, 8192; setp.ne.u32 d2, tmp, 0;\n"
            "mad.lo.u32 cnt, a0, %5, ea; @pe mbarrier.arrive.relaxed.cta.shared::cta.b64 _, [cnt+280]; mad.lo.s32 ea, st, 2560, ea;\n"
            "ld.shared.u32 mt, [aa+512];\n"
            "mma.sync.aligned.m16n8k16.row.col.f32.bf16.bf16.f32 {c0,c1,c2,c3}, {a0,a1,a2,a3}, {x0,x1}, {c0,c1,c2,c3};\n"
            "mma.sync.aligned.m16n8k16.row.col.f32.bf16.bf16.f32 {c4,c5,c6,c7}, {a0,a1,a2,a3}, {x2,x3}, {c4,c5,c6,c7};\n"
            "ld.shared.v4.u32 {x0,x1,x2,x3}, [xa+0];\n"
            "tanh.approx.f32 th0, h0;\n"
            "tanh.approx.f32 th1, h2;\n"
            "fma.rn.f32 th0, h0, th0, h0;\n"
            "fma.rn.f32 th1, h2, th1, h2;\n"
            "cvt.rn.bf16x2.f32 r0, th1, th0;\n"
            "mma.sync.aligned.m16n8k16.row.col.f32.bf16.bf16.f32 {c8,c9,c10,c11}, {a0,a1,a2,a3}, {x4,x5}, {c8,c9,c10,c11};\n"
            "mma.sync.aligned.m16n8k16.row.col.f32.bf16.bf16.f32 {c12,c13,c14,c15}, {a0,a1,a2,a3}, {x6,x7}, {c12,c13,c14,c15};\n"
            "ld.shared.v4.u32 {x4,x5,x6,x7}, [xa+128];\n"
            "tanh.approx.f32 th2, h4;\n"
            "tanh.approx.f32 th3, h6;\n"
            "fma.rn.f32 th2, h4, th2, h4;\n"
            "fma.rn.f32 th3, h6, th3, h6;\n"
            "cvt.rn.bf16x2.f32 r1, th3, th2;\n"
            "mma.sync.aligned.m16n8k16.row.col.f32.bf16.bf16.f32 {c16,c17,c18,c19}, {a0,a1,a2,a3}, {x8,x9}, {c16,c17,c18,c19};\n"
            "mma.sync.aligned.m16n8k16.row.col.f32.bf16.bf16.f32 {c20,c21,c22,c23}, {a0,a1,a2,a3}, {x10,x11}, {c20,c21,c22,c23};\n"
            "ld.shared.v4.u32 {x8,x9,x10,x11}, [xa+512];\n"
            "tanh.approx.f32 th4, h8;\n"
            "tanh.approx.f32 th5, h10;\n"
            "fma.rn.f32 th4, h8, th4, h8;\n"
            "fma.rn.f32 th5, h10, th5, h10;\n"
            "cvt.rn.bf16x2.f32 r2, th5, th4;\n"
            "mma.sync.aligned.m16n8k16.row.col.f32.bf16.bf16.f32 {c24,c25,c26,c27}, {a0,a1,a2,a3}, {x12,x13}, {c24,c25,c26,c27};\n"
            "mma.sync.aligned.m16n8k16.row.col.f32.bf16.bf16.f32 {c28,c29,c30,c31}, {a0,a1,a2,a3}, {x14,x15}, {c28,c29,c30,c31};\n"
            "ld.shared.v4.u32 {x12,x13,x14,x15}, [xa+640];\n"
            "tanh.approx.f32 th6, h12;\n"
            "tanh.approx.f32 th7, h14;\n"
            "fma.rn.f32 th6, h12, th6, h12;\n"
            "fma.rn.f32 th7, h14, th7, h14;\n"
            "cvt.rn.bf16x2.f32 r3, th7, th6;\n"
            "ld.shared.v4.u32 {a0,a1,a2,a3}, [ab+0];\n"
            "mov.b32 {lo,hi}, r0; mov.b32 rl, {lo,lo}; mov.b32 rh, {hi,hi};\n"
            "mul.bf16x2 x0, x0, rl; mul.bf16x2 x1, x1, rl; mul.bf16x2 x2, x2, rh; mul.bf16x2 x3, x3, rh;\n"
            "mov.b32 {lo,hi}, r1; mov.b32 rl, {lo,lo}; mov.b32 rh, {hi,hi};\n"
            "mul.bf16x2 x4, x4, rl; mul.bf16x2 x5, x5, rl; mul.bf16x2 x6, x6, rh; mul.bf16x2 x7, x7, rh;\n"
            "mov.b32 {lo,hi}, r2; mov.b32 rl, {lo,lo}; mov.b32 rh, {hi,hi};\n"
            "mul.bf16x2 x8, x8, rl; mul.bf16x2 x9, x9, rl; mul.bf16x2 x10, x10, rh; mul.bf16x2 x11, x11, rh;\n"
            "mov.b32 {lo,hi}, r3; mov.b32 rl, {lo,lo}; mov.b32 rh, {hi,hi};\n"
            "mul.bf16x2 x12, x12, rl; mul.bf16x2 x13, x13, rl; mul.bf16x2 x14, x14, rh; mul.bf16x2 x15, x15, rh;\n"
            "@d1 bra.uni L1; @d2 bra.uni B1_4; @d0 bra.uni B1_1; bra.uni B1_0;\n"
            "B0_1:\n"
            "xor.b32 tmp, mt, %3; and.b32 tmp, tmp, 1536; setp.eq.u32 pm, tmp, 0; selp.b32 ab, aa, %3, pm;\n"
            "and.b32 tmp, mt, 2048; setp.ne.u32 d0, tmp, 0; and.b32 tmp, mt, 4096; setp.ne.u32 d1, tmp, 0; and.b32 tmp, mt, 8192; setp.ne.u32 d2, tmp, 0;\n"
            "mad.lo.u32 cnt, a0, %5, ea; @pe mbarrier.arrive.relaxed.cta.shared::cta.b64 _, [cnt+280]; mad.lo.s32 ea, st, 2560, ea;\n"
            "ld.shared.u32 mt, [aa+512];\n"
            "mma.sync.aligned.m16n8k16.row.col.f32.bf16.bf16.f32 {c32,c33,c34,c35}, {a0,a1,a2,a3}, {x0,x1}, {c32,c33,c34,c35};\n"
            "mma.sync.aligned.m16n8k16.row.col.f32.bf16.bf16.f32 {c36,c37,c38,c39}, {a0,a1,a2,a3}, {x2,x3}, {c36,c37,c38,c39};\n"
            "ld.shared.v4.u32 {x0,x1,x2,x3}, [xa+0];\n"
            "tanh.approx.f32 th0, h0;\n"
            "tanh.approx.f32 th1, h2;\n"
            "fma.rn.f32 th0, h0, th0, h0;\n"
            "fma.rn.f32 th1, h2, th1, h2;\n"
            "cvt.rn.bf16x2.f32 r0, th1, th0;\n"
            "mma.sync.aligned.m16n8k16.row.col.f32.bf16.bf16.f32 {c40,c41,c42,c43}, {a0,a1,a2,a3}, {x4,x5}, {c40,c41,c42,c43};\n"
            "mma.sync.aligned.m16n8k16.row.col.f32.bf16.bf16.f32 {c44,c45,c46,c47}, {a0,a1,a2,a3}, {x6,x7}, {c44,c45,c46,c47};\n"
            "ld.shared.v4.u32 {x4,x5,x6,x7}, [xa+128];\n"
            "tanh.approx.f32 th2, h4;\n"
            "tanh.approx.f32 th3, h6;\n"
            "fma.rn.f32 th2, h4, th2, h4;\n"
            "fma.rn.f32 th3, h6, th3, h6;\n"
            "cvt.rn.bf16x2.f32 r1, th3, th2;\n"
            "mma.sync.aligned.m16n8k16.row.col.f32.bf16.bf16.f32 {c48,c49,c50,c51}, {a0,a1,a2,a3}, {x8,x9}, {c48,c49,c50,c51};\n"
            "mma.sync.aligned.m16n8k16.row.col.f32.bf16.bf16.f32 {c52,c53,c54,c55}, {a0,a1,a2,a3}, {x10,x11}, {c52,c53,c54,c55};\n"
            "ld.shared.v4.u32 {x8,x9,x10,x11}, [xa+512];\n"
            "tanh.approx.f32 th4, h8;\n"
            "tanh.approx.f32 th5, h10;\n"
            "fma.rn.f32 th4, h8, th4, h8;\n"
            "fma.rn.f32 th5, h10, th5, h10;\n"
            "cvt.rn.bf16x2.f32 r2, th5, th4;\n"
            "mma.sync.aligned.m16n8k16.row.col.f32.bf16.bf16.f32 {c56,c57,c58,c59}, {a0,a1,a2,a3}, {x12,x13}, {c56,c57,c58,c59};\n"
            "mma.sync.aligned.m16n8k16.row.col.f32.bf16.bf16.f32 {c60,c61,c62,c63}, {a0,a1,a2,a3}, {x14,x15}, {c60,c61,c62,c63};\n"
            "ld.shared.v4.u32 {x12,x13,x14,x15}, [xa+640];\n"
            "tanh.approx.f32 th6, h12;\n"
            "tanh.approx.f32 th7, h14;\n"
            "fma.rn.f32 th6, h12, th6, h12;\n"
            "fma.rn.f32 th7, h14, th7, h14;\n"
            "cvt.rn.bf16x2.f32 r3, th7, th6;\n"
            "ld.shared.v4.u32 {a0,a1,a2,a3}, [ab+0];\n"
            "mov.b32 {lo,hi}, r0; mov.b32 rl, {lo,lo}; mov.b32 rh, {hi,hi};\n"
            "mul.bf16x2 x0, x0, rl; mul.bf16x2 x1, x1, rl; mul.bf16x2 x2, x2, rh; mul.bf16x2 x3, x3, rh;\n"
            "mov.b32 {lo,hi}, r1; mov.b32 rl, {lo,lo}; mov.b32 rh, {hi,hi};\n"
            "mul.bf16x2 x4, x4, rl; mul.bf16x2 x5, x5, rl; mul.bf16x2 x6, x6, rh; mul.bf16x2 x7, x7, rh;\n"
            "mov.b32 {lo,hi}, r2; mov.b32 rl, {lo,lo}; mov.b32 rh, {hi,hi};\n"
            "mul.bf16x2 x8, x8, rl; mul.bf16x2 x9, x9, rl; mul.bf16x2 x10, x10, rh; mul.bf16x2 x11, x11, rh;\n"
            "mov.b32 {lo,hi}, r3; mov.b32 rl, {lo,lo}; mov.b32 rh, {hi,hi};\n"
            "mul.bf16x2 x12, x12, rl; mul.bf16x2 x13, x13, rl; mul.bf16x2 x14, x14, rh; mul.bf16x2 x15, x15, rh;\n"
            "@d1 bra.uni L1; @d2 bra.uni B1_4; @d0 bra.uni B1_1; bra.uni B1_0;\n"
            "L0: @d0 bra.uni B0_3;\n"
            "B0_2:\n"
            "xor.b32 tmp, mt, %3; and.b32 tmp, tmp, 1536; setp.eq.u32 pm, tmp, 0; selp.b32 ab, aa, %3, pm;\n"
            "and.b32 tmp, mt, 2048; setp.ne.u32 d0, tmp, 0; and.b32 tmp, mt, 4096; setp.ne.u32 d1, tmp, 0; and.b32 tmp, mt, 8192; setp.ne.u32 d2, tmp, 0;\n"
            "mad.lo.u32 cnt, a0, %5, ea; @pe mbarrier.arrive.relaxed.cta.shared::cta.b64 _, [cnt+280]; mad.lo.s32 ea, st, 2560, ea;\n"
            "ld.shared.u32 mt, [aa+512];\n"
            "mma.sync.aligned.m16n8k16.row.col.f32.bf16.bf16.f32 {c64,c65,c66,c67}, {a0,a1,a2,a3}, {x0,x1}, {c64,c65,c66,c67};\n"
            "mma.sync.aligned.m16n8k16.row.col.f32.bf16.bf16.f32 {c68,c69,c70,c71}, {a0,a1,a2,a3}, {x2,x3}, {c68,c69,c70,c71};\n"
            "ld.shared.v4.u32 {x0,x1,x2,x3}, [xa+0];\n"
            "tanh.approx.f32 th0, h0;\n"
            "tanh.approx.f32 th1, h2;\n"
            "fma.rn.f32 th0, h0, th0, h0;\n"
            "fma.rn.f32 th1, h2, th1, h2;\n"
            "cvt.rn.bf16x2.f32 r0, th1, th0;\n"
            "mma.sync.aligned.m16n8k16.row.col.f32.bf16.bf16.f32 {c72,c73,c74,c75}, {a0,a1,a2,a3}, {x4,x5}, {c72,c73,c74,c75};\n"
            "mma.sync.aligned.m16n8k16.row.col.f32.bf16.bf16.f32 {c76,c77,c78,c79}, {a0,a1,a2,a3}, {x6,x7}, {c76,c77,c78,c79};\n"
            "ld.shared.v4.u32 {x4,x5,x6,x7}, [xa+128];\n"
            "tanh.approx.f32 th2, h4;\n"
            "tanh.approx.f32 th3, h6;\n"
            "fma.rn.f32 th2, h4, th2, h4;\n"
            "fma.rn.f32 th3, h6, th3, h6;\n"
            "cvt.rn.bf16x2.f32 r1, th3, th2;\n"
            "mma.sync.aligned.m16n8k16.row.col.f32.bf16.bf16.f32 {c80,c81,c82,c83}, {a0,a1,a2,a3}, {x8,x9}, {c80,c81,c82,c83};\n"
            "mma.sync.aligned.m16n8k16.row.col.f32.bf16.bf16.f32 {c84,c85,c86,c87}, {a0,a1,a2,a3}, {x10,x11}, {c84,c85,c86,c87};\n"
            "ld.shared.v4.u32 {x8,x9,x10,x11}, [xa+512];\n"
            "tanh.approx.f32 th4, h8;\n"
            "tanh.approx.f32 th5, h10;\n"
            "fma.rn.f32 th4, h8, th4, h8;\n"
            "fma.rn.f32 th5, h10, th5, h10;\n"
            "cvt.rn.bf16x2.f32 r2, th5, th4;\n"
            "mma.sync.aligned.m16n8k16.row.col.f32.bf16.bf16.f32 {c88,c89,c90,c91}, {a0,a1,a2,a3}, {x12,x13}, {c88,c89,c90,c91};\n"
            "mma.sync.aligned.m16n8k16.row.col.f32.bf16.bf16.f32 {c92,c93,c94,c95}, {a0,a1,a2,a3}, {x14,x15}, {c92,c93,c94,c95};\n"
            "ld.shared.v4.u32 {x12,x13,x14,x15}, [xa+640];\n"
            "tanh.approx.f32 th6, h12;\n"
            "tanh.approx.f32 th7, h14;\n"
            "fma.rn.f32 th6, h12, th6, h12;\n"
            "fma.rn.f32 th7, h14, th7, h14;\n"
            "cvt.rn.bf16x2.f32 r3, th7, th6;\n"
            "ld.shared.v4.u32 {a0,a1,a2,a3}, [ab+0];\n"
            "mov.b32 {lo,hi}, r0; mov.b32 rl, {lo,lo}; mov.b32 rh, {hi,hi};\n"
            "mul.bf16x2 x0, x0, rl; mul.bf16x2 x1, x1, rl; mul.bf16x2 x2, x2, rh; mul.bf16x2 x3, x3, rh;\n"
            "mov.b32 {lo,hi}, r1; mov.b32 rl, {lo,lo}; mov.b32 rh, {hi,hi};\n"
            "mul.bf16x2 x4, x4, rl; mul.bf16x2 x5, x5, rl; mul.bf16x2 x6, x6, rh; mul.bf16x2 x7, x7, rh;\n"
            "mov.b32 {lo,hi}, r2; mov.b32 rl, {lo,lo}; mov.b32 rh, {hi,hi};\n"
            "mul.bf16x2 x8, x8, rl; mul.bf16x2 x9, x9, rl; mul.bf16x2 x10, x10, rh; mul.bf16x2 x11, x11, rh;\n"
            "mov.b32 {lo,hi}, r3; mov.b32 rl, {lo,lo}; mov.b32 rh, {hi,hi};\n"
            "mul.bf16x2 x12, x12, rl; mul.bf16x2 x13, x13, rl; mul.bf16x2 x14, x14, rh; mul.bf16x2 x15, x15, rh;\n"
            "@d1 bra.uni L1; @d2 bra.uni B1_4; @d0 bra.uni B1_1; bra.uni B1_0;\n"
            "B0_3:\n"
            "xor.b32 tmp, mt, %3; and.b32 tmp, tmp, 1536; setp.eq.u32 pm, tmp, 0; selp.b32 ab, aa, %3, pm;\n"
            "and.b32 tmp, mt, 2048; setp.ne.u32 d0, tmp, 0; and.b32 tmp, mt, 4096; setp.ne.u32 d1, tmp, 0; and.b32 tmp, mt, 8192; setp.ne.u32 d2, tmp, 0;\n"
            "mad.lo.u32 cnt, a0, %5, ea; @pe mbarrier.arrive.relaxed.cta.shared::cta.b64 _, [cnt+280]; mad.lo.s32 ea, st, 2560, ea;\n"
            "ld.shared.u32 mt, [aa+512];\n"
            "mma.sync.aligned.m16n8k16.row.col.f32.bf16.bf16.f32 {c96,c97,c98,c99}, {a0,a1,a2,a3}, {x0,x1}, {c96,c97,c98,c99};\n"
            "mma.sync.aligned.m16n8k16.row.col.f32.bf16.bf16.f32 {c100,c101,c102,c103}, {a0,a1,a2,a3}, {x2,x3}, {c100,c101,c102,c103};\n"
            "ld.shared.v4.u32 {x0,x1,x2,x3}, [xa+0];\n"
            "tanh.approx.f32 th0, h0;\n"
            "tanh.approx.f32 th1, h2;\n"
            "fma.rn.f32 th0, h0, th0, h0;\n"
            "fma.rn.f32 th1, h2, th1, h2;\n"
            "cvt.rn.bf16x2.f32 r0, th1, th0;\n"
            "mma.sync.aligned.m16n8k16.row.col.f32.bf16.bf16.f32 {c104,c105,c106,c107}, {a0,a1,a2,a3}, {x4,x5}, {c104,c105,c106,c107};\n"
            "mma.sync.aligned.m16n8k16.row.col.f32.bf16.bf16.f32 {c108,c109,c110,c111}, {a0,a1,a2,a3}, {x6,x7}, {c108,c109,c110,c111};\n"
            "ld.shared.v4.u32 {x4,x5,x6,x7}, [xa+128];\n"
            "tanh.approx.f32 th2, h4;\n"
            "tanh.approx.f32 th3, h6;\n"
            "fma.rn.f32 th2, h4, th2, h4;\n"
            "fma.rn.f32 th3, h6, th3, h6;\n"
            "cvt.rn.bf16x2.f32 r1, th3, th2;\n"
            "mma.sync.aligned.m16n8k16.row.col.f32.bf16.bf16.f32 {c112,c113,c114,c115}, {a0,a1,a2,a3}, {x8,x9}, {c112,c113,c114,c115};\n"
            "mma.sync.aligned.m16n8k16.row.col.f32.bf16.bf16.f32 {c116,c117,c118,c119}, {a0,a1,a2,a3}, {x10,x11}, {c116,c117,c118,c119};\n"
            "ld.shared.v4.u32 {x8,x9,x10,x11}, [xa+512];\n"
            "tanh.approx.f32 th4, h8;\n"
            "tanh.approx.f32 th5, h10;\n"
            "fma.rn.f32 th4, h8, th4, h8;\n"
            "fma.rn.f32 th5, h10, th5, h10;\n"
            "cvt.rn.bf16x2.f32 r2, th5, th4;\n"
            "mma.sync.aligned.m16n8k16.row.col.f32.bf16.bf16.f32 {c120,c121,c122,c123}, {a0,a1,a2,a3}, {x12,x13}, {c120,c121,c122,c123};\n"
            "mma.sync.aligned.m16n8k16.row.col.f32.bf16.bf16.f32 {c124,c125,c126,c127}, {a0,a1,a2,a3}, {x14,x15}, {c124,c125,c126,c127};\n"
            "ld.shared.v4.u32 {x12,x13,x14,x15}, [xa+640];\n"
            "tanh.approx.f32 th6, h12;\n"
            "tanh.approx.f32 th7, h14;\n"
            "fma.rn.f32 th6, h12, th6, h12;\n"
            "fma.rn.f32 th7, h14, th7, h14;\n"
            "cvt.rn.bf16x2.f32 r3, th7, th6;\n"
            "ld.shared.v4.u32 {a0,a1,a2,a3}, [ab+0];\n"
            "mov.b32 {lo,hi}, r0; mov.b32 rl, {lo,lo}; mov.b32 rh, {hi,hi};\n"
            "mul.bf16x2 x0, x0, rl; mul.bf16x2 x1, x1, rl; mul.bf16x2 x2, x2, rh; mul.bf16x2 x3, x3, rh;\n"
            "mov.b32 {lo,hi}, r1; mov.b32 rl, {lo,lo}; mov.b32 rh, {hi,hi};\n"
            "mul.bf16x2 x4, x4, rl; mul.bf16x2 x5, x5, rl; mul.bf16x2 x6, x6, rh; mul.bf16x2 x7, x7, rh;\n"
            "mov.b32 {lo,hi}, r2; mov.b32 rl, {lo,lo}; mov.b32 rh, {hi,hi};\n"
            "mul.bf16x2 x8, x8, rl; mul.bf16x2 x9, x9, rl; mul.bf16x2 x10, x10, rh; mul.bf16x2 x11, x11, rh;\n"
            "mov.b32 {lo,hi}, r3; mov.b32 rl, {lo,lo}; mov.b32 rh, {hi,hi};\n"
            "mul.bf16x2 x12, x12, rl; mul.bf16x2 x13, x13, rl; mul.bf16x2 x14, x14, rh; mul.bf16x2 x15, x15, rh;\n"
            "@d1 bra.uni L1; @d2 bra.uni B1_4; @d0 bra.uni B1_1; bra.uni B1_0;\n"
            "B0_4:\n"
            "xor.b32 tmp, mt, %3; and.b32 tmp, tmp, 1536; setp.eq.u32 pm, tmp, 0; selp.b32 ab, aa, %3, pm;\n"
            "and.b32 tmp, mt, 2048; setp.ne.u32 d0, tmp, 0; and.b32 tmp, mt, 4096; setp.ne.u32 d1, tmp, 0; and.b32 tmp, mt, 8192; setp.ne.u32 d2, tmp, 0;\n"
            "mad.lo.u32 cnt, a0, %5, ea; @pe mbarrier.arrive.relaxed.cta.shared::cta.b64 _, [cnt+280]; mad.lo.s32 ea, st, 2560, ea;\n"
            "ld.shared.u32 mt, [aa+512];\n"
            "mma.sync.aligned.m16n8k16.row.col.f32.bf16.bf16.f32 {c128,c129,c130,c131}, {a0,a1,a2,a3}, {x0,x1}, {c128,c129,c130,c131};\n"
            "mma.sync.aligned.m16n8k16.row.col.f32.bf16.bf16.f32 {c132,c133,c134,c135}, {a0,a1,a2,a3}, {x2,x3}, {c132,c133,c134,c135};\n"
            "ld.shared.v4.u32 {x0,x1,x2,x3}, [xa+0];\n"
            "tanh.approx.f32 th0, h0;\n"
            "tanh.approx.f32 th1, h2;\n"
            "fma.rn.f32 th0, h0, th0, h0;\n"
            "fma.rn.f32 th1, h2, th1, h2;\n"
            "cvt.rn.bf16x2.f32 r0, th1, th0;\n"
            "mma.sync.aligned.m16n8k16.row.col.f32.bf16.bf16.f32 {c136,c137,c138,c139}, {a0,a1,a2,a3}, {x4,x5}, {c136,c137,c138,c139};\n"
            "mma.sync.aligned.m16n8k16.row.col.f32.bf16.bf16.f32 {c140,c141,c142,c143}, {a0,a1,a2,a3}, {x6,x7}, {c140,c141,c142,c143};\n"
            "ld.shared.v4.u32 {x4,x5,x6,x7}, [xa+128];\n"
            "tanh.approx.f32 th2, h4;\n"
            "tanh.approx.f32 th3, h6;\n"
            "fma.rn.f32 th2, h4, th2, h4;\n"
            "fma.rn.f32 th3, h6, th3, h6;\n"
            "cvt.rn.bf16x2.f32 r1, th3, th2;\n"
            "mma.sync.aligned.m16n8k16.row.col.f32.bf16.bf16.f32 {c144,c145,c146,c147}, {a0,a1,a2,a3}, {x8,x9}, {c144,c145,c146,c147};\n"
            "mma.sync.aligned.m16n8k16.row.col.f32.bf16.bf16.f32 {c148,c149,c150,c151}, {a0,a1,a2,a3}, {x10,x11}, {c148,c149,c150,c151};\n"
            "ld.shared.v4.u32 {x8,x9,x10,x11}, [xa+512];\n"
            "tanh.approx.f32 th4, h8;\n"
            "tanh.approx.f32 th5, h10;\n"
            "fma.rn.f32 th4, h8, th4, h8;\n"
            "fma.rn.f32 th5, h10, th5, h10;\n"
            "cvt.rn.bf16x2.f32 r2, th5, th4;\n"
            "mma.sync.aligned.m16n8k16.row.col.f32.bf16.bf16.f32 {c152,c153,c154,c155}, {a0,a1,a2,a3}, {x12,x13}, {c152,c153,c154,c155};\n"
            "mma.sync.aligned.m16n8k16.row.col.f32.bf16.bf16.f32 {c156,c157,c158,c159}, {a0,a1,a2,a3}, {x14,x15}, {c156,c157,c158,c159};\n"
            "ld.shared.v4.u32 {x12,x13,x14,x15}, [xa+640];\n"
            "tanh.approx.f32 th6, h12;\n"
            "tanh.approx.f32 th7, h14;\n"
            "fma.rn.f32 th6, h12, th6, h12;\n"
            "fma.rn.f32 th7, h14, th7, h14;\n"
            "cvt.rn.bf16x2.f32 r3, th7, th6;\n"
            "ld.shared.v4.u32 {a0,a1,a2,a3}, [ab+0];\n"
            "mov.b32 {lo,hi}, r0; mov.b32 rl, {lo,lo}; mov.b32 rh, {hi,hi};\n"
            "mul.bf16x2 x0, x0, rl; mul.bf16x2 x1, x1, rl; mul.bf16x2 x2, x2, rh; mul.bf16x2 x3, x3, rh;\n"
            "mov.b32 {lo,hi}, r1; mov.b32 rl, {lo,lo}; mov.b32 rh, {hi,hi};\n"
            "mul.bf16x2 x4, x4, rl; mul.bf16x2 x5, x5, rl; mul.bf16x2 x6, x6, rh; mul.bf16x2 x7, x7, rh;\n"
            "mov.b32 {lo,hi}, r2; mov.b32 rl, {lo,lo}; mov.b32 rh, {hi,hi};\n"
            "mul.bf16x2 x8, x8, rl; mul.bf16x2 x9, x9, rl; mul.bf16x2 x10, x10, rh; mul.bf16x2 x11, x11, rh;\n"
            "mov.b32 {lo,hi}, r3; mov.b32 rl, {lo,lo}; mov.b32 rh, {hi,hi};\n"
            "mul.bf16x2 x12, x12, rl; mul.bf16x2 x13, x13, rl; mul.bf16x2 x14, x14, rh; mul.bf16x2 x15, x15, rh;\n"
            "@d1 bra.uni L1; @d2 bra.uni B1_4; @d0 bra.uni B1_1; bra.uni B1_0;\n"
            "B1_0:\n"
            "xor.b32 tmp, mt, ea; and.b32 tmp, tmp, 192; setp.eq.u32 pm, tmp, 0; selp.b32 ab, aa, %3, pm;\n"
            "and.b32 tmp, mt, 8; setp.ne.u32 d0, tmp, 0; and.b32 tmp, mt, 16; setp.ne.u32 d1, tmp, 0; and.b32 tmp, mt, 32; setp.ne.u32 d2, tmp, 0;\n"
            "ld.shared.v2.u32 {e0,e1}, [ea];\n"
            "shr.s32 st, mt, 24; mad.lo.s32 aa, st, 2560, aa;\n"
            "mma.sync.aligned.m16n8k16.row.col.f32.bf16.bf16.f32 {c0,c1,c2,c3}, {a0,a1,a2,a3}, {x0,x1}, {c0,c1,c2,c3};\n"
            "mma.sync.aligned.m16n8k16.row.col.f32.bf16.bf16.f32 {c4,c5,c6,c7}, {a0,a1,a2,a3}, {x2,x3}, {c4,c5,c6,c7};\n"
            "ld.shared.v4.u32 {x0,x1,x2,x3}, [xa+1024];\n"
            "tanh.approx.f32 th0, h1;\n"
            "tanh.approx.f32 th1, h3;\n"
            "fma.rn.f32 th0, h1, th0, h1;\n"
            "fma.rn.f32 th1, h3, th1, h3;\n"
            "cvt.rn.bf16x2.f32 r0, th1, th0;\n"
            "mma.sync.aligned.m16n8k16.row.col.f32.bf16.bf16.f32 {h0,h1,h2,h3}, {%7,%8,%9,%10}, {e0,e1}, {fz,fz,fz,fz};\n"
            "mma.sync.aligned.m16n8k16.row.col.f32.bf16.bf16.f32 {c8,c9,c10,c11}, {a0,a1,a2,a3}, {x4,x5}, {c8,c9,c10,c11};\n"
            "mma.sync.aligned.m16n8k16.row.col.f32.bf16.bf16.f32 {c12,c13,c14,c15}, {a0,a1,a2,a3}, {x6,x7}, {c12,c13,c14,c15};\n"
            "ld.shared.v4.u32 {x4,x5,x6,x7}, [xa+1152];\n"
            "tanh.approx.f32 th2, h5;\n"
            "tanh.approx.f32 th3, h7;\n"
            "fma.rn.f32 th2, h5, th2, h5;\n"
            "fma.rn.f32 th3, h7, th3, h7;\n"
            "cvt.rn.bf16x2.f32 r1, th3, th2;\n"
            "mma.sync.aligned.m16n8k16.row.col.f32.bf16.bf16.f32 {h4,h5,h6,h7}, {%11,%12,%13,%14}, {e0,e1}, {fz,fz,fz,fz};\n"
            "mma.sync.aligned.m16n8k16.row.col.f32.bf16.bf16.f32 {c16,c17,c18,c19}, {a0,a1,a2,a3}, {x8,x9}, {c16,c17,c18,c19};\n"
            "mma.sync.aligned.m16n8k16.row.col.f32.bf16.bf16.f32 {c20,c21,c22,c23}, {a0,a1,a2,a3}, {x10,x11}, {c20,c21,c22,c23};\n"
            "ld.shared.v4.u32 {x8,x9,x10,x11}, [xa+1536];\n"
            "tanh.approx.f32 th4, h9;\n"
            "tanh.approx.f32 th5, h11;\n"
            "fma.rn.f32 th4, h9, th4, h9;\n"
            "fma.rn.f32 th5, h11, th5, h11;\n"
            "cvt.rn.bf16x2.f32 r2, th5, th4;\n"
            "mma.sync.aligned.m16n8k16.row.col.f32.bf16.bf16.f32 {h8,h9,h10,h11}, {%15,%16,%17,%18}, {e0,e1}, {fz,fz,fz,fz};\n"
            "mma.sync.aligned.m16n8k16.row.col.f32.bf16.bf16.f32 {c24,c25,c26,c27}, {a0,a1,a2,a3}, {x12,x13}, {c24,c25,c26,c27};\n"
            "mma.sync.aligned.m16n8k16.row.col.f32.bf16.bf16.f32 {c28,c29,c30,c31}, {a0,a1,a2,a3}, {x14,x15}, {c28,c29,c30,c31};\n"
            "ld.shared.v4.u32 {x12,x13,x14,x15}, [xa+1664];\n"
            "tanh.approx.f32 th6, h13;\n"
            "tanh.approx.f32 th7, h15;\n"
            "fma.rn.f32 th6, h13, th6, h13;\n"
            "fma.rn.f32 th7, h15, th7, h15;\n"
            "cvt.rn.bf16x2.f32 r3, th7, th6;\n"
            "mma.sync.aligned.m16n8k16.row.col.f32.bf16.bf16.f32 {h12,h13,h14,h15}, {%19,%20,%21,%22}, {e0,e1}, {fz,fz,fz,fz};\n"
            "ld.shared.v4.u32 {a0,a1,a2,a3}, [ab+128];\n"
            "and.b32 tmp, aa, 0xffffff80; mbarrier.test_wait.parity.shared::cta.b64 pw, [tmp+520], mt;\n"
            "mad.lo.s32 xa, st, 2048, xa;\n"
            "mov.b32 {lo,hi}, r0; mov.b32 rl, {lo,lo}; mov.b32 rh, {hi,hi};\n"
            "mul.bf16x2 x0, x0, rl; mul.bf16x2 x1, x1, rl; mul.bf16x2 x2, x2, rh; mul.bf16x2 x3, x3, rh;\n"
            "mov.b32 {lo,hi}, r1; mov.b32 rl, {lo,lo}; mov.b32 rh, {hi,hi};\n"
            "mul.bf16x2 x4, x4, rl; mul.bf16x2 x5, x5, rl; mul.bf16x2 x6, x6, rh; mul.bf16x2 x7, x7, rh;\n"
            "mov.b32 {lo,hi}, r2; mov.b32 rl, {lo,lo}; mov.b32 rh, {hi,hi};\n"
            "mul.bf16x2 x8, x8, rl; mul.bf16x2 x9, x9, rl; mul.bf16x2 x10, x10, rh; mul.bf16x2 x11, x11, rh;\n"
            "mov.b32 {lo,hi}, r3; mov.b32 rl, {lo,lo}; mov.b32 rh, {hi,hi};\n"
            "mul.bf16x2 x12, x12, rl; mul.bf16x2 x13, x13, rl; mul.bf16x2 x14, x14, rh; mul.bf16x2 x15, x15, rh;\n"
            "@!pw bra.uni W1;\n"
            "@d2 bra.uni B0_4; @d1 bra.uni L0; @d0 bra.uni B0_1; bra.uni B0_0;\n"
            "B1_1:\n"
            "xor.b32 tmp, mt, ea; and.b32 tmp, tmp, 192; setp.eq.u32 pm, tmp, 0; selp.b32 ab, aa, %3, pm;\n"
            "and.b32 tmp, mt, 8; setp.ne.u32 d0, tmp, 0; and.b32 tmp, mt, 16; setp.ne.u32 d1, tmp, 0; and.b32 tmp, mt, 32; setp.ne.u32 d2, tmp, 0;\n"
            "ld.shared.v2.u32 {e0,e1}, [ea];\n"
            "shr.s32 st, mt, 24; mad.lo.s32 aa, st, 2560, aa;\n"
            "mma.sync.aligned.m16n8k16.row.col.f32.bf16.bf16.f32 {c32,c33,c34,c35}, {a0,a1,a2,a3}, {x0,x1}, {c32,c33,c34,c35};\n"
            "mma.sync.aligned.m16n8k16.row.col.f32.bf16.bf16.f32 {c36,c37,c38,c39}, {a0,a1,a2,a3}, {x2,x3}, {c36,c37,c38,c39};\n"
            "ld.shared.v4.u32 {x0,x1,x2,x3}, [xa+1024];\n"
            "tanh.approx.f32 th0, h1;\n"
            "tanh.approx.f32 th1, h3;\n"
            "fma.rn.f32 th0, h1, th0, h1;\n"
            "fma.rn.f32 th1, h3, th1, h3;\n"
            "cvt.rn.bf16x2.f32 r0, th1, th0;\n"
            "mma.sync.aligned.m16n8k16.row.col.f32.bf16.bf16.f32 {h0,h1,h2,h3}, {%7,%8,%9,%10}, {e0,e1}, {fz,fz,fz,fz};\n"
            "mma.sync.aligned.m16n8k16.row.col.f32.bf16.bf16.f32 {c40,c41,c42,c43}, {a0,a1,a2,a3}, {x4,x5}, {c40,c41,c42,c43};\n"
            "mma.sync.aligned.m16n8k16.row.col.f32.bf16.bf16.f32 {c44,c45,c46,c47}, {a0,a1,a2,a3}, {x6,x7}, {c44,c45,c46,c47};\n"
            "ld.shared.v4.u32 {x4,x5,x6,x7}, [xa+1152];\n"
            "tanh.approx.f32 th2, h5;\n"
            "tanh.approx.f32 th3, h7;\n"
            "fma.rn.f32 th2, h5, th2, h5;\n"
            "fma.rn.f32 th3, h7, th3, h7;\n"
            "cvt.rn.bf16x2.f32 r1, th3, th2;\n"
            "mma.sync.aligned.m16n8k16.row.col.f32.bf16.bf16.f32 {h4,h5,h6,h7}, {%11,%12,%13,%14}, {e0,e1}, {fz,fz,fz,fz};\n"
            "mma.sync.aligned.m16n8k16.row.col.f32.bf16.bf16.f32 {c48,c49,c50,c51}, {a0,a1,a2,a3}, {x8,x9}, {c48,c49,c50,c51};\n"
            "mma.sync.aligned.m16n8k16.row.col.f32.bf16.bf16.f32 {c52,c53,c54,c55}, {a0,a1,a2,a3}, {x10,x11}, {c52,c53,c54,c55};\n"
            "ld.shared.v4.u32 {x8,x9,x10,x11}, [xa+1536];\n"
            "tanh.approx.f32 th4, h9;\n"
            "tanh.approx.f32 th5, h11;\n"
            "fma.rn.f32 th4, h9, th4, h9;\n"
            "fma.rn.f32 th5, h11, th5, h11;\n"
            "cvt.rn.bf16x2.f32 r2, th5, th4;\n"
            "mma.sync.aligned.m16n8k16.row.col.f32.bf16.bf16.f32 {h8,h9,h10,h11}, {%15,%16,%17,%18}, {e0,e1}, {fz,fz,fz,fz};\n"
            "mma.sync.aligned.m16n8k16.row.col.f32.bf16.bf16.f32 {c56,c57,c58,c59}, {a0,a1,a2,a3}, {x12,x13}, {c56,c57,c58,c59};\n"
            "mma.sync.aligned.m16n8k16.row.col.f32.bf16.bf16.f32 {c60,c61,c62,c63}, {a0,a1,a2,a3}, {x14,x15}, {c60,c61,c62,c63};\n"
            "ld.shared.v4.u32 {x12,x13,x14,x15}, [xa+1664];\n"
            "tanh.approx.f32 th6, h13;\n"
            "tanh.approx.f32 th7, h15;\n"
            "fma.rn.f32 th6, h13, th6, h13;\n"
            "fma.rn.f32 th7, h15, th7, h15;\n"
            "cvt.rn.bf16x2.f32 r3, th7, th6;\n"
            "mma.sync.aligned.m16n8k16.row.col.f32.bf16.bf16.f32 {h12,h13,h14,h15}, {%19,%20,%21,%22}, {e0,e1}, {fz,fz,fz,fz};\n"
            "ld.shared.v4.u32 {a0,a1,a2,a3}, [ab+128];\n"
            "and.b32 tmp, aa, 0xffffff80; mbarrier.test_wait.parity.shared::cta.b64 pw, [tmp+520], mt;\n"
            "mad.lo.s32 xa, st, 2048, xa;\n"
            "mov.b32 {lo,hi}, r0; mov.b32 rl, {lo,lo}; mov.b32 rh, {hi,hi};\n"
            "mul.bf16x2 x0, x0, rl; mul.bf16x2 x1, x1, rl; mul.bf16x2 x2, x2, rh; mul.bf16x2 x3, x3, rh;\n"
            "mov.b32 {lo,hi}, r1; mov.b32 rl, {lo,lo}; mov.b32 rh, {hi,hi};\n"
            "mul.bf16x2 x4, x4, rl; mul.bf16x2 x5, x5, rl; mul.bf16x2 x6, x6, rh; mul.bf16x2 x7, x7, rh;\n"
            "mov.b32 {lo,hi}, r2; mov.b32 rl, {lo,lo}; mov.b32 rh, {hi,hi};\n"
            "mul.bf16x2 x8, x8, rl; mul.bf16x2 x9, x9, rl; mul.bf16x2 x10, x10, rh; mul.bf16x2 x11, x11, rh;\n"
            "mov.b32 {lo,hi}, r3; mov.b32 rl, {lo,lo}; mov.b32 rh, {hi,hi};\n"
            "mul.bf16x2 x12, x12, rl; mul.bf16x2 x13, x13, rl; mul.bf16x2 x14, x14, rh; mul.bf16x2 x15, x15, rh;\n"
            "@!pw bra.uni W1;\n"
            "@d2 bra.uni B0_4; @d1 bra.uni L0; @d0 bra.uni B0_1; bra.uni B0_0;\n"
            "L1: @d2 bra.uni END; @d0 bra.uni B1_3;\n"
            "B1_2:\n"
            "xor.b32 tmp, mt, ea; and.b32 tmp, tmp, 192; setp.eq.u32 pm, tmp, 0; selp.b32 ab, aa, %3, pm;\n"
            "and.b32 tmp, mt, 8; setp.ne.u32 d0, tmp, 0; and.b32 tmp, mt, 16; setp.ne.u32 d1, tmp, 0; and.b32 tmp, mt, 32; setp.ne.u32 d2, tmp, 0;\n"
            "ld.shared.v2.u32 {e0,e1}, [ea];\n"
            "shr.s32 st, mt, 24; mad.lo.s32 aa, st, 2560, aa;\n"
            "mma.sync.aligned.m16n8k16.row.col.f32.bf16.bf16.f32 {c64,c65,c66,c67}, {a0,a1,a2,a3}, {x0,x1}, {c64,c65,c66,c67};\n"
            "mma.sync.aligned.m16n8k16.row.col.f32.bf16.bf16.f32 {c68,c69,c70,c71}, {a0,a1,a2,a3}, {x2,x3}, {c68,c69,c70,c71};\n"
            "ld.shared.v4.u32 {x0,x1,x2,x3}, [xa+1024];\n"
            "tanh.approx.f32 th0, h1;\n"
            "tanh.approx.f32 th1, h3;\n"
            "fma.rn.f32 th0, h1, th0, h1;\n"
            "fma.rn.f32 th1, h3, th1, h3;\n"
            "cvt.rn.bf16x2.f32 r0, th1, th0;\n"
            "mma.sync.aligned.m16n8k16.row.col.f32.bf16.bf16.f32 {h0,h1,h2,h3}, {%7,%8,%9,%10}, {e0,e1}, {fz,fz,fz,fz};\n"
            "mma.sync.aligned.m16n8k16.row.col.f32.bf16.bf16.f32 {c72,c73,c74,c75}, {a0,a1,a2,a3}, {x4,x5}, {c72,c73,c74,c75};\n"
            "mma.sync.aligned.m16n8k16.row.col.f32.bf16.bf16.f32 {c76,c77,c78,c79}, {a0,a1,a2,a3}, {x6,x7}, {c76,c77,c78,c79};\n"
            "ld.shared.v4.u32 {x4,x5,x6,x7}, [xa+1152];\n"
            "tanh.approx.f32 th2, h5;\n"
            "tanh.approx.f32 th3, h7;\n"
            "fma.rn.f32 th2, h5, th2, h5;\n"
            "fma.rn.f32 th3, h7, th3, h7;\n"
            "cvt.rn.bf16x2.f32 r1, th3, th2;\n"
            "mma.sync.aligned.m16n8k16.row.col.f32.bf16.bf16.f32 {h4,h5,h6,h7}, {%11,%12,%13,%14}, {e0,e1}, {fz,fz,fz,fz};\n"
            "mma.sync.aligned.m16n8k16.row.col.f32.bf16.bf16.f32 {c80,c81,c82,c83}, {a0,a1,a2,a3}, {x8,x9}, {c80,c81,c82,c83};\n"
            "mma.sync.aligned.m16n8k16.row.col.f32.bf16.bf16.f32 {c84,c85,c86,c87}, {a0,a1,a2,a3}, {x10,x11}, {c84,c85,c86,c87};\n"
            "ld.shared.v4.u32 {x8,x9,x10,x11}, [xa+1536];\n"
            "tanh.approx.f32 th4, h9;\n"
            "tanh.approx.f32 th5, h11;\n"
            "fma.rn.f32 th4, h9, th4, h9;\n"
            "fma.rn.f32 th5, h11, th5, h11;\n"
            "cvt.rn.bf16x2.f32 r2, th5, th4;\n"
            "mma.sync.aligned.m16n8k16.row.col.f32.bf16.bf16.f32 {h8,h9,h10,h11}, {%15,%16,%17,%18}, {e0,e1}, {fz,fz,fz,fz};\n"
            "mma.sync.aligned.m16n8k16.row.col.f32.bf16.bf16.f32 {c88,c89,c90,c91}, {a0,a1,a2,a3}, {x12,x13}, {c88,c89,c90,c91};\n"
            "mma.sync.aligned.m16n8k16.row.col.f32.bf16.bf16.f32 {c92,c93,c94,c95}, {a0,a1,a2,a3}, {x14,x15}, {c92,c93,c94,c95};\n"
            "ld.shared.v4.u32 {x12,x13,x14,x15}, [xa+1664];\n"
            "tanh.approx.f32 th6, h13;\n"
            "tanh.approx.f32 th7, h15;\n"
            "fma.rn.f32 th6, h13, th6, h13;\n"
            "fma.rn.f32 th7, h15, th7, h15;\n"
            "cvt.rn.bf16x2.f32 r3, th7, th6;\n"
            "mma.sync.aligned.m16n8k16.row.col.f32.bf16.bf16.f32 {h12,h13,h14,h15}, {%19,%20,%21,%22}, {e0,e1}, {fz,fz,fz,fz};\n"
            "ld.shared.v4.u32 {a0,a1,a2,a3}, [ab+128];\n"
            "and.b32 tmp, aa, 0xffffff80; mbarrier.test_wait.parity.shared::cta.b64 pw, [tmp+520], mt;\n"
            "mad.lo.s32 xa, st, 2048, xa;\n"
            "mov.b32 {lo,hi}, r0; mov.b32 rl, {lo,lo}; mov.b32 rh, {hi,hi};\n"
            "mul.bf16x2 x0, x0, rl; mul.bf16x2 x1, x1, rl; mul.bf16x2 x2, x2, rh; mul.bf16x2 x3, x3, rh;\n"
            "mov.b32 {lo,hi}, r1; mov.b32 rl, {lo,lo}; mov.b32 rh, {hi,hi};\n"
            "mul.bf16x2 x4, x4, rl; mul.bf16x2 x5, x5, rl; mul.bf16x2 x6, x6, rh; mul.bf16x2 x7, x7, rh;\n"
            "mov.b32 {lo,hi}, r2; mov.b32 rl, {lo,lo}; mov.b32 rh, {hi,hi};\n"
            "mul.bf16x2 x8, x8, rl; mul.bf16x2 x9, x9, rl; mul.bf16x2 x10, x10, rh; mul.bf16x2 x11, x11, rh;\n"
            "mov.b32 {lo,hi}, r3; mov.b32 rl, {lo,lo}; mov.b32 rh, {hi,hi};\n"
            "mul.bf16x2 x12, x12, rl; mul.bf16x2 x13, x13, rl; mul.bf16x2 x14, x14, rh; mul.bf16x2 x15, x15, rh;\n"
            "@!pw bra.uni W1;\n"
            "@d2 bra.uni B0_4; @d1 bra.uni L0; @d0 bra.uni B0_1; bra.uni B0_0;\n"
            "B1_3:\n"
            "xor.b32 tmp, mt, ea; and.b32 tmp, tmp, 192; setp.eq.u32 pm, tmp, 0; selp.b32 ab, aa, %3, pm;\n"
            "and.b32 tmp, mt, 8; setp.ne.u32 d0, tmp, 0; and.b32 tmp, mt, 16; setp.ne.u32 d1, tmp, 0; and.b32 tmp, mt, 32; setp.ne.u32 d2, tmp, 0;\n"
            "ld.shared.v2.u32 {e0,e1}, [ea];\n"
            "shr.s32 st, mt, 24; mad.lo.s32 aa, st, 2560, aa;\n"
            "mma.sync.aligned.m16n8k16.row.col.f32.bf16.bf16.f32 {c96,c97,c98,c99}, {a0,a1,a2,a3}, {x0,x1}, {c96,c97,c98,c99};\n"
            "mma.sync.aligned.m16n8k16.row.col.f32.bf16.bf16.f32 {c100,c101,c102,c103}, {a0,a1,a2,a3}, {x2,x3}, {c100,c101,c102,c103};\n"
            "ld.shared.v4.u32 {x0,x1,x2,x3}, [xa+1024];\n"
            "tanh.approx.f32 th0, h1;\n"
            "tanh.approx.f32 th1, h3;\n"
            "fma.rn.f32 th0, h1, th0, h1;\n"
            "fma.rn.f32 th1, h3, th1, h3;\n"
            "cvt.rn.bf16x2.f32 r0, th1, th0;\n"
            "mma.sync.aligned.m16n8k16.row.col.f32.bf16.bf16.f32 {h0,h1,h2,h3}, {%7,%8,%9,%10}, {e0,e1}, {fz,fz,fz,fz};\n"
            "mma.sync.aligned.m16n8k16.row.col.f32.bf16.bf16.f32 {c104,c105,c106,c107}, {a0,a1,a2,a3}, {x4,x5}, {c104,c105,c106,c107};\n"
            "mma.sync.aligned.m16n8k16.row.col.f32.bf16.bf16.f32 {c108,c109,c110,c111}, {a0,a1,a2,a3}, {x6,x7}, {c108,c109,c110,c111};\n"
            "ld.shared.v4.u32 {x4,x5,x6,x7}, [xa+1152];\n"
            "tanh.approx.f32 th2, h5;\n"
            "tanh.approx.f32 th3, h7;\n"
            "fma.rn.f32 th2, h5, th2, h5;\n"
            "fma.rn.f32 th3, h7, th3, h7;\n"
            "cvt.rn.bf16x2.f32 r1, th3, th2;\n"
            "mma.sync.aligned.m16n8k16.row.col.f32.bf16.bf16.f32 {h4,h5,h6,h7}, {%11,%12,%13,%14}, {e0,e1}, {fz,fz,fz,fz};\n"
            "mma.sync.aligned.m16n8k16.row.col.f32.bf16.bf16.f32 {c112,c113,c114,c115}, {a0,a1,a2,a3}, {x8,x9}, {c112,c113,c114,c115};\n"
            "mma.sync.aligned.m16n8k16.row.col.f32.bf16.bf16.f32 {c116,c117,c118,c119}, {a0,a1,a2,a3}, {x10,x11}, {c116,c117,c118,c119};\n"
            "ld.shared.v4.u32 {x8,x9,x10,x11}, [xa+1536];\n"
            "tanh.approx.f32 th4, h9;\n"
            "tanh.approx.f32 th5, h11;\n"
            "fma.rn.f32 th4, h9, th4, h9;\n"
            "fma.rn.f32 th5, h11, th5, h11;\n"
            "cvt.rn.bf16x2.f32 r2, th5, th4;\n"
            "mma.sync.aligned.m16n8k16.row.col.f32.bf16.bf16.f32 {h8,h9,h10,h11}, {%15,%16,%17,%18}, {e0,e1}, {fz,fz,fz,fz};\n"
            "mma.sync.aligned.m16n8k16.row.col.f32.bf16.bf16.f32 {c120,c121,c122,c123}, {a0,a1,a2,a3}, {x12,x13}, {c120,c121,c122,c123};\n"
            "mma.sync.aligned.m16n8k16.row.col.f32.bf16.bf16.f32 {c124,c125,c126,c127}, {a0,a1,a2,a3}, {x14,x15}, {c124,c125,c126,c127};\n"
            "ld.shared.v4.u32 {x12,x13,x14,x15}, [xa+1664];\n"
            "tanh.approx.f32 th6, h13;\n"
            "tanh.approx.f32 th7, h15;\n"
            "fma.rn.f32 th6, h13, th6, h13;\n"
            "fma.rn.f32 th7, h15, th7, h15;\n"
            "cvt.rn.bf16x2.f32 r3, th7, th6;\n"
            "mma.sync.aligned.m16n8k16.row.col.f32.bf16.bf16.f32 {h12,h13,h14,h15}, {%19,%20,%21,%22}, {e0,e1}, {fz,fz,fz,fz};\n"
            "ld.shared.v4.u32 {a0,a1,a2,a3}, [ab+128];\n"
            "and.b32 tmp, aa, 0xffffff80; mbarrier.test_wait.parity.shared::cta.b64 pw, [tmp+520], mt;\n"
            "mad.lo.s32 xa, st, 2048, xa;\n"
            "mov.b32 {lo,hi}, r0; mov.b32 rl, {lo,lo}; mov.b32 rh, {hi,hi};\n"
            "mul.bf16x2 x0, x0, rl; mul.bf16x2 x1, x1, rl; mul.bf16x2 x2, x2, rh; mul.bf16x2 x3, x3, rh;\n"
            "mov.b32 {lo,hi}, r1; mov.b32 rl, {lo,lo}; mov.b32 rh, {hi,hi};\n"
            "mul.bf16x2 x4, x4, rl; mul.bf16x2 x5, x5, rl; mul.bf16x2 x6, x6, rh; mul.bf16x2 x7, x7, rh;\n"
            "mov.b32 {lo,hi}, r2; mov.b32 rl, {lo,lo}; mov.b32 rh, {hi,hi};\n"
            "mul.bf16x2 x8, x8, rl; mul.bf16x2 x9, x9, rl; mul.bf16x2 x10, x10, rh; mul.bf16x2 x11, x11, rh;\n"
            "mov.b32 {lo,hi}, r3; mov.b32 rl, {lo,lo}; mov.b32 rh, {hi,hi};\n"
            "mul.bf16x2 x12, x12, rl; mul.bf16x2 x13, x13, rl; mul.bf16x2 x14, x14, rh; mul.bf16x2 x15, x15, rh;\n"
            "@!pw bra.uni W1;\n"
            "@d2 bra.uni B0_4; @d1 bra.uni L0; @d0 bra.uni B0_1; bra.uni B0_0;\n"
            "B1_4:\n"
            "xor.b32 tmp, mt, ea; and.b32 tmp, tmp, 192; setp.eq.u32 pm, tmp, 0; selp.b32 ab, aa, %3, pm;\n"
            "and.b32 tmp, mt, 8; setp.ne.u32 d0, tmp, 0; and.b32 tmp, mt, 16; setp.ne.u32 d1, tmp, 0; and.b32 tmp, mt, 32; setp.ne.u32 d2, tmp, 0;\n"
            "ld.shared.v2.u32 {e0,e1}, [ea];\n"
            "shr.s32 st, mt, 24; mad.lo.s32 aa, st, 2560, aa;\n"
            "mma.sync.aligned.m16n8k16.row.col.f32.bf16.bf16.f32 {c128,c129,c130,c131}, {a0,a1,a2,a3}, {x0,x1}, {c128,c129,c130,c131};\n"
            "mma.sync.aligned.m16n8k16.row.col.f32.bf16.bf16.f32 {c132,c133,c134,c135}, {a0,a1,a2,a3}, {x2,x3}, {c132,c133,c134,c135};\n"
            "ld.shared.v4.u32 {x0,x1,x2,x3}, [xa+1024];\n"
            "tanh.approx.f32 th0, h1;\n"
            "tanh.approx.f32 th1, h3;\n"
            "fma.rn.f32 th0, h1, th0, h1;\n"
            "fma.rn.f32 th1, h3, th1, h3;\n"
            "cvt.rn.bf16x2.f32 r0, th1, th0;\n"
            "mma.sync.aligned.m16n8k16.row.col.f32.bf16.bf16.f32 {h0,h1,h2,h3}, {%7,%8,%9,%10}, {e0,e1}, {fz,fz,fz,fz};\n"
            "mma.sync.aligned.m16n8k16.row.col.f32.bf16.bf16.f32 {c136,c137,c138,c139}, {a0,a1,a2,a3}, {x4,x5}, {c136,c137,c138,c139};\n"
            "mma.sync.aligned.m16n8k16.row.col.f32.bf16.bf16.f32 {c140,c141,c142,c143}, {a0,a1,a2,a3}, {x6,x7}, {c140,c141,c142,c143};\n"
            "ld.shared.v4.u32 {x4,x5,x6,x7}, [xa+1152];\n"
            "tanh.approx.f32 th2, h5;\n"
            "tanh.approx.f32 th3, h7;\n"
            "fma.rn.f32 th2, h5, th2, h5;\n"
            "fma.rn.f32 th3, h7, th3, h7;\n"
            "cvt.rn.bf16x2.f32 r1, th3, th2;\n"
            "mma.sync.aligned.m16n8k16.row.col.f32.bf16.bf16.f32 {h4,h5,h6,h7}, {%11,%12,%13,%14}, {e0,e1}, {fz,fz,fz,fz};\n"
            "mma.sync.aligned.m16n8k16.row.col.f32.bf16.bf16.f32 {c144,c145,c146,c147}, {a0,a1,a2,a3}, {x8,x9}, {c144,c145,c146,c147};\n"
            "mma.sync.aligned.m16n8k16.row.col.f32.bf16.bf16.f32 {c148,c149,c150,c151}, {a0,a1,a2,a3}, {x10,x11}, {c148,c149,c150,c151};\n"
            "ld.shared.v4.u32 {x8,x9,x10,x11}, [xa+1536];\n"
            "tanh.approx.f32 th4, h9;\n"
            "tanh.approx.f32 th5, h11;\n"
            "fma.rn.f32 th4, h9, th4, h9;\n"
            "fma.rn.f32 th5, h11, th5, h11;\n"
            "cvt.rn.bf16x2.f32 r2, th5, th4;\n"
            "mma.sync.aligned.m16n8k16.row.col.f32.bf16.bf16.f32 {h8,h9,h10,h11}, {%15,%16,%17,%18}, {e0,e1}, {fz,fz,fz,fz};\n"
            "mma.sync.aligned.m16n8k16.row.col.f32.bf16.bf16.f32 {c152,c153,c154,c155}, {a0,a1,a2,a3}, {x12,x13}, {c152,c153,c154,c155};\n"
            "mma.sync.aligned.m16n8k16.row.col.f32.bf16.bf16.f32 {c156,c157,c158,c159}, {a0,a1,a2,a3}, {x14,x15}, {c156,c157,c158,c159};\n"
            "ld.shared.v4.u32 {x12,x13,x14,x15}, [xa+1664];\n"
            "tanh.approx.f32 th6, h13;\n"
            "tanh.approx.f32 th7, h15;\n"
            "fma.rn.f32 th6, h13, th6, h13;\n"
            "fma.rn.f32 th7, h15, th7, h15;\n"
            "cvt.rn.bf16x2.f32 r3, th7, th6;\n"
            "mma.sync.aligned.m16n8k16.row.col.f32.bf16.bf16.f32 {h12,h13,h14,h15}, {%19,%20,%21,%22}, {e0,e1}, {fz,fz,fz,fz};\n"
            "ld.shared.v4.u32 {a0,a1,a2,a3}, [ab+128];\n"
            "and.b32 tmp, aa, 0xffffff80; mbarrier.test_wait.parity.shared::cta.b64 pw, [tmp+520], mt;\n"
            "mad.lo.s32 xa, st, 2048, xa;\n"
            "mov.b32 {lo,hi}, r0; mov.b32 rl, {lo,lo}; mov.b32 rh, {hi,hi};\n"
            "mul.bf16x2 x0, x0, rl; mul.bf16x2 x1, x1, rl; mul.bf16x2 x2, x2, rh; mul.bf16x2 x3, x3, rh;\n"
            "mov.b32 {lo,hi}, r1; mov.b32 rl, {lo,lo}; mov.b32 rh, {hi,hi};\n"
            "mul.bf16x2 x4, x4, rl; mul.bf16x2 x5, x5, rl; mul.bf16x2 x6, x6, rh; mul.bf16x2 x7, x7, rh;\n"
            "mov.b32 {lo,hi}, r2; mov.b32 rl, {lo,lo}; mov.b32 rh, {hi,hi};\n"
            "mul.bf16x2 x8, x8, rl; mul.bf16x2 x9, x9, rl; mul.bf16x2 x10, x10, rh; mul.bf16x2 x11, x11, rh;\n"
            "mov.b32 {lo,hi}, r3; mov.b32 rl, {lo,lo}; mov.b32 rh, {hi,hi};\n"
            "mul.bf16x2 x12, x12, rl; mul.bf16x2 x13, x13, rl; mul.bf16x2 x14, x14, rh; mul.bf16x2 x15, x15, rh;\n"
            "@!pw bra.uni W1;\n"
            "@d2 bra.uni B0_4; @d1 bra.uni L0; @d0 bra.uni B0_1; bra.uni B0_0;\n"
            "W1:\n"
            "mov.u32 cnt, 0; and.b32 tmp, aa, 0xffffff80;\n"
            "W1L: mbarrier.try_wait.parity.shared::cta.b64 pw, [tmp+520], mt; @pw bra.uni W1D;\n"
            "add.u32 cnt, cnt, 1; setp.lt.u32 pk, cnt, 1000000; @pk bra.uni W1L; trap;\n"
            "W1D:\n"
            "@d2 bra.uni B0_4; @d1 bra.uni L0; @d0 bra.uni B0_1; bra.uni B0_0;\n"
            "END:\n"
            "cvt.rn.bf16x2.f32 p0, c1, c0; cvt.rn.bf16x2.f32 p1, c5, c4; cvt.rn.bf16x2.f32 p2, c9, c8; cvt.rn.bf16x2.f32 p3, c13, c12; cvt.rn.bf16x2.f32 p4, c17, c16; cvt.rn.bf16x2.f32 p5, c21, c20; cvt.rn.bf16x2.f32 p6, c25, c24; cvt.rn.bf16x2.f32 p7, c29, c28;\n"
            "cvt.rn.bf16x2.f32 p8, c3, c2; cvt.rn.bf16x2.f32 p9, c7, c6; cvt.rn.bf16x2.f32 p10, c11, c10; cvt.rn.bf16x2.f32 p11, c15, c14; cvt.rn.bf16x2.f32 p12, c19, c18; cvt.rn.bf16x2.f32 p13, c23, c22; cvt.rn.bf16x2.f32 p14, c27, c26; cvt.rn.bf16x2.f32 p15, c31, c30;\n"
            "cvt.rn.bf16x2.f32 p16, c33, c32; cvt.rn.bf16x2.f32 p17, c37, c36; cvt.rn.bf16x2.f32 p18, c41, c40; cvt.rn.bf16x2.f32 p19, c45, c44; cvt.rn.bf16x2.f32 p20, c49, c48; cvt.rn.bf16x2.f32 p21, c53, c52; cvt.rn.bf16x2.f32 p22, c57, c56; cvt.rn.bf16x2.f32 p23, c61, c60;\n"
            "cvt.rn.bf16x2.f32 p24, c35, c34; cvt.rn.bf16x2.f32 p25, c39, c38; cvt.rn.bf16x2.f32 p26, c43, c42; cvt.rn.bf16x2.f32 p27, c47, c46; cvt.rn.bf16x2.f32 p28, c51, c50; cvt.rn.bf16x2.f32 p29, c55, c54; cvt.rn.bf16x2.f32 p30, c59, c58; cvt.rn.bf16x2.f32 p31, c63, c62;\n"
            "cvt.rn.bf16x2.f32 p32, c65, c64; cvt.rn.bf16x2.f32 p33, c69, c68; cvt.rn.bf16x2.f32 p34, c73, c72; cvt.rn.bf16x2.f32 p35, c77, c76; cvt.rn.bf16x2.f32 p36, c81, c80; cvt.rn.bf16x2.f32 p37, c85, c84; cvt.rn.bf16x2.f32 p38, c89, c88; cvt.rn.bf16x2.f32 p39, c93, c92;\n"
            "cvt.rn.bf16x2.f32 p40, c67, c66; cvt.rn.bf16x2.f32 p41, c71, c70; cvt.rn.bf16x2.f32 p42, c75, c74; cvt.rn.bf16x2.f32 p43, c79, c78; cvt.rn.bf16x2.f32 p44, c83, c82; cvt.rn.bf16x2.f32 p45, c87, c86; cvt.rn.bf16x2.f32 p46, c91, c90; cvt.rn.bf16x2.f32 p47, c95, c94;\n"
            "cvt.rn.bf16x2.f32 p48, c97, c96; cvt.rn.bf16x2.f32 p49, c101, c100; cvt.rn.bf16x2.f32 p50, c105, c104; cvt.rn.bf16x2.f32 p51, c109, c108; cvt.rn.bf16x2.f32 p52, c113, c112; cvt.rn.bf16x2.f32 p53, c117, c116; cvt.rn.bf16x2.f32 p54, c121, c120; cvt.rn.bf16x2.f32 p55, c125, c124;\n"
            "cvt.rn.bf16x2.f32 p56, c99, c98; cvt.rn.bf16x2.f32 p57, c103, c102; cvt.rn.bf16x2.f32 p58, c107, c106; cvt.rn.bf16x2.f32 p59, c111, c110; cvt.rn.bf16x2.f32 p60, c115, c114; cvt.rn.bf16x2.f32 p61, c119, c118; cvt.rn.bf16x2.f32 p62, c123, c122; cvt.rn.bf16x2.f32 p63, c127, c126;\n"
            "cvt.rn.bf16x2.f32 p64, c129, c128; cvt.rn.bf16x2.f32 p65, c133, c132; cvt.rn.bf16x2.f32 p66, c137, c136; cvt.rn.bf16x2.f32 p67, c141, c140; cvt.rn.bf16x2.f32 p68, c145, c144; cvt.rn.bf16x2.f32 p69, c149, c148; cvt.rn.bf16x2.f32 p70, c153, c152; cvt.rn.bf16x2.f32 p71, c157, c156;\n"
            "cvt.rn.bf16x2.f32 p72, c131, c130; cvt.rn.bf16x2.f32 p73, c135, c134; cvt.rn.bf16x2.f32 p74, c139, c138; cvt.rn.bf16x2.f32 p75, c143, c142; cvt.rn.bf16x2.f32 p76, c147, c146; cvt.rn.bf16x2.f32 p77, c151, c150; cvt.rn.bf16x2.f32 p78, c155, c154; cvt.rn.bf16x2.f32 p79, c159, c158;\n"
            "and.b32 aa, %3, 0xfffff980; sub.u32 aa, aa, %6; mov.u32 mt, %%tid.x; shr.u32 st, mt, 7; shr.u32 cnt, mt, 5; add.u32 cnt, cnt, st; and.b32 cnt, cnt, 3;\n"
            "and.b32 mt, mt, 31; mad.lo.u32 tmp, mt, 16, aa; mad.lo.u32 tmp, st, 1024, tmp; mad.lo.u32 tmp, cnt, 20480, tmp;\n"
            "bar.sync 1, 256;\n"
            "stmatrix.sync.aligned.m8n8.x4.shared.b16 [tmp+0], {p0,p1,p2,p3};\n"
            "stmatrix.sync.aligned.m8n8.x4.shared.b16 [tmp+512], {p4,p5,p6,p7};\n"
            "stmatrix.sync.aligned.m8n8.x4.shared.b16 [tmp+2048], {p8,p9,p10,p11};\n"
            "stmatrix.sync.aligned.m8n8.x4.shared.b16 [tmp+2560], {p12,p13,p14,p15};\n"
            "stmatrix.sync.aligned.m8n8.x4.shared.b16 [tmp+4096], {p16,p17,p18,p19};\n"
            "stmatrix.sync.aligned.m8n8.x4.shared.b16 [tmp+4608], {p20,p21,p22,p23};\n"
            "stmatrix.sync.aligned.m8n8.x4.shared.b16 [tmp+6144], {p24,p25,p26,p27};\n"
            "stmatrix.sync.aligned.m8n8.x4.shared.b16 [tmp+6656], {p28,p29,p30,p31};\n"
            "stmatrix.sync.aligned.m8n8.x4.shared.b16 [tmp+8192], {p32,p33,p34,p35};\n"
            "stmatrix.sync.aligned.m8n8.x4.shared.b16 [tmp+8704], {p36,p37,p38,p39};\n"
            "stmatrix.sync.aligned.m8n8.x4.shared.b16 [tmp+10240], {p40,p41,p42,p43};\n"
            "stmatrix.sync.aligned.m8n8.x4.shared.b16 [tmp+10752], {p44,p45,p46,p47};\n"
            "stmatrix.sync.aligned.m8n8.x4.shared.b16 [tmp+12288], {p48,p49,p50,p51};\n"
            "stmatrix.sync.aligned.m8n8.x4.shared.b16 [tmp+12800], {p52,p53,p54,p55};\n"
            "stmatrix.sync.aligned.m8n8.x4.shared.b16 [tmp+14336], {p56,p57,p58,p59};\n"
            "stmatrix.sync.aligned.m8n8.x4.shared.b16 [tmp+14848], {p60,p61,p62,p63};\n"
            "stmatrix.sync.aligned.m8n8.x4.shared.b16 [tmp+16384], {p64,p65,p66,p67};\n"
            "stmatrix.sync.aligned.m8n8.x4.shared.b16 [tmp+16896], {p68,p69,p70,p71};\n"
            "stmatrix.sync.aligned.m8n8.x4.shared.b16 [tmp+18432], {p72,p73,p74,p75};\n"
            "stmatrix.sync.aligned.m8n8.x4.shared.b16 [tmp+18944], {p76,p77,p78,p79};\n"
            "mov.b32 %0, aa;\n"
            "}\n"
            : "=r"(sb2)
            : "r"(sb + t * XREG + grp * (NST * 2048) + half * 256 + ((g ^ ((2 * t + 2 * half) & 7)) << 4)),
              "r"(sb + AUX_OFF + grp * AUX_GR + t * 32 + (g & 1) * 16), "r"(az),
              "r"(sb + AUX_OFF + grp * AUX_GR + 256 + lane * 8), "r"(zero), "n"(ZERO_OFF),
              "r"(wr[0][0]), "r"(wr[0][1]), "r"(wr[0][2]), "r"(wr[0][3]), "r"(wr[1][0]), "r"(wr[1][1]), "r"(wr[1][2]), "r"(wr[1][3]),
              "r"(wr[2][0]), "r"(wr[2][1]), "r"(wr[2][2]), "r"(wr[2][3]), "r"(wr[3][0]), "r"(wr[3][1]), "r"(wr[3][2]), "r"(wr[3][3])
            : "memory");
        const int tid2 = threadIdx.x;
        sb2 = __shfl_sync(0xffffffffu, sb2, 0);
        const uint2 own = lds64(sb2 + MISC_OFF + 24);
        mbar_wait(sb2 + MISC_OFF + 16, 0);
        asm volatile("fence.proxy.async.shared::cta;" ::: "memory");
        asm volatile("bar.sync 1, 256;" ::: "memory");
        const uint32_t wg = __shfl_sync(0xffffffffu, tid2 >> 7, 0);
        const uint64_t da = (uint64_t)((sb2 + WM_OFF + wg * 16384) >> 4) | (1ull << 16) | (64ull << 32) | (1ull << 62);
        const uint64_t db = (uint64_t)(sb2 >> 4) | (8ull << 16) | (128ull << 32);
        float d[4][40];
        asm volatile("wgmma.fence.sync.aligned;" ::: "memory");
#pragma unroll
        for (int q = 0; q < 4; q++) {
#pragma unroll
            for (int ks = 0; ks < 8; ks++) wgmma_n80(d[q], da + ks * 128, db + q * 1280 + ks * 16, ks);
            asm volatile("wgmma.commit_group.sync.aligned;" ::: "memory");
        }
        const int n0 = (int)own.x, left = (int)own.y;
        uint32_t* op = out + (size_t)(n0 + 4 * (tid2 & 3)) * 256 + ((tid2 >> 5) * 16 + ((tid2 & 31) >> 2)) * 2;
#pragma unroll
        for (int q = 0; q < 4; q++) {
            if (q == 0) asm volatile("wgmma.wait_group.sync.aligned 3;" ::: "memory");
            if (q == 1) asm volatile("wgmma.wait_group.sync.aligned 2;" ::: "memory");
            if (q == 2) asm volatile("wgmma.wait_group.sync.aligned 1;" ::: "memory");
            if (q == 3) asm volatile("wgmma.wait_group.sync.aligned 0;" ::: "memory");
#pragma unroll
            for (int i = 0; i < 40; i++) asm volatile("" : "+f"(d[q][i])::"memory");
#pragma unroll
            for (int k = 0; k < 5; k++) {
                const bool ok = 16 * k + q + 4 * (tid2 & 3) < left;
#pragma unroll
                for (int u = 0; u < 2; u++)
                    stg64_if(ok, op + (16 * k + q) * 256 + u * 16, pack_bf16(d[q][8 * k + 2 * u], d[q][8 * k + 2 * u + 1]),
                             pack_bf16(d[q][8 * k + 4 + 2 * u], d[q][8 * k + 4 + 2 * u + 1]));
            }
        }
    } else {
        asm volatile("setmaxnreg.dec.sync.aligned.u32 40;");
        auto uni = [&](uint32_t v) { return __shfl_sync(0xffffffffu, v + (lane & zero), 0); };
        auto keep = [&](uint32_t v) { return __shfl_sync(0xffffffffu, v, lane); };
        const int grp = (warp + 2) & 3;
        const uint32_t s0 = uni(sb);
        const uint64_t map0 = reinterpret_cast<uint64_t>(&xmap);
        const uint64_t map = ((uint64_t)uni((uint32_t)(map0 >> 32)) << 32) | uni((uint32_t)(map0 & 0xffffffffu));
        const uint32_t T0 = uni(clock_lo() + (uint32_t)((int)(short)(ms.ref + ms.dmax - global_ticks()) * 57 + lead));
        const uint32_t ab = s0 + AUX_OFF + grp * AUX_GR, xb = s0 + grp * (NST * 2048);
        uint32_t yp = s0 + SY_OFF + grp * GCAP * 4;
        const uint32_t noct = uni((uint32_t)(ms.nq[grp] + 1) >> 1);
        const uint32_t yend = yp + noct * 32;
        const uint32_t e_l = keep(SE_OFF - SY_OFF + (4 * (g & 1) + (g >> 1)) * 4);
        uint32_t h_l = keep(sb + SH_OFF + grp * GCAP * 8 + g * 8 + (t & 1) * 4);
        const uint32_t f_l = keep(sb + AUX_OFF + grp * AUX_GR + 512 + (g >> 1) * 32 + (t & 1) * 16 + (~g & 1));
        const uint32_t w_l = keep(sb + AUX_OFF + grp * AUX_GR + lane * 8);
        const char* efl = ef + keep(t * 8);
        const bool odd = g & 1;
        const uint32_t pace_r = keep(pace);
        uint32_t par = 0, prev = 0;
        int last = -(1 << 30);
        auto ahead = [&](int st, uint32_t ev) {
            asm volatile("cp.async.ca.shared.global [%0], [%1], 8;" ::"r"(w_l + st * AUX_ST + 256), "l"(efl + (ev & 0x1ffffe0u)) : "memory");
            cp_async_arrive(ab + st * AUX_ST + BAR_F0);
            sts8(f_l + st * AUX_ST, ((odd ? prev : ev) >> 24 & 0xfeu) | (st == NST - 1 ? par ^ 1u : par));
            prev = ev;
        };
        auto due = [&](uint32_t ysum) {
            const int tq = max((int)__umulhi(ysum, pace_r), last + gap);
            last = (int)((uint32_t)clock64() - T0);
            if (__any_sync(0xffffffffu, tq > last)) {
#pragma unroll 1
                do {
                    __nanosleep(slp);
                    last = (int)((uint32_t)clock64() - T0);
                } while (__any_sync(0xffffffffu, tq > last));
            }
        };
        auto step = [&](int st) {
            const uint32_t hv = lds32(h_l);
            const uint32_t ev = lds32(yp + 32 + e_l);
            const uint4 y0 = lds128(yp), y1 = lds128(yp + 16);
            float w0[4], w1[4];
            mma1688_z(w0, hv, hv, cgb0);
            mma1688_z(w1, hv, hv, cgb1);
            yp += 32;
            h_l += 64;
            mbar_wait(ab + st * AUX_ST + BAR_EM, par ^ 1u);
            ahead(st, ev);
            sts64(w_l + st * AUX_ST, pack_bf16(w0[0], w0[1]), pack_bf16(w1[0], w1[1]));
            due(y0.z + y1.y);
            fetch_quad<true>(xb + st * 2048, ab + st * AUX_ST + BAR_F0, y0, map);
            fetch_quad<false>(xb + st * 2048 + 1024, ab + st * AUX_ST + BAR_F0, y1, map);
        };
        ahead(0, lds32(yp + e_l));
        __syncwarp();
        mbar_arrive_one(ab + BAR_F0);
        uint32_t fin;
#pragma unroll 1
        for (;;) {
            fin = 1; if (yp == yend) break;
            step(1);
            fin = 2; if (yp == yend) break;
            step(2);
            fin = 3; if (yp == yend) break;
            step(3);
            fin = 4; if (yp == yend) break;
            step(4);
            par ^= 1u;
            fin = 0; if (yp == yend) break;
            step(0);
        }
        mbar_wait(ab + fin * AUX_ST + BAR_EM, par ^ 1u);
        asm volatile("mbarrier.arrive.shared::cta.b64 _, [%0];" ::"r"(ab + fin * AUX_ST + BAR_F0) : "memory");
        mbar_arrive_one(ab + fin * AUX_ST + BAR_F0);
        asm volatile("bar.sync 2, 128;" ::: "memory");
        const int ln = threadIdx.x & 31;
#pragma unroll 4
        for (int i = 0; i < 16; i++) {
            const int kr = i * 8 + grp * 2 + (ln >> 4);
            const int dj = ((i >> 1) & 1) + (i & 4), n = kr & 7;
            const int ch = 16 * (2 * (i >> 3) + dj) + 2 * (n ^ dj) + (i & 1);
            asm volatile("cp.async.cg.shared.global [%0], [%1], 16;"
                         ::"r"(s0 + WM_OFF + ((ln >> 3) & 1) * 16384 + kr * 128 + (((ln & 7) ^ n) << 4)),
                           "l"(w_mix + ch * 128 + (ln & 15) * 8) : "memory");
        }
        cp_async_arrive(s0 + MISC_OFF + 16);
        asm volatile("cp.async.wait_all;" ::: "memory");
    }
}

typedef CUresult (*EncodeFn)(CUtensorMap*, CUtensorMapDataType, cuuint32_t, void*, const cuuint64_t*, const cuuint64_t*,
                             const cuuint32_t*, const cuuint32_t*, CUtensorMapInterleave, CUtensorMapSwizzle,
                             CUtensorMapL2promotion, CUtensorMapFloatOOBfill);

}

#define WALK 47000
#define GAP 0
#define LEAD 8000

extern "C" void kernel_launch(void* const* d_in, const int* in_sizes, int n_in, void* d_out, int out_size) {
    const char* x = (const char*)d_in[0];
    const int* src = (const int*)d_in[1];
    const int* dst = (const int*)d_in[2];
    const uint2* Y = (const uint2*)d_in[3];
    const char* ef = (const char*)d_in[4];
    const __nv_bfloat16* w_rad = (const __nv_bfloat16*)d_in[5];
    const __nv_bfloat16* cg = (const __nv_bfloat16*)d_in[6];
    const __nv_bfloat16* w_mix = (const __nv_bfloat16*)d_in[7];
    const int N = in_sizes[0] / 512;
    const int E = in_sizes[1];

    static int num_cta = 0;
    static EncodeFn encode = nullptr;
    if (num_cta == 0) {
        int dev = 0, sms = 0;
        cudaGetDevice(&dev);
        cudaDeviceGetAttribute(&sms, cudaDevAttrMultiProcessorCount, dev);
        num_cta = sms < MAXCTA ? sms : MAXCTA;
        cudaFuncSetAttribute(tfn_kernel, cudaFuncAttributeMaxDynamicSharedMemorySize, SMEM_BYTES);
        void* fn = nullptr;
        cudaDriverEntryPointQueryResult qr;
        cudaGetDriverEntryPoint("cuTensorMapEncodeTiled", &fn, cudaEnableDefault, &qr);
        encode = (EncodeFn)fn;
    }
    int S = (N + num_cta - 1) / num_cta;
    if (S < 2) S = 2;
    const int EPC = ((E + num_cta - 1) / num_cta + 3) & ~3;
    if (S > SMAX || EPC > EPC_MAX || N < 128 || N > 16384 || E <= 0 || E > (1 << 20) || encode == nullptr) return;
    CUtensorMap xmap;
    const cuuint64_t gd[2] = {64, (cuuint64_t)N * 8}, gs[1] = {128};
    const cuuint32_t bx[2] = {64, BOX_LINES}, es[2] = {1, 1};
    if (encode(&xmap, CU_TENSOR_MAP_DATA_TYPE_BFLOAT16, 2, (void*)x, gd, gs, bx, es, CU_TENSOR_MAP_INTERLEAVE_NONE,
               CU_TENSOR_MAP_SWIZZLE_128B, CU_TENSOR_MAP_L2_PROMOTION_NONE, CU_TENSOR_MAP_FLOAT_OOB_FILL_NONE) != CUDA_SUCCESS)
        return;
    const uint32_t magicS = (uint32_t)((0x100000000ull + S - 1) / S);
    const uint32_t magicB = (uint32_t)(((unsigned long long)NB << 32) / N);
    int walk = WALK, lead = LEAD, gap = GAP, slp = 100;
    double pc = (double)walk * ((double)E / N * S / 2432.0) / (16.0 * N);
    if (pc > 0.99) pc = 0.99;
    const uint32_t pace = (uint32_t)(pc * 4294967296.0);
    tfn_kernel<<<num_cta, NT, SMEM_BYTES, cudaStreamPerThread>>>(xmap, x, src, dst, Y, ef, w_rad, cg, w_mix, (uint32_t*)d_out, N, E, S,
                                                                 EPC, magicS, magicB, 0u, pace, lead, gap, slp);
}
```

```cpp
#include <cuda_runtime.h>
#include <cuda.h>
#include <cuda_bf16.h>
#include <stdint.h>

namespace {

constexpr int NT = 384;
constexpr int NWARP = NT / 32;
constexpr int MAXCTA = 132;
constexpr int SFAST = 80;
constexpr int SMAX = 96;
constexpr int EPC_MAX = 3072;
constexpr int RND = 10;
constexpr int NB = 96;
constexpr int GCAP = 800;
constexpr int NCOL = NWARP - 1;
constexpr int JCAP = NCOL * RND * 8 + 8;
constexpr int RND0 = 8;
constexpr uint32_t TAGM = 31u;
constexpr int NST = 5;
constexpr uint32_t F0_COUNT = 33;
#define SLEEPNS 100
constexpr uint32_t SLEEP = SLEEPNS;
constexpr int SPIN_LIMIT = 1 << 22;

constexpr int XREG = 4 * NST * 2048 + 256;
constexpr int AUX_OFF = 4 * XREG;
constexpr int AUX_ST = 2560, AUX_GR = 640;
constexpr int BAR_F0 = 520, BAR_EM = 536;
constexpr int SY_OFF = AUX_OFF + NST * AUX_ST;
constexpr int SE_OFF = SY_OFF + 4 * GCAP * 4;
constexpr int SH_OFF = SE_OFF + 4 * GCAP * 4;
constexpr int MISC_OFF = SH_OFF + 4 * GCAP * 8;
constexpr int ZERO_OFF = ((MISC_OFF + 1024 + 2047) & ~2047) - 1024;
constexpr int WM_OFF = (SE_OFF + 1023) & ~1023;
constexpr int CNT_OFF = 20 * JCAP * 4, START_OFF = CNT_OFF + 1024;
constexpr int BCNT_OFF = START_OFF + 1024;
constexpr int BCUM_OFF = BCNT_OFF + 20 * NB * 4;
constexpr int SEG_OFF = BCUM_OFF + 20 * NB * 4;
constexpr int WR_OFF = SEG_OFF + 1024;
constexpr int GI_OFF = 0;
struct Misc {
    unsigned long long wbar;
    int node0, Sc;
    unsigned long long rbar;
    int nq[4];
    int over, dmax;
    uint32_t epoch, ref;
    uint32_t rseg[MAXCTA];
};
constexpr int SMEM_BYTES = ZERO_OFF + 1792;
static_assert(MISC_OFF + (int)sizeof(Misc) <= ZERO_OFF, "layout");
static_assert(SMEM_BYTES <= 227 * 1024, "shared memory");
static_assert(EPC_MAX * 16 <= CNT_OFF && WR_OFF + 4096 <= AUX_OFF && WR_OFF % 128 == 0, "tables");
static_assert(WM_OFF + 32768 <= MISC_OFF && SMAX * 2048 <= MISC_OFF, "layout");
static_assert(AUX_OFF % 256 == 0 && NB == 96 && NWARP == 12, "layout");

__device__ __align__(128) uint4 g_staged[(size_t)MAXCTA * EPC_MAX];
__device__ __align__(128) uint2 g_table[MAXCTA * 144];
__device__ unsigned int g_epoch[MAXCTA];

__device__ __forceinline__ void mma1688_z(float (&d)[4], uint32_t a0, uint32_t a1, uint32_t b0) {
    asm volatile(
        "mma.sync.aligned.m16n8k8.row.col.f32.bf16.bf16.f32 {%0,%1,%2,%3}, {%4,%5}, {%6}, {%7,%7,%7,%7};"
        : "=f"(d[0]), "=f"(d[1]), "=f"(d[2]), "=f"(d[3])
        : "r"(a0), "r"(a1), "r"(b0), "f"(0.0f));
}
__device__ __forceinline__ uint32_t pack_bf16(float lo, float hi) {
    uint32_t r;
    asm("cvt.rn.bf16x2.f32 %0, %1, %2;" : "=r"(r) : "f"(hi), "f"(lo));
    return r;
}
__device__ __forceinline__ uint32_t half_bf16x2(uint32_t v) {
    uint32_t r;
    asm("mul.bf16x2 %0, %1, %2;" : "=r"(r) : "r"(v), "r"(0x3f003f00u));
    return r;
}
__device__ __forceinline__ uint4 lds128(uint32_t a) {
    uint4 v;
    asm volatile("ld.shared.v4.u32 {%0,%1,%2,%3}, [%4];" : "=r"(v.x), "=r"(v.y), "=r"(v.z), "=r"(v.w) : "r"(a) : "memory");
    return v;
}
__device__ __forceinline__ uint32_t lds32(uint32_t a) {
    uint32_t v;
    asm volatile("ld.shared.u32 %0, [%1];" : "=r"(v) : "r"(a) : "memory");
    return v;
}
__device__ __forceinline__ uint2 lds64(uint32_t a) {
    uint2 v;
    asm volatile("ld.shared.v2.u32 {%0,%1}, [%2];" : "=r"(v.x), "=r"(v.y) : "r"(a) : "memory");
    return v;
}
__device__ __forceinline__ void sts8(uint32_t a, uint32_t v) {
    asm volatile("st.shared.u8 [%0], %1;" ::"r"(a), "r"(v) : "memory");
}
__device__ __forceinline__ void sts64(uint32_t a, uint32_t v0, uint32_t v1) {
    asm volatile("st.shared.v2.u32 [%0], {%1,%2};" ::"r"(a), "r"(v0), "r"(v1) : "memory");
}
#define OCT_BYTES 8192
#define BOX_LINES 8
__device__ __forceinline__ void fetch_quad(uint32_t dst, uint32_t bar, const uint4& y, uint64_t map) {
    asm volatile("{\n\t.reg .pred P;\n\telect.sync _|P, 0xffffffff;\n\t"
                 "@P cp.async.bulk.tensor.2d.shared::cluster.global.mbarrier::complete_tx::bytes [%0], [%6, {0, %2}], [%1];\n\t"
                 "@P cp.async.bulk.tensor.2d.shared::cluster.global.mbarrier::complete_tx::bytes [%0+%7], [%6, {0, %3}], [%1];\n\t"
                 "@P cp.async.bulk.tensor.2d.shared::cluster.global.mbarrier::complete_tx::bytes [%0+%8], [%6, {0, %4}], [%1];\n\t"
                 "@P cp.async.bulk.tensor.2d.shared::cluster.global.mbarrier::complete_tx::bytes [%0+%9], [%6, {0, %5}], [%1];\n\t}"
                 ::"r"(dst), "r"(bar), "r"(y.x), "r"(y.y), "r"(y.z), "r"(y.w), "l"(map), "n"(XREG), "n"(2 * XREG), "n"(3 * XREG)
                 : "memory");
}
__device__ __forceinline__ void mbar_arrive_one(uint32_t bar) {
    asm volatile("{\n\t.reg .pred P;\n\telect.sync _|P, 0xffffffff;\n\t@P mbarrier.arrive.shared::cta.b64 _, [%0];\n\t}" ::"r"(bar) : "memory");
}
__device__ __forceinline__ void cp_async_arrive(uint32_t bar) {
    asm volatile("cp.async.mbarrier.arrive.noinc.shared::cta.b64 [%0];" ::"r"(bar) : "memory");
}
__device__ __forceinline__ void mbar_init(uint32_t bar, uint32_t count) {
    asm volatile("mbarrier.init.shared::cta.b64 [%0], %1;" ::"r"(bar), "r"(count) : "memory");
}
__device__ __forceinline__ bool mbar_try(uint32_t bar, uint32_t parity) {
    uint32_t ok;
    asm volatile("{\n\t.reg .pred p;\n\tmbarrier.try_wait.parity.shared::cta.b64 p, [%1], %2;\n\tselp.u32 %0, 1, 0, p;\n\t}"
                 : "=r"(ok) : "r"(bar), "r"(parity) : "memory");
    return ok;
}
__device__ __forceinline__ void mbar_wait(uint32_t bar, uint32_t parity) {
    if (mbar_try(bar, parity)) return;
#pragma unroll 1
    for (int it = 0; it < SPIN_LIMIT; it++)
        if (mbar_try(bar, parity)) return;
    __trap();
}
__device__ __forceinline__ uint32_t clock_lo() {
    uint32_t v;
    asm volatile("mov.u32 %0, %%clock;" : "=r"(v));
    return v;
}
__device__ __forceinline__ uint32_t global_ticks() {
    uint32_t v;
    asm volatile("mov.u32 %0, %%globaltimer_lo;" : "=r"(v));
    return v >> 5;
}

#define TBL(snd, own) ((snd) * 144 + (own))
__device__ __forceinline__ void prefetch_line(const void* p) { asm volatile("prefetch.global.L2 [%0];" ::"l"(p)); }
__device__ __forceinline__ uint4 ld_entry(const uint4* p) {
    uint4 e;
    asm volatile("ld.relaxed.gpu.global.v4.u32 {%0,%1,%2,%3}, [%4];" : "=r"(e.x), "=r"(e.y), "=r"(e.z), "=r"(e.w) : "l"(p) : "memory");
    return e;
}
__device__ __forceinline__ uint4 wait_entry(const uint4* p, uint4 e, uint32_t tag) {
    int it = 0;
    while (((e.y ^ tag) & TAGM) != 0u) {
        if (++it > SPIN_LIMIT) __trap();
        e = ld_entry(p);
    }
    return e;
}
__device__ __forceinline__ uint4 ldg128_if(bool p, const void* a, uint32_t other) {
    uint4 v = make_uint4(other, other, other, other);
    asm volatile("{\n\t.reg .pred P;\n\tsetp.ne.u32 P, %5, 0;\n\t@P ld.global.nc.L1::no_allocate.v4.u32 {%0,%1,%2,%3}, [%4];\n\t}"
                 : "+r"(v.x), "+r"(v.y), "+r"(v.z), "+r"(v.w) : "l"(a), "r"((uint32_t)p));
    return v;
}
__device__ __forceinline__ uint32_t ldg_u16(const void* p) {
    unsigned short v;
    asm volatile("ld.global.nc.u16 %0, [%1];" : "=h"(v) : "l"(p));
    return v;
}
__device__ __forceinline__ void stg64_if(bool p, void* a, uint32_t v0, uint32_t v1) {
    asm volatile("{\n\t.reg .pred P;\n\tsetp.ne.u32 P, %0, 0;\n\t@P st.global.v2.u32 [%1], {%2,%3};\n\t}"
                 ::"r"((uint32_t)p), "l"(a), "r"(v0), "r"(v1) : "memory");
}
__device__ __forceinline__ float bf_lo(uint32_t v) { return __uint_as_float(v << 16); }
__device__ __forceinline__ float bf_hi(uint32_t v) { return __uint_as_float(v & 0xffff0000u); }

#define F8(o) "+f"(d[o]), "+f"(d[o + 1]), "+f"(d[o + 2]), "+f"(d[o + 3]), "+f"(d[o + 4]), "+f"(d[o + 5]), "+f"(d[o + 6]), "+f"(d[o + 7])
template <int T>
__device__ __forceinline__ void wgmma_tiles(float (&d)[40], uint64_t a, uint64_t b, uint32_t acc) {
    if constexpr (T == 1)
        asm volatile("{\n\t.reg .pred P;\n\tsetp.ne.u32 P, %10, 0;\n\twgmma.mma_async.sync.aligned.m64n16k16.f32.bf16.bf16 "
                     "{%0,%1,%2,%3,%4,%5,%6,%7}, "
                     "%8, %9, P, 1, 1, 1, 0;\n\t}"
                     : F8(0) : "l"(a), "l"(b), "r"(acc));
    if constexpr (T == 2)
        asm volatile("{\n\t.reg .pred P;\n\tsetp.ne.u32 P, %18, 0;\n\twgmma.mma_async.sync.aligned.m64n32k16.f32.bf16.bf16 "
                     "{%0,%1,%2,%3,%4,%5,%6,%7,%8,%9,%10,%11,%12,%13,%14,%15}, "
                     "%16, %17, P, 1, 1, 1, 0;\n\t}"
                     : F8(0), F8(8) : "l"(a), "l"(b), "r"(acc));
    if constexpr (T == 3)
        asm volatile("{\n\t.reg .pred P;\n\tsetp.ne.u32 P, %26, 0;\n\twgmma.mma_async.sync.aligned.m64n48k16.f32.bf16.bf16 "
                     "{%0,%1,%2,%3,%4,%5,%6,%7,%8,%9,%10,%11,%12,%13,%14,%15,%16,%17,%18,%19,%20,%21,%22,%23}, "
                     "%24, %25, P, 1, 1, 1, 0;\n\t}"
                     : F8(0), F8(8), F8(16) : "l"(a), "l"(b), "r"(acc));
    if constexpr (T == 4)
        asm volatile("{\n\t.reg .pred P;\n\tsetp.ne.u32 P, %34, 0;\n\twgmma.mma_async.sync.aligned.m64n64k16.f32.bf16.bf16 "
                     "{%0,%1,%2,%3,%4,%5,%6,%7,%8,%9,%10,%11,%12,%13,%14,%15,%16,%17,%18,%19,%20,%21,%22,%23,%24,%25,%26,%27,%28,%29,%30,%31}, "
                     "%32, %33, P, 1, 1, 1, 0;\n\t}"
                     : F8(0), F8(8), F8(16), F8(24) : "l"(a), "l"(b), "r"(acc));
    if constexpr (T == 5)
        asm volatile("{\n\t.reg .pred P;\n\tsetp.ne.u32 P, %42, 0;\n\twgmma.mma_async.sync.aligned.m64n80k16.f32.bf16.bf16 "
                     "{%0,%1,%2,%3,%4,%5,%6,%7,%8,%9,%10,%11,%12,%13,%14,%15,%16,%17,%18,%19,%20,%21,%22,%23,%24,%25,%26,%27,%28,%29,%30,%31,%32,%33,%34,%35,%36,%37,%38,%39}, "
                     "%40, %41, P, 1, 1, 1, 0;\n\t}"
                     : F8(0), F8(8), F8(16), F8(24), F8(32) : "l"(a), "l"(b), "r"(acc));
}
template <int T, int O>
__device__ __forceinline__ void mix_tiles(float (&d)[40], uint64_t da, uint64_t db) {
    asm volatile("wgmma.fence.sync.aligned;" ::: "memory");
#pragma unroll
    for (int ks = 0; ks < 8; ks++) wgmma_tiles<T>(d, da + ks * 128, db + O * 256 + ks * 16, ks);
    asm volatile("wgmma.commit_group.sync.aligned;" ::: "memory");
}
template <int T, int O, int PENDING>
__device__ __forceinline__ void store_tiles(float (&d)[40], uint32_t* op, int left, uint32_t bar) {
    asm volatile("wgmma.wait_group.sync.aligned %0;" ::"n"(PENDING) : "memory");
#pragma unroll
    for (int i = 0; i < 8 * T; i++) asm volatile("" : "+f"(d[i])::"memory");
#pragma unroll
    for (int k = 0; k < T; k++) {
        const int n = 16 * ((O + k) % 5) + (O + k) / 5;
#pragma unroll
        for (int u = 0; u < 2; u++)
            stg64_if(n < left, op + n * 256 + u * 16, pack_bf16(d[8 * k + 2 * u], d[8 * k + 2 * u + 1]),
                     pack_bf16(d[8 * k + 4 + 2 * u], d[8 * k + 4 + 2 * u + 1]));
    }
    if (PENDING) asm volatile("bar.sync %0, 128;" ::"r"(bar) : "memory");
}

__device__ __noinline__ void slow_cta(unsigned char* smem, const char* x, const char* ef, const __nv_bfloat16* w_rad,
                                      const __nv_bfloat16* cg, const __nv_bfloat16* w_mix, uint32_t* out, int node0, int Sc,
                                      uint32_t tag) {
    float* agg = reinterpret_cast<float*>(smem);
    Misc& ms = *reinterpret_cast<Misc*>(smem + MISC_OFF);
    const int tid = threadIdx.x, lane = tid & 31, warp = tid >> 5;
    for (int i = tid; i < Sc * 512; i += NT) agg[i] = 0.f;
    if (tid < (int)gridDim.x) {
        uint32_t v;
        asm volatile("ld.relaxed.gpu.global.u32 %0, [%1];" : "=r"(v) : "l"(&g_table[TBL(tid, blockIdx.x)]) : "memory");
        ms.rseg[tid] = v;
    }
    __syncthreads();
    uint2 wr[16];
#pragma unroll
    for (int f = 0; f < 16; f++) wr[f] = *reinterpret_cast<const uint2*>(w_rad + f * 128 + 4 * lane);
    float cgl[4];
#pragma unroll
    for (int f = 0; f < 4; f++) cgl[f] = __bfloat162float(cg[((lane >> 2) & 3) * 16 + f * 4 + (lane & 3)]);
    for (int s = 0; s < (int)gridDim.x; s++) {
        const int cn = ms.rseg[s] & 0xfffu;
        const uint4* p = g_staged + s * EPC_MAX + ((ms.rseg[s] >> 12) & 0xfffu);
        for (int i = (warp + s) % NWARP; i < cn; i += NWARP) {
            const uint4 e = wait_entry(p + i, ld_entry(p + i), tag);
            const uint4* xp = reinterpret_cast<const uint4*>(x + (size_t)(e.x & 0x1fff8u) * 128 + lane * 32);
            const uint4* fp = reinterpret_cast<const uint4*>(ef + (e.y & 0x1ffffe0u));
            const uint4 xa = xp[0], xb = xp[1], fa = fp[0], fb = fp[1];
            const uint32_t fv[8] = {fa.x, fa.y, fa.z, fa.w, fb.x, fb.y, fb.z, fb.w};
            const uint32_t xv[8] = {xa.x, xa.y, xa.z, xa.w, xb.x, xb.y, xb.z, xb.w};
            float h[4] = {0.f, 0.f, 0.f, 0.f};
#pragma unroll
            for (int f = 0; f < 16; f++) {
                const float v = (f & 1) ? bf_hi(fv[f >> 1]) : bf_lo(fv[f >> 1]);
                h[0] += v * bf_lo(wr[f].x); h[1] += v * bf_hi(wr[f].x); h[2] += v * bf_lo(wr[f].y); h[3] += v * bf_hi(wr[f].y);
            }
            const float wl = bf_lo(e.z) * cgl[0] + bf_hi(e.z) * cgl[1] + bf_lo(e.w) * cgl[2] + bf_hi(e.w) * cgl[3];
            const uint32_t tile = (e.x >> 19) / NB;
            float* ap = agg + ((tile >> 2) * 16 + ((e.y >> 25) & 3u) * 4 + (tile & 3)) * 512 + lane * 16;
#pragma unroll
            for (int o = 0; o < 4; o++) {
                const float w0 = __shfl_sync(0xffffffffu, wl, o), w1 = __shfl_sync(0xffffffffu, wl, 4 + o);
                const float w2 = __shfl_sync(0xffffffffu, wl, 8 + o), w3 = __shfl_sync(0xffffffffu, wl, 12 + o);
#pragma unroll
                for (int k = 0; k < 4; k++) {
                    const float tp = bf_lo(xv[2 * k]) * w0 + bf_hi(xv[2 * k]) * w1 + bf_lo(xv[2 * k + 1]) * w2 + bf_hi(xv[2 * k + 1]) * w3;
                    atomicAdd(ap + k * 4 + o, tp * (h[k] / (1.f + __expf(-h[k]))));
                }
            }
        }
    }
    __syncthreads();
    for (int n = tid >> 7; n < Sc; n += NT / 128) {
        const int d = tid & 127;
        float o[4] = {0.f, 0.f, 0.f, 0.f};
        for (int c = 0; c < 128; c++) {
            const float4 a = *reinterpret_cast<const float4*>(agg + n * 512 + c * 4);
            const float w = __bfloat162float(w_mix[c * 128 + d]);
            o[0] += a.x * w; o[1] += a.y * w; o[2] += a.z * w; o[3] += a.w * w;
        }
        *reinterpret_cast<uint2*>(out + (size_t)(node0 + n) * 256 + d * 2) = make_uint2(pack_bf16(o[0], o[1]), pack_bf16(o[2], o[3]));
    }
}

__global__ void __launch_bounds__(NT, 1)
tfn_kernel(const __grid_constant__ CUtensorMap xmap, const char* __restrict__ x, const int* __restrict__ src,
           const int* __restrict__ dst, const uint2* __restrict__ Y, const char* __restrict__ ef,
           const __nv_bfloat16* __restrict__ w_rad, const __nv_bfloat16* __restrict__ cg,
           const __nv_bfloat16* __restrict__ w_mix, uint32_t* __restrict__ out, int N, int E, int S, int EPC,
           uint32_t magicS, uint32_t magicB, uint32_t zero, uint32_t pace, int lead, uint32_t ramp, int rsh, int pfx, int pfe) {
    extern __shared__ __align__(1024) unsigned char smem[];
    Misc& ms = *reinterpret_cast<Misc*>(smem + MISC_OFF);
    int* const cnt = reinterpret_cast<int*>(smem + CNT_OFF);
    int* const start = reinterpret_cast<int*>(smem + START_OFF);
    uint32_t* const bcnt = reinterpret_cast<uint32_t*>(smem + BCNT_OFF);
    uint32_t* const bcum = reinterpret_cast<uint32_t*>(smem + BCUM_OFF);
    uint32_t* const gi = reinterpret_cast<uint32_t*>(smem + GI_OFF);
    const int tid = threadIdx.x;
    const int lane = tid & 31, warp = __shfl_sync(0xffffffffu, tid >> 5, 0);
    const int c = blockIdx.x;
    const int numCTA = gridDim.x;
    const int node0 = c * S;
    const int Sc = max(0, min(S, N - node0));
    const uint32_t sb = (uint32_t)__cvta_generic_to_shared(smem);

    const int eb = c * EPC;
    const int ne = max(0, min(EPC, E - eb));
    int d8[8], s8[8];
#pragma unroll
    for (int h = 0; h < 2; h++) {
        const uint4 v = ldg128_if(4 * (tid + h * NT) + 3 < ne, dst + eb + 4 * (tid + h * NT), 0xffffffffu);
        d8[4 * h] = (int)v.x; d8[4 * h + 1] = (int)v.y; d8[4 * h + 2] = (int)v.z; d8[4 * h + 3] = (int)v.w;
    }
#pragma unroll
    for (int h = 0; h < 2; h++) {
        const uint4 v = ldg128_if(4 * (tid + h * NT) + 3 < ne, src + eb + 4 * (tid + h * NT), 0u);
        s8[4 * h] = (int)v.x; s8[4 * h + 1] = (int)v.y; s8[4 * h + 2] = (int)v.z; s8[4 * h + 3] = (int)v.w;
    }
    if (ne & 3) {
#pragma unroll
        for (int k = 0; k < 8; k++) {
            const int i = 4 * (tid + (k >> 2) * NT) + (k & 3);
            if (i >= (ne & ~3) && i < ne) { d8[k] = __ldg(dst + eb + i); s8[k] = __ldg(src + eb + i); }
        }
    }
    if (tid == NT - 64) asm volatile("prefetch.tensormap [%0];" ::"l"(&xmap) : "memory");
    uint32_t ep0 = 0;
    if (tid == NT - 1) asm volatile("ld.relaxed.gpu.global.u32 %0, [%1];" : "=r"(ep0) : "l"(&g_epoch[c]) : "memory");
    uint32_t cgr[4] = {0u, 0u, 0u, 0u};
    if (warp >= 8 && (lane & 3) < 2) {
        const unsigned short* cu = reinterpret_cast<const unsigned short*>(cg) + ((lane >> 2) & 3) * 16 + (lane & 3) * 8 + (lane >> 4);
        cgr[0] = ldg_u16(cu); cgr[1] = ldg_u16(cu + 4); cgr[2] = ldg_u16(cu + 2); cgr[3] = ldg_u16(cu + 6);
    }
    if (warp == 7) {
        for (int i = c + lane * numCTA; i < 32 + 256; i += 32 * numCTA)
            prefetch_line(i < 32 ? (const char*)w_rad + i * 128 : (const char*)w_mix + (i - 32) * 128);
    }
    if (tid < MAXCTA) cnt[tid] = 0;
#pragma unroll
    for (int k = 0; k < 5; k++) bcnt[tid + k * NT] = 0u;
    if (tid < 224) reinterpret_cast<uint2*>(smem + ZERO_OFF)[tid] = make_uint2(0u, 0u);
    if (tid >= 160 && tid < 320) {
        const int i = tid - 160;
        *reinterpret_cast<uint32_t*>(smem + AUX_OFF + (i >> 5) * AUX_ST + ((i >> 3) & 3) * AUX_GR + 512 + (i & 7) * 16) =
            (i >> 5) == NST - 1 ? (uint32_t)(1 - NST) << 24 : 1u << 24;
    }
    if (lane < NST && warp < 8) {
        const int k = warp >> 2;
        mbar_init(sb + AUX_OFF + lane * AUX_ST + (warp & 3) * AUX_GR + BAR_F0 + 16 * k, k == 0 ? F0_COUNT : 2u);
    }
    if (tid == 330) { mbar_init(sb + MISC_OFF + 16, 1); mbar_init(sb + MISC_OFF, 128); ms.node0 = node0; ms.Sc = Sc; ms.over = S > SFAST; ms.dmax = -32768; ms.ref = global_ticks(); }
    __syncthreads();
    const uint32_t cgb0 = cgr[0] | (cgr[1] << 16), cgb1 = cgr[2] | (cgr[3] << 16);
    uint2 y8[8];
#pragma unroll
    for (int h = 0; h < 4; h++) {
        const int i = 4 * (tid + (h >> 1) * NT) + 2 * (h & 1);
        const uint4 v = ldg128_if(i + 1 < ne, Y + eb + i, 0u);
        y8[2 * h] = make_uint2(v.x, v.y); y8[2 * h + 1] = make_uint2(v.z, v.w);
    }
    int bin[8], pos[8];
#pragma unroll
    for (int k = 0; k < 8; k++) {
        bin[k] = (int)__umulhi((uint32_t)d8[k], magicS);
        if (d8[k] >= 0) pos[k] = atomicAdd(&cnt[bin[k]], 1);
    }
    if (tid == NT - 1) {
        ms.epoch = ep0 + 1u;
        g_epoch[c] = ep0 + 1u;
    }
    __syncthreads();
    const uint32_t epoch = ms.epoch;
    if (warp < 5) {
        int pre = 0;
#pragma unroll
        for (int k = 0; k < 4; k++)
            if (k < warp) pre += cnt[lane + 32 * k];
        const int v = tid < numCTA ? cnt[tid] : 0;
        int incl = v;
#pragma unroll
        for (int o = 1; o < 32; o <<= 1) {
            int t_ = __shfl_up_sync(0xffffffffu, incl, o);
            if (lane >= o) incl += t_;
        }
        const int ex = __reduce_add_sync(0xffffffffu, pre) + incl - v;
        if (tid < MAXCTA) start[tid] = ex;
        if (tid < numCTA)
            asm volatile("st.relaxed.gpu.global.u32 [%0], %1;" ::"l"(g_table + TBL(c, tid)), "r"((epoch << 24) | (ex << 12) | v) : "memory");
    }
    const uint32_t tag = epoch & TAGM;
    uint32_t w0[8], w1[8];
#pragma unroll
    for (int k = 0; k < 8; k++) {
        const uint32_t dl = (uint32_t)(d8[k] - bin[k] * S);
        w0[k] = (((((dl >> 2) & 0x1cu) | (dl & 3u)) * NB + __umulhi((uint32_t)s8[k], magicB)) << 19) + (uint32_t)s8[k] * 8u;
        w1[k] = (((dl << 23) & 0x3e000000u) | (((dl << 28) & 0xc0000000u) ^ (dl << 31))) +
                ((uint32_t)(eb + 4 * tid) * 32u + tag + ((k >> 2) * 4 * NT + (k & 3)) * 32);
    }
    __syncthreads();
    if (tid == 192)
        asm volatile("mbarrier.arrive.expect_tx.shared::cta.b64 _, [%2], 4096;\n\t"
                     "cp.async.bulk.shared::cluster.global.mbarrier::complete_tx::bytes [%0], [%1], 4096, [%2];"
                     ::"r"(sb + WR_OFF), "l"(w_rad), "r"(sb + MISC_OFF + 16) : "memory");
    if (ne & 1) {
#pragma unroll
        for (int h = 0; h < 4; h++)
            if (4 * (tid + (h >> 1) * NT) + 2 * (h & 1) + 1 == ne) y8[2 * h] = __ldg(Y + eb + ne - 1);
    }
#pragma unroll
    for (int k = 0; k < 8; k++)
        if (d8[k] >= 0) pos[k] += start[bin[k]];
#pragma unroll
    for (int k = 0; k < 8; k++)
        if (d8[k] >= 0) reinterpret_cast<uint4*>(smem)[pos[k]] = make_uint4(w0[k], w1[k], y8[k].x, y8[k].y);
    asm volatile("fence.proxy.async.shared::cta;" ::: "memory");
    __syncthreads();
    if (tid == NT - 32 && ne > 0) {
        asm volatile("cp.async.bulk.global.shared::cta.bulk_group [%0], [%1], %2;" ::"l"(g_staged + (size_t)c * EPC_MAX),
                     "r"(sb), "r"(ne * 16) : "memory");
        asm volatile("cp.async.bulk.commit_group;" ::: "memory");
    }

    const int g = lane >> 2, t = lane & 3;
    uint32_t wr[4][4];
    if (tid == 64 && pfx && (c + 1) * pfx <= N)
        asm volatile("cp.async.bulk.prefetch.L2.global [%0], %1;" ::"l"(x + (size_t)c * pfx * 1024), "r"(pfx * 1024) : "memory");

    uint4 ent[RND];
    uint32_t rk[RND];
    int tot = 0;
    if (warp == NWARP - 1) {
        asm volatile("cp.async.bulk.wait_group 0;" ::: "memory");
        __syncwarp();
        const uint32_t w = (epoch << 16) | (global_ticks() & 0xffffu);
#pragma unroll
        for (int k = 0; k < 5; k++)
            asm volatile("{\n\t.reg .pred P;\n\tsetp.lt.s32 P, %0, %1;\n\t@P st.relaxed.gpu.global.u32 [%2+4], %3;\n\t}"
                         ::"r"(lane + 32 * k), "r"(numCTA), "l"(g_table + TBL(c, lane) + 32 * k), "r"(w) : "memory");
    } else {
        const bool mine = warp + NCOL * lane < numCTA;
        const uint2* tp = g_table + TBL(warp + NCOL * lane, c);
        const uint4* gp[RND];
        auto poll = [&](const uint32_t* p, uint32_t v, int sh) {
            int it = 0;
            do {
                if (mine) asm volatile("ld.relaxed.gpu.global.u32 %0, [%1];" : "=r"(v) : "l"(p) : "memory");
                if (++it > SPIN_LIMIT) __trap();
            } while (!__all_sync(0xffffffffu, ((v ^ (epoch << sh)) >> sh) == 0u));
            return v;
        };
        const uint32_t sv = poll(&tp->x, epoch << 24, 24);
        int incl = (int)(sv & 0xfffu);
#pragma unroll
        for (int o = 1; o < 16; o <<= 1) {
            int t_ = __shfl_up_sync(0xffffffffu, incl, o);
            if (lane >= o) incl += t_;
        }
        tot = __shfl_sync(0xffffffffu, incl, 15);
        const bool some = (sv & 0xfffu) != 0u;
        const uint32_t seg_b = sb + SEG_OFF + warp * 64;
        if (some)
            asm volatile("st.shared.u32 [%0], %1;" ::"r"(seg_b + 4 * __popc(__ballot_sync(__activemask(), true) & ((1u << lane) - 1u))),
                         "r"((warp + NCOL * lane) * EPC_MAX + (int)((sv >> 12) & 0xfffu) - incl + (int)(sv & 0xfffu)) : "memory");
        __syncwarp();
        if (!some) incl = -1;
        const uint32_t le = (2u << lane) - 1u;
        uint32_t sg = seg_b;
#pragma unroll
        for (int r = 0; r < RND; r++) {
            uint32_t bit;
            asm("shl.b32 %0, 1, %1;" : "=r"(bit) : "r"(incl - 32 * r));
            const uint32_t ends = __reduce_or_sync(0xffffffffu, bit);
            gp[r] = g_staged + (lane + 32 * r + (int)lds32(sg + 4 * __popc(ends & le)));
            sg += 4 * __popc(ends);
            ent[r].y = tag;
        }
        if (warp < 8) {
            mbar_wait(sb + MISC_OFF + 16, 0);
#pragma unroll
            for (int j = 0; j < 4; j++) {
                const int dj = (j & 1) + 4 * (j >> 1);
                const uint32_t p = sb + WR_OFF + t * 4 * 256 + 32 * (2 * ((warp >> 2) & 1) + dj) + 4 * (g ^ dj);
#pragma unroll
                for (int i = 0; i < 4; i++) wr[j][i] = lds32(p + i * 256);
            }
#pragma unroll
            for (int j = 0; j < 4; j++) {
                uint32_t h[4];
#pragma unroll
                for (int i = 0; i < 4; i++) h[i] = half_bf16x2(wr[j][i]);
                wr[j][0] = __byte_perm(h[0], h[1], 0x5410);
                wr[j][1] = __byte_perm(h[0], h[1], 0x7632);
                wr[j][2] = __byte_perm(h[2], h[3], 0x5410);
                wr[j][3] = __byte_perm(h[2], h[3], 0x7632);
            }
        }
        const uint32_t ts = poll(&tp->y, (epoch << 16) | (ms.ref & 0xffffu), 16);
#pragma unroll
        for (int r = 0; r < RND; r++)
            if (lane + 32 * r < tot) ent[r] = ld_entry(gp[r]);
        const int dm = __reduce_max_sync(0xffffffffu, (int)(short)(ts - ms.ref));
        if (lane == 0) {
            atomicMax(&ms.dmax, dm);
            if (tot > 32 * RND) ms.over = 1;
        }
        uint32_t stale = 0;
#pragma unroll
        for (int r = 0; r < RND; r++) stale |= ent[r].y ^ tag;
        if (stale & TAGM) {
#pragma unroll
            for (int r = 0; r < RND; r++)
                if (lane + 32 * r < tot) ent[r] = wait_entry(gp[r], ent[r], tag);
        }
#pragma unroll
        for (int r = 0; r < RND; r++)
            if (lane + 32 * r < tot) rk[r] = atomicAdd(reinterpret_cast<uint32_t*>(smem + BCNT_OFF + (ent[r].x >> 17)), 1u);
    }
    __syncthreads();
    {
        const int grp = warp & 3, u = warp >> 2;
        uint32_t v[3], incl[3], lo[3], hi[3], tt[3];
#pragma unroll
        for (int p = 0; p < 3; p++) {
            uint32_t a[3];
#pragma unroll
            for (int i = 0; i < 3; i++) {
                a[i] = bcnt[(grp + 8 * p) * NB + 32 * i + lane];
                if (p < 2) a[i] += bcnt[(grp + 8 * p + 4) * NB + 32 * i + lane] << 16;
            }
            v[p] = u == 0 ? a[0] : (u == 1 ? a[1] : a[2]);
            incl[p] = v[p];
            lo[p] = __reduce_add_sync(0xffffffffu, u == 0 ? 0u : (u == 1 ? a[0] : a[0] + a[1]));
            tt[p] = __reduce_add_sync(0xffffffffu, a[0] + a[1] + a[2]);
        }
#pragma unroll
        for (int o = 1; o < 32; o <<= 1)
#pragma unroll
            for (int p = 0; p < 3; p++) {
                const uint32_t t_ = __shfl_up_sync(0xffffffffu, incl[p], o);
                if (lane >= o) incl[p] += t_;
            }
        uint32_t all = 0, nq = 0;
#pragma unroll
        for (int p = 0; p < 3; p++) {
            const uint32_t up = (tt[p] + 0x30003u) & 0xfffcfffcu;
            nq += up >> 2;
            tt[p] = up - tt[p];
            incl[p] += lo[p] + tt[p];
            v[p] = incl[p] - v[p];
            lo[p] = warp < 4 && lane == 0 ? 0u : ((v[p] + 0x10001u) >> 2) & 0x3fff3fffu;
            hi[p] = ((incl[p] + 0x10001u) >> 2) & 0x3fff3fffu;
            all += lo[p];
        }
        nq = (nq & 0xffffu) + (nq >> 16);
        uint32_t run = (all & 0xffffu) + (all >> 16) + (nq & 1u) + grp * (GCAP / 4);
#pragma unroll
        for (int i = 0; i < 5; i++) {
            const uint32_t l = (i & 1) ? lo[i >> 1] >> 16 : lo[i >> 1] & 0xffffu, h = (i & 1) ? hi[i >> 1] >> 16 : hi[i >> 1] & 0xffffu;
            const uint32_t tb = (grp + 4 * i) * JCAP;
            bcum[(grp + 4 * i) * NB + 32 * u + lane] = ((i & 1) ? v[i >> 1] >> 16 : v[i >> 1] & 0xffffu) + 4 * tb;
            const uint32_t rel = (run - l - tb) * 16u;
            if (l < h) gi[tb + l] = rel;
            if (l + 1 < h) {
#pragma unroll 1
                for (uint32_t j = l + 1; j < h; j++) gi[tb + j] = rel;
            }
            run += h - l;
        }
        if (warp < 4 && lane == 0) {
            ms.nq[grp] = (int)nq;
            if (4 * nq + 12 > GCAP) ms.over = 1;
        }
    }
    asm volatile("fence.proxy.async.shared::cta;" ::: "memory");
    __syncthreads();
    if (__shfl_sync(0xffffffffu, ms.over + (int)(lane & zero), 0) != 0) {
        slow_cta(smem, x, ef, w_rad, cg, w_mix, out, node0, Sc, tag);
        return;
    }
    auto uni = [&](uint32_t v) { return __shfl_sync(0xffffffffu, v + (lane & zero), 0); };
    auto keep = [&](uint32_t v) { return __shfl_sync(0xffffffffu, v, lane); };
    const int pgrp = (warp + 2) & 3;
    const uint32_t s0 = uni(sb);
    const uint64_t map0 = reinterpret_cast<uint64_t>(&xmap);
    const uint64_t map = ((uint64_t)uni((uint32_t)(map0 >> 32)) << 32) | uni((uint32_t)(map0 & 0xffffffffu));
    const uint32_t T0 = uni(clock_lo() + (uint32_t)((int)(short)(ms.ref + ms.dmax - global_ticks()) * 63 + lead));
    const uint32_t ab = s0 + AUX_OFF + pgrp * AUX_GR, xb = s0 + pgrp * (NST * 2048);
    uint32_t yp = s0 + SY_OFF + pgrp * GCAP * 4;
    const uint32_t noct = uni((uint32_t)(ms.nq[pgrp] + 1) >> 1);
    const uint32_t yend = yp + noct * 32 + 32;
    const uint32_t e_l = keep(SE_OFF - SY_OFF + (4 * (g & 1) + (g >> 1)) * 4);
    uint32_t h_l = keep(sb + SH_OFF + pgrp * GCAP * 8 + g * 8 + (t & 1) * 4);
    const uint32_t f_l = keep(sb + AUX_OFF + pgrp * AUX_GR + 512 + (g >> 1) * 32 + (t & 1) * 16 + (~g & 1));
    const uint32_t w_l = keep(sb + AUX_OFF + pgrp * AUX_GR + lane * 8);
    const char* efl = ef + keep(t * 8);
    const bool odd = g & 1;
    const uint32_t bytes = keep(lane == 0 ? OCT_BYTES : 0u);
    {
        auto put = [&](bool ok, uint32_t p4, uint32_t y, uint32_t e) {
            asm volatile("{\n\t.reg .pred P;\n\tsetp.ne.u32 P, %0, 0;\n\t@P st.shared.u32 [%1+%4], %2;\n\t@P st.shared.u32 [%1+%5], %3;\n\t}"
                         ::"r"((uint32_t)ok), "r"(sb + p4), "r"(y), "r"(e), "n"(SY_OFF), "n"(SE_OFF) : "memory");
        };
        auto puty = [&](bool ok, uint32_t p4, uint32_t h0, uint32_t h1) {
            asm volatile("{\n\t.reg .pred P;\n\tsetp.ne.u32 P, %0, 0;\n\t@P st.shared.v2.u32 [%1+%4], {%2,%3};\n\t}"
                         ::"r"((uint32_t)ok), "r"(sb + 2 * p4), "r"(h0), "r"(h1), "n"(SH_OFF) : "memory");
        };
        auto place = [&](int r0, int r1) {
#pragma unroll
            for (int r = r0; r < r1; r++)
                if (lane + 32 * r < tot) rk[r] += *reinterpret_cast<const uint32_t*>(smem + BCUM_OFF + (ent[r].x >> 17));
#pragma unroll
            for (int r = r0; r < r1; r++)
                if (lane + 32 * r < tot) rk[r] = 4u * rk[r] + gi[rk[r] >> 2];
#pragma unroll
            for (int r = r0; r < r1; r++) put(lane + 32 * r < tot, rk[r], ent[r].x & 0x1ffffu, ent[r].y);
#pragma unroll
            for (int r = r0; r < r1; r++) puty(lane + 32 * r < tot, rk[r], ent[r].z, ent[r].w);
        };
        if (warp < 5) {
            const uint32_t i = tid & 15, grp = (tid >> 4) & 3, tile = min(tid >> 2, 19);
            const uint32_t c0 = bcum[tile * NB], rel = gi[tile * JCAP], nq = ms.nq[grp];
            bool ok = (tid & 3) < (c0 & 3u);
            uint32_t p4 = rel + (tile * JCAP * 4 + (tid & 3)) * 4, e = tile >> 2 << 27;
            if (tid >= 80) {
                ok = tid >= 96 && (i < 8 || (i < 12 && (nq & 1)));
                p4 = (grp * GCAP + (i < 8 ? 4 * ((nq + 1) & ~1u) + i : i - 8)) * 4;
                e = i < 8 ? 6u << 27 : 0u;
            }
            put(ok, p4, ((uint32_t)(tid + 53 * c) & 127u) * 8u, e);
            puty(ok, p4, 0u, 0u);
        }
        place(0, RND0);
        if (tot > 32 * RND0) place(RND0, RND);
    }
    __syncthreads();

    if (warp < 8) {
        asm volatile("setmaxnreg.inc.sync.aligned.u32 232;");
        const int half = warp >> 2, grp = (warp + half) & 3;
        const uint32_t az = __shfl_sync(0xffffffffu, sb + ZERO_OFF + (g >> 1) * 512 + t * 32 + (g & 1) * 16, lane);
        uint32_t sb2;
        asm volatile(
            "{\n"
            ".reg .f32 c<160>, h<16>, th<8>, fz;\n"
            ".reg .b32 x<16>, a<4>, r<4>, e<2>, p<80>, mt, mtn, xa, aa, an, ab, ea, tmp, cnt, st, rl, rh, dum, du2;\n"
            ".reg .b16 lo, hi;\n"
            ".reg .pred pk, pm, pw, pe, d0, d1, d2, d3, d4;\n"
            "mov.f32 fz, 0f00000000;\n"
            "mov.f32 c0, fz; mov.f32 c1, fz; mov.f32 c2, fz; mov.f32 c3, fz; mov.f32 c4, fz; mov.f32 c5, fz; mov.f32 c6, fz; mov.f32 c7, fz;\n"
            "mov.f32 c8, fz; mov.f32 c9, fz; mov.f32 c10, fz; mov.f32 c11, fz; mov.f32 c12, fz; mov.f32 c13, fz; mov.f32 c14, fz; mov.f32 c15, fz;\n"
            "mov.f32 c16, fz; mov.f32 c17, fz; mov.f32 c18, fz; mov.f32 c19, fz; mov.f32 c20, fz; mov.f32 c21, fz; mov.f32 c22, fz; mov.f32 c23, fz;\n"
            "mov.f32 c24, fz; mov.f32 c25, fz; mov.f32 c26, fz; mov.f32 c27, fz; mov.f32 c28, fz; mov.f32 c29, fz; mov.f32 c30, fz; mov.f32 c31, fz;\n"
            "mov.f32 c32, fz; mov.f32 c33, fz; mov.f32 c34, fz; mov.f32 c35, fz; mov.f32 c36, fz; mov.f32 c37, fz; mov.f32 c38, fz; mov.f32 c39, fz;\n"
            "mov.f32 c40, fz; mov.f32 c41, fz; mov.f32 c42, fz; mov.f32 c43, fz; mov.f32 c44, fz; mov.f32 c45, fz; mov.f32 c46, fz; mov.f32 c47, fz;\n"
            "mov.f32 c48, fz; mov.f32 c49, fz; mov.f32 c50, fz; mov.f32 c51, fz; mov.f32 c52, fz; mov.f32 c53, fz; mov.f32 c54, fz; mov.f32 c55, fz;\n"
            "mov.f32 c56, fz; mov.f32 c57, fz; mov.f32 c58, fz; mov.f32 c59, fz; mov.f32 c60, fz; mov.f32 c61, fz; mov.f32 c62, fz; mov.f32 c63, fz;\n"
            "mov.f32 c64, fz; mov.f32 c65, fz; mov.f32 c66, fz; mov.f32 c67, fz; mov.f32 c68, fz; mov.f32 c69, fz; mov.f32 c70, fz; mov.f32 c71, fz;\n"
            "mov.f32 c72, fz; mov.f32 c73, fz; mov.f32 c74, fz; mov.f32 c75, fz; mov.f32 c76, fz; mov.f32 c77, fz; mov.f32 c78, fz; mov.f32 c79, fz;\n"
            "mov.f32 c80, fz; mov.f32 c81, fz; mov.f32 c82, fz; mov.f32 c83, fz; mov.f32 c84, fz; mov.f32 c85, fz; mov.f32 c86, fz; mov.f32 c87, fz;\n"
            "mov.f32 c88, fz; mov.f32 c89, fz; mov.f32 c90, fz; mov.f32 c91, fz; mov.f32 c92, fz; mov.f32 c93, fz; mov.f32 c94, fz; mov.f32 c95, fz;\n"
            "mov.f32 c96, fz; mov.f32 c97, fz; mov.f32 c98, fz; mov.f32 c99, fz; mov.f32 c100, fz; mov.f32 c101, fz; mov.f32 c102, fz; mov.f32 c103, fz;\n"
            "mov.f32 c104, fz; mov.f32 c105, fz; mov.f32 c106, fz; mov.f32 c107, fz; mov.f32 c108, fz; mov.f32 c109, fz; mov.f32 c110, fz; mov.f32 c111, fz;\n"
            "mov.f32 c112, fz; mov.f32 c113, fz; mov.f32 c114, fz; mov.f32 c115, fz; mov.f32 c116, fz; mov.f32 c117, fz; mov.f32 c118, fz; mov.f32 c119, fz;\n"
            "mov.f32 c120, fz; mov.f32 c121, fz; mov.f32 c122, fz; mov.f32 c123, fz; mov.f32 c124, fz; mov.f32 c125, fz; mov.f32 c126, fz; mov.f32 c127, fz;\n"
            "mov.f32 c128, fz; mov.f32 c129, fz; mov.f32 c130, fz; mov.f32 c131, fz; mov.f32 c132, fz; mov.f32 c133, fz; mov.f32 c134, fz; mov.f32 c135, fz;\n"
            "mov.f32 c136, fz; mov.f32 c137, fz; mov.f32 c138, fz; mov.f32 c139, fz; mov.f32 c140, fz; mov.f32 c141, fz; mov.f32 c142, fz; mov.f32 c143, fz;\n"
            "mov.f32 c144, fz; mov.f32 c145, fz; mov.f32 c146, fz; mov.f32 c147, fz; mov.f32 c148, fz; mov.f32 c149, fz; mov.f32 c150, fz; mov.f32 c151, fz;\n"
            "mov.f32 c152, fz; mov.f32 c153, fz; mov.f32 c154, fz; mov.f32 c155, fz; mov.f32 c156, fz; mov.f32 c157, fz; mov.f32 c158, fz; mov.f32 c159, fz;\n"
            "mov.b32 x0, 0; mov.b32 x1, 0; mov.b32 x2, 0; mov.b32 x3, 0; mov.b32 x4, 0; mov.b32 x5, 0; mov.b32 x6, 0; mov.b32 x7, 0; mov.b32 x8, 0; mov.b32 x9, 0; mov.b32 x10, 0; mov.b32 x11, 0; mov.b32 x12, 0; mov.b32 x13, 0; mov.b32 x14, 0; mov.b32 x15, 0;\n"
            "mov.b32 a0, 0; mov.b32 a1, 0; mov.b32 a2, 0; mov.b32 a3, 0;\n"
            "elect.sync _|pe, 0xffffffff;\n"
            "mov.b32 xa, %1; mov.b32 aa, %2; mov.b32 ea, %4;\n"
            "mov.u32 cnt, 0; and.b32 tmp, aa, 0xffffff80;\n"
            "S0L: mbarrier.try_wait.parity.shared::cta.b64 pw, [tmp+520], 0; @pw bra.uni S0D;\n"
            "add.u32 cnt, cnt, 1; setp.lt.u32 pk, cnt, 1000000; @pk bra.uni S0L; trap;\n"
            "S0D:\n"
            "ld.shared.v2.u32 {e0,e1}, [ea]; ld.shared.u32 mt, [aa+512];\n"
            "mma.sync.aligned.m16n8k16.row.col.f32.bf16.bf16.f32 {h0,h1,h2,h3}, {%7,%8,%9,%10}, {e0,e1}, {fz,fz,fz,fz};\n"
            "mma.sync.aligned.m16n8k16.row.col.f32.bf16.bf16.f32 {h4,h5,h6,h7}, {%11,%12,%13,%14}, {e0,e1}, {fz,fz,fz,fz};\n"
            "mma.sync.aligned.m16n8k16.row.col.f32.bf16.bf16.f32 {h8,h9,h10,h11}, {%15,%16,%17,%18}, {e0,e1}, {fz,fz,fz,fz};\n"
            "mma.sync.aligned.m16n8k16.row.col.f32.bf16.bf16.f32 {h12,h13,h14,h15}, {%19,%20,%21,%22}, {e0,e1}, {fz,fz,fz,fz};\n"
            "or.b32 a0, e0, mt; and.b32 a0, a0, %5;\n"
            "add.u32 xa, xa, 2048; add.u32 aa, aa, 2560; mov.u32 st, 1;\n"
            "mov.u32 cnt, 0; and.b32 tmp, aa, 0xffffff80;\n"
            "S1L: mbarrier.try_wait.parity.shared::cta.b64 pw, [tmp+520], 0; @pw bra.uni S1D;\n"
            "add.u32 cnt, cnt, 1; setp.lt.u32 pk, cnt, 1000000; @pk bra.uni S1L; trap;\n"
            "S1D:\n"
            "B0_0:\n"
            "xor.b32 tmp, mt, %3; and.b32 tmp, tmp, 1536; setp.eq.u32 pm, tmp, 0; selp.b32 ab, aa, %3, pm;\n"
            "and.b32 tmp, mt, 2048; setp.ne.u32 d0, tmp, 0; and.b32 tmp, mt, 4096; setp.ne.u32 d1, tmp, 0; and.b32 tmp, mt, 8192; setp.ne.u32 d2, tmp, 0;\n"
            "mad.lo.u32 cnt, a0, %5, ea; mad.lo.s32 ea, st, 2560, ea;\n"
            "ld.shared.u32 mt, [aa+512];\n"
            "mma.sync.aligned.m16n8k16.row.col.f32.bf16.bf16.f32 {c0,c1,c2,c3}, {a0,a1,a2,a3}, {x0,x1}, {c0,c1,c2,c3};\n"
            "mma.sync.aligned.m16n8k16.row.col.f32.bf16.bf16.f32 {c4,c5,c6,c7}, {a0,a1,a2,a3}, {x2,x3}, {c4,c5,c6,c7};\n"
            "ld.shared.v4.u32 {x0,x1,x2,x3}, [xa+0];\n"
            "tanh.approx.f32 th0, h0;\n"
            "tanh.approx.f32 th1, h2;\n"
            "fma.rn.f32 th0, h0, th0, h0;\n"
            "fma.rn.f32 th1, h2, th1, h2;\n"
            "cvt.rn.bf16x2.f32 r0, th1, th0;\n"
            "mma.sync.aligned.m16n8k16.row.col.f32.bf16.bf16.f32 {c8,c9,c10,c11}, {a0,a1,a2,a3}, {x4,x5}, {c8,c9,c10,c11};\n"
            "mma.sync.aligned.m16n8k16.row.col.f32.bf16.bf16.f32 {c12,c13,c14,c15}, {a0,a1,a2,a3}, {x6,x7}, {c12,c13,c14,c15};\n"
            "ld.shared.v4.u32 {x4,x5,x6,x7}, [xa+128];\n"
            "tanh.approx.f32 th2, h4;\n"
            "tanh.approx.f32 th3, h6;\n"
            "fma.rn.f32 th2, h4, th2, h4;\n"
            "fma.rn.f32 th3, h6, th3, h6;\n"
            "cvt.rn.bf16x2.f32 r1, th3, th2;\n"
            "mma.sync.aligned.m16n8k16.row.col.f32.bf16.bf16.f32 {c16,c17,c18,c19}, {a0,a1,a2,a3}, {x8,x9}, {c16,c17,c18,c19};\n"
            "mma.sync.aligned.m16n8k16.row.col.f32.bf16.bf16.f32 {c20,c21,c22,c23}, {a0,a1,a2,a3}, {x10,x11}, {c20,c21,c22,c23};\n"
            "ld.shared.v4.u32 {x8,x9,x10,x11}, [xa+512];\n"
            "tanh.approx.f32 th4, h8;\n"
            "tanh.approx.f32 th5, h10;\n"
            "fma.rn.f32 th4, h8, th4, h8;\n"
            "fma.rn.f32 th5, h10, th5, h10;\n"
            "cvt.rn.bf16x2.f32 r2, th5, th4;\n"
            "mma.sync.aligned.m16n8k16.row.col.f32.bf16.bf16.f32 {c24,c25,c26,c27}, {a0,a1,a2,a3}, {x12,x13}, {c24,c25,c26,c27};\n"
            "mma.sync.aligned.m16n8k16.row.col.f32.bf16.bf16.f32 {c28,c29,c30,c31}, {a0,a1,a2,a3}, {x14,x15}, {c28,c29,c30,c31};\n"
            "ld.shared.v4.u32 {x12,x13,x14,x15}, [xa+640];\n"
            "tanh.approx.f32 th6, h12;\n"
            "tanh.approx.f32 th7, h14;\n"
            "fma.rn.f32 th6, h12, th6, h12;\n"
            "fma.rn.f32 th7, h14, th7, h14;\n"
            "cvt.rn.bf16x2.f32 r3, th7, th6;\n"
            "ld.shared.v4.u32 {a0,a1,a2,a3}, [ab+0];\n"
            "@pe mbarrier.arrive.shared::cta.b64 _, [cnt+280];\n"
            "mov.b32 {lo,hi}, r0; mov.b32 rl, {lo,lo}; mov.b32 rh, {hi,hi};\n"
            "mul.bf16x2 x0, x0, rl; mul.bf16x2 x1, x1, rl; mul.bf16x2 x2, x2, rh; mul.bf16x2 x3, x3, rh;\n"
            "mov.b32 {lo,hi}, r1; mov.b32 rl, {lo,lo}; mov.b32 rh, {hi,hi};\n"
            "mul.bf16x2 x4, x4, rl; mul.bf16x2 x5, x5, rl; mul.bf16x2 x6, x6, rh; mul.bf16x2 x7, x7, rh;\n"
            "mov.b32 {lo,hi}, r2; mov.b32 rl, {lo,lo}; mov.b32 rh, {hi,hi};\n"
            "mul.bf16x2 x8, x8, rl; mul.bf16x2 x9, x9, rl; mul.bf16x2 x10, x10, rh; mul.bf16x2 x11, x11, rh;\n"
            "mov.b32 {lo,hi}, r3; mov.b32 rl, {lo,lo}; mov.b32 rh, {hi,hi};\n"
            "mul.bf16x2 x12, x12, rl; mul.bf16x2 x13, x13, rl; mul.bf16x2 x14, x14, rh; mul.bf16x2 x15, x15, rh;\n"
            "@d1 bra.uni L1; @d2 bra.uni B1_4; @d0 bra.uni B1_1; bra.uni B1_0;\n"
            "B0_1:\n"
            "xor.b32 tmp, mt, %3; and.b32 tmp, tmp, 1536; setp.eq.u32 pm, tmp, 0; selp.b32 ab, aa, %3, pm;\n"
            "and.b32 tmp, mt, 2048; setp.ne.u32 d0, tmp, 0; and.b32 tmp, mt, 4096; setp.ne.u32 d1, tmp, 0; and.b32 tmp, mt, 8192; setp.ne.u32 d2, tmp, 0;\n"
            "mad.lo.u32 cnt, a0, %5, ea; mad.lo.s32 ea, st, 2560, ea;\n"
            "ld.shared.u32 mt, [aa+512];\n"
            "mma.sync.aligned.m16n8k16.row.col.f32.bf16.bf16.f32 {c32,c33,c34,c35}, {a0,a1,a2,a3}, {x0,x1}, {c32,c33,c34,c35};\n"
            "mma.sync.aligned.m16n8k16.row.col.f32.bf16.bf16.f32 {c36,c37,c38,c39}, {a0,a1,a2,a3}, {x2,x3}, {c36,c37,c38,c39};\n"
            "ld.shared.v4.u32 {x0,x1,x2,x3}, [xa+0];\n"
            "tanh.approx.f32 th0, h0;\n"
            "tanh.approx.f32 th1, h2;\n"
            "fma.rn.f32 th0, h0, th0, h0;\n"
            "fma.rn.f32 th1, h2, th1, h2;\n"
            "cvt.rn.bf16x2.f32 r0, th1, th0;\n"
            "mma.sync.aligned.m16n8k16.row.col.f32.bf16.bf16.f32 {c40,c41,c42,c43}, {a0,a1,a2,a3}, {x4,x5}, {c40,c41,c42,c43};\n"
            "mma.sync.aligned.m16n8k16.row.col.f32.bf16.bf16.f32 {c44,c45,c46,c47}, {a0,a1,a2,a3}, {x6,x7}, {c44,c45,c46,c47};\n"
            "ld.shared.v4.u32 {x4,x5,x6,x7}, [xa+128];\n"
            "tanh.approx.f32 th2, h4;\n"
            "tanh.approx.f32 th3, h6;\n"
            "fma.rn.f32 th2, h4, th2, h4;\n"
            "fma.rn.f32 th3, h6, th3, h6;\n"
            "cvt.rn.bf16x2.f32 r1, th3, th2;\n"
            "mma.sync.aligned.m16n8k16.row.col.f32.bf16.bf16.f32 {c48,c49,c50,c51}, {a0,a1,a2,a3}, {x8,x9}, {c48,c49,c50,c51};\n"
            "mma.sync.aligned.m16n8k16.row.col.f32.bf16.bf16.f32 {c52,c53,c54,c55}, {a0,a1,a2,a3}, {x10,x11}, {c52,c53,c54,c55};\n"
            "ld.shared.v4.u32 {x8,x9,x10,x11}, [xa+512];\n"
            "tanh.approx.f32 th4, h8;\n"
            "tanh.approx.f32 th5, h10;\n"
            "fma.rn.f32 th4, h8, th4, h8;\n"
            "fma.rn.f32 th5, h10, th5, h10;\n"
            "cvt.rn.bf16x2.f32 r2, th5, th4;\n"
            "mma.sync.aligned.m16n8k16.row.col.f32.bf16.bf16.f32 {c56,c57,c58,c59}, {a0,a1,a2,a3}, {x12,x13}, {c56,c57,c58,c59};\n"
            "mma.sync.aligned.m16n8k16.row.col.f32.bf16.bf16.f32 {c60,c61,c62,c63}, {a0,a1,a2,a3}, {x14,x15}, {c60,c61,c62,c63};\n"
            "ld.shared.v4.u32 {x12,x13,x14,x15}, [xa+640];\n"
            "tanh.approx.f32 th6, h12;\n"
            "tanh.approx.f32 th7, h14;\n"
            "fma.rn.f32 th6, h12, th6, h12;\n"
            "fma.rn.f32 th7, h14, th7, h14;\n"
            "cvt.rn.bf16x2.f32 r3, th7, th6;\n"
            "ld.shared.v4.u32 {a0,a1,a2,a3}, [ab+0];\n"
            "@pe mbarrier.arrive.shared::cta.b64 _, [cnt+280];\n"
            "mov.b32 {lo,hi}, r0; mov.b32 rl, {lo,lo}; mov.b32 rh, {hi,hi};\n"
            "mul.bf16x2 x0, x0, rl; mul.bf16x2 x1, x1, rl; mul.bf16x2 x2, x2, rh; mul.bf16x2 x3, x3, rh;\n"
            "mov.b32 {lo,hi}, r1; mov.b32 rl, {lo,lo}; mov.b32 rh, {hi,hi};\n"
            "mul.bf16x2 x4, x4, rl; mul.bf16x2 x5, x5, rl; mul.bf16x2 x6, x6, rh; mul.bf16x2 x7, x7, rh;\n"
            "mov.b32 {lo,hi}, r2; mov.b32 rl, {lo,lo}; mov.b32 rh, {hi,hi};\n"
            "mul.bf16x2 x8, x8, rl; mul.bf16x2 x9, x9, rl; mul.bf16x2 x10, x10, rh; mul.bf16x2 x11, x11, rh;\n"
            "mov.b32 {lo,hi}, r3; mov.b32 rl, {lo,lo}; mov.b32 rh, {hi,hi};\n"
            "mul.bf16x2 x12, x12, rl; mul.bf16x2 x13, x13, rl; mul.bf16x2 x14, x14, rh; mul.bf16x2 x15, x15, rh;\n"
            "@d1 bra.uni L1; @d2 bra.uni B1_4; @d0 bra.uni B1_1; bra.uni B1_0;\n"
            "L0: @d0 bra.uni B0_3;\n"
            "B0_2:\n"
            "xor.b32 tmp, mt, %3; and.b32 tmp, tmp, 1536; setp.eq.u32 pm, tmp, 0; selp.b32 ab, aa, %3, pm;\n"
            "and.b32 tmp, mt, 2048; setp.ne.u32 d0, tmp, 0; and.b32 tmp, mt, 4096; setp.ne.u32 d1, tmp, 0; and.b32 tmp, mt, 8192; setp.ne.u32 d2, tmp, 0;\n"
            "mad.lo.u32 cnt, a0, %5, ea; mad.lo.s32 ea, st, 2560, ea;\n"
            "ld.shared.u32 mt, [aa+512];\n"
            "mma.sync.aligned.m16n8k16.row.col.f32.bf16.bf16.f32 {c64,c65,c66,c67}, {a0,a1,a2,a3}, {x0,x1}, {c64,c65,c66,c67};\n"
            "mma.sync.aligned.m16n8k16.row.col.f32.bf16.bf16.f32 {c68,c69,c70,c71}, {a0,a1,a2,a3}, {x2,x3}, {c68,c69,c70,c71};\n"
            "ld.shared.v4.u32 {x0,x1,x2,x3}, [xa+0];\n"
            "tanh.approx.f32 th0, h0;\n"
            "tanh.approx.f32 th1, h2;\n"
            "fma.rn.f32 th0, h0, th0, h0;\n"
            "fma.rn.f32 th1, h2, th1, h2;\n"
            "cvt.rn.bf16x2.f32 r0, th1, th0;\n"
            "mma.sync.aligned.m16n8k16.row.col.f32.bf16.bf16.f32 {c72,c73,c74,c75}, {a0,a1,a2,a3}, {x4,x5}, {c72,c73,c74,c75};\n"
            "mma.sync.aligned.m16n8k16.row.col.f32.bf16.bf16.f32 {c76,c77,c78,c79}, {a0,a1,a2,a3}, {x6,x7}, {c76,c77,c78,c79};\n"
            "ld.shared.v4.u32 {x4,x5,x6,x7}, [xa+128];\n"
            "tanh.approx.f32 th2, h4;\n"
            "tanh.approx.f32 th3, h6;\n"
            "fma.rn.f32 th2, h4, th2, h4;\n"
            "fma.rn.f32 th3, h6, th3, h6;\n"
            "cvt.rn.bf16x2.f32 r1, th3, th2;\n"
            "mma.sync.aligned.m16n8k16.row.col.f32.bf16.bf16.f32 {c80,c81,c82,c83}, {a0,a1,a2,a3}, {x8,x9}, {c80,c81,c82,c83};\n"
            "mma.sync.aligned.m16n8k16.row.col.f32.bf16.bf16.f32 {c84,c85,c86,c87}, {a0,a1,a2,a3}, {x10,x11}, {c84,c85,c86,c87};\n"
            "ld.shared.v4.u32 {x8,x9,x10,x11}, [xa+512];\n"
            "tanh.approx.f32 th4, h8;\n"
            "tanh.approx.f32 th5, h10;\n"
            "fma.rn.f32 th4, h8, th4, h8;\n"
            "fma.rn.f32 th5, h10, th5, h10;\n"
            "cvt.rn.bf16x2.f32 r2, th5, th4;\n"
            "mma.sync.aligned.m16n8k16.row.col.f32.bf16.bf16.f32 {c88,c89,c90,c91}, {a0,a1,a2,a3}, {x12,x13}, {c88,c89,c90,c91};\n"
            "mma.sync.aligned.m16n8k16.row.col.f32.bf16.bf16.f32 {c92,c93,c94,c95}, {a0,a1,a2,a3}, {x14,x15}, {c92,c93,c94,c95};\n"
            "ld.shared.v4.u32 {x12,x13,x14,x15}, [xa+640];\n"
            "tanh.approx.f32 th6, h12;\n"
            "tanh.approx.f32 th7, h14;\n"
            "fma.rn.f32 th6, h12, th6, h12;\n"
            "fma.rn.f32 th7, h14, th7, h14;\n"
            "cvt.rn.bf16x2.f32 r3, th7, th6;\n"
            "ld.shared.v4.u32 {a0,a1,a2,a3}, [ab+0];\n"
            "@pe mbarrier.arrive.shared::cta.b64 _, [cnt+280];\n"
            "mov.b32 {lo,hi}, r0; mov.b32 rl, {lo,lo}; mov.b32 rh, {hi,hi};\n"
            "mul.bf16x2 x0, x0, rl; mul.bf16x2 x1, x1, rl; mul.bf16x2 x2, x2, rh; mul.bf16x2 x3, x3, rh;\n"
            "mov.b32 {lo,hi}, r1; mov.b32 rl, {lo,lo}; mov.b32 rh, {hi,hi};\n"
            "mul.bf16x2 x4, x4, rl; mul.bf16x2 x5, x5, rl; mul.bf16x2 x6, x6, rh; mul.bf16x2 x7, x7, rh;\n"
            "mov.b32 {lo,hi}, r2; mov.b32 rl, {lo,lo}; mov.b32 rh, {hi,hi};\n"
            "mul.bf16x2 x8, x8, rl; mul.bf16x2 x9, x9, rl; mul.bf16x2 x10, x10, rh; mul.bf16x2 x11, x11, rh;\n"
            "mov.b32 {lo,hi}, r3; mov.b32 rl, {lo,lo}; mov.b32 rh, {hi,hi};\n"
            "mul.bf16x2 x12, x12, rl; mul.bf16x2 x13, x13, rl; mul.bf16x2 x14, x14, rh; mul.bf16x2 x15, x15, rh;\n"
            "@d1 bra.uni L1; @d2 bra.uni B1_4; @d0 bra.uni B1_1; bra.uni B1_0;\n"
            "B0_3:\n"
            "xor.b32 tmp, mt, %3; and.b32 tmp, tmp, 1536; setp.eq.u32 pm, tmp, 0; selp.b32 ab, aa, %3, pm;\n"
            "and.b32 tmp, mt, 2048; setp.ne.u32 d0, tmp, 0; and.b32 tmp, mt, 4096; setp.ne.u32 d1, tmp, 0; and.b32 tmp, mt, 8192; setp.ne.u32 d2, tmp, 0;\n"
            "mad.lo.u32 cnt, a0, %5, ea; mad.lo.s32 ea, st, 2560, ea;\n"
            "ld.shared.u32 mt, [aa+512];\n"
            "mma.sync.aligned.m16n8k16.row.col.f32.bf16.bf16.f32 {c96,c97,c98,c99}, {a0,a1,a2,a3}, {x0,x1}, {c96,c97,c98,c99};\n"
            "mma.sync.aligned.m16n8k16.row.col.f32.bf16.bf16.f32 {c100,c101,c102,c103}, {a0,a1,a2,a3}, {x2,x3}, {c100,c101,c102,c103};\n"
            "ld.shared.v4.u32 {x0,x1,x2,x3}, [xa+0];\n"
            "tanh.approx.f32 th0, h0;\n"
            "tanh.approx.f32 th1, h2;\n"
            "fma.rn.f32 th0, h0, th0, h0;\n"
            "fma.rn.f32 th1, h2, th1, h2;\n"
            "cvt.rn.bf16x2.f32 r0, th1, th0;\n"
            "mma.sync.aligned.m16n8k16.row.col.f32.bf16.bf16.f32 {c104,c105,c106,c107}, {a0,a1,a2,a3}, {x4,x5}, {c104,c105,c106,c107};\n"
            "mma.sync.aligned.m16n8k16.row.col.f32.bf16.bf16.f32 {c108,c109,c110,c111}, {a0,a1,a2,a3}, {x6,x7}, {c108,c109,c110,c111};\n"
            "ld.shared.v4.u32 {x4,x5,x6,x7}, [xa+128];\n"
            "tanh.approx.f32 th2, h4;\n"
            "tanh.approx.f32 th3, h6;\n"
            "fma.rn.f32 th2, h4, th2, h4;\n"
            "fma.rn.f32 th3, h6, th3, h6;\n"
            "cvt.rn.bf16x2.f32 r1, th3, th2;\n"
            "mma.sync.aligned.m16n8k16.row.col.f32.bf16.bf16.f32 {c112,c113,c114,c115}, {a0,a1,a2,a3}, {x8,x9}, {c112,c113,c114,c115};\n"
            "mma.sync.aligned.m16n8k16.row.col.f32.bf16.bf16.f32 {c116,c117,c118,c119}, {a0,a1,a2,a3}, {x10,x11}, {c116,c117,c118,c119};\n"
            "ld.shared.v4.u32 {x8,x9,x10,x11}, [xa+512];\n"
            "tanh.approx.f32 th4, h8;\n"
            "tanh.approx.f32 th5, h10;\n"
            "fma.rn.f32 th4, h8, th4, h8;\n"
            "fma.rn.f32 th5, h10, th5, h10;\n"
            "cvt.rn.bf16x2.f32 r2, th5, th4;\n"
            "mma.sync.aligned.m16n8k16.row.col.f32.bf16.bf16.f32 {c120,c121,c122,c123}, {a0,a1,a2,a3}, {x12,x13}, {c120,c121,c122,c123};\n"
            "mma.sync.aligned.m16n8k16.row.col.f32.bf16.bf16.f32 {c124,c125,c126,c127}, {a0,a1,a2,a3}, {x14,x15}, {c124,c125,c126,c127};\n"
            "ld.shared.v4.u32 {x12,x13,x14,x15}, [xa+640];\n"
            "tanh.approx.f32 th6, h12;\n"
            "tanh.approx.f32 th7, h14;\n"
            "fma.rn.f32 th6, h12, th6, h12;\n"
            "fma.rn.f32 th7, h14, th7, h14;\n"
            "cvt.rn.bf16x2.f32 r3, th7, th6;\n"
            "ld.shared.v4.u32 {a0,a1,a2,a3}, [ab+0];\n"
            "@pe mbarrier.arrive.shared::cta.b64 _, [cnt+280];\n"
            "mov.b32 {lo,hi}, r0; mov.b32 rl, {lo,lo}; mov.b32 rh, {hi,hi};\n"
            "mul.bf16x2 x0, x0, rl; mul.bf16x2 x1, x1, rl; mul.bf16x2 x2, x2, rh; mul.bf16x2 x3, x3, rh;\n"
            "mov.b32 {lo,hi}, r1; mov.b32 rl, {lo,lo}; mov.b32 rh, {hi,hi};\n"
            "mul.bf16x2 x4, x4, rl; mul.bf16x2 x5, x5, rl; mul.bf16x2 x6, x6, rh; mul.bf16x2 x7, x7, rh;\n"
            "mov.b32 {lo,hi}, r2; mov.b32 rl, {lo,lo}; mov.b32 rh, {hi,hi};\n"
            "mul.bf16x2 x8, x8, rl; mul.bf16x2 x9, x9, rl; mul.bf16x2 x10, x10, rh; mul.bf16x2 x11, x11, rh;\n"
            "mov.b32 {lo,hi}, r3; mov.b32 rl, {lo,lo}; mov.b32 rh, {hi,hi};\n"
            "mul.bf16x2 x12, x12, rl; mul.bf16x2 x13, x13, rl; mul.bf16x2 x14, x14, rh; mul.bf16x2 x15, x15, rh;\n"
            "@d1 bra.uni L1; @d2 bra.uni B1_4; @d0 bra.uni B1_1; bra.uni B1_0;\n"
            "B0_4:\n"
            "xor.b32 tmp, mt, %3; and.b32 tmp, tmp, 1536; setp.eq.u32 pm, tmp, 0; selp.b32 ab, aa, %3, pm;\n"
            "and.b32 tmp, mt, 2048; setp.ne.u32 d0, tmp, 0; and.b32 tmp, mt, 4096; setp.ne.u32 d1, tmp, 0; and.b32 tmp, mt, 8192; setp.ne.u32 d2, tmp, 0;\n"
            "mad.lo.u32 cnt, a0, %5, ea; mad.lo.s32 ea, st, 2560, ea;\n"
            "ld.shared.u32 mt, [aa+512];\n"
            "mma.sync.aligned.m16n8k16.row.col.f32.bf16.bf16.f32 {c128,c129,c130,c131}, {a0,a1,a2,a3}, {x0,x1}, {c128,c129,c130,c131};\n"
            "mma.sync.aligned.m16n8k16.row.col.f32.bf16.bf16.f32 {c132,c133,c134,c135}, {a0,a1,a2,a3}, {x2,x3}, {c132,c133,c134,c135};\n"
            "ld.shared.v4.u32 {x0,x1,x2,x3}, [xa+0];\n"
            "tanh.approx.f32 th0, h0;\n"
            "tanh.approx.f32 th1, h2;\n"
            "fma.rn.f32 th0, h0, th0, h0;\n"
            "fma.rn.f32 th1, h2, th1, h2;\n"
            "cvt.rn.bf16x2.f32 r0, th1, th0;\n"
            "mma.sync.aligned.m16n8k16.row.col.f32.bf16.bf16.f32 {c136,c137,c138,c139}, {a0,a1,a2,a3}, {x4,x5}, {c136,c137,c138,c139};\n"
            "mma.sync.aligned.m16n8k16.row.col.f32.bf16.bf16.f32 {c140,c141,c142,c143}, {a0,a1,a2,a3}, {x6,x7}, {c140,c141,c142,c143};\n"
            "ld.shared.v4.u32 {x4,x5,x6,x7}, [xa+128];\n"
            "tanh.approx.f32 th2, h4;\n"
            "tanh.approx.f32 th3, h6;\n"
            "fma.rn.f32 th2, h4, th2, h4;\n"
            "fma.rn.f32 th3, h6, th3, h6;\n"
            "cvt.rn.bf16x2.f32 r1, th3, th2;\n"
            "mma.sync.aligned.m16n8k16.row.col.f32.bf16.bf16.f32 {c144,c145,c146,c147}, {a0,a1,a2,a3}, {x8,x9}, {c144,c145,c146,c147};\n"
            "mma.sync.aligned.m16n8k16.row.col.f32.bf16.bf16.f32 {c148,c149,c150,c151}, {a0,a1,a2,a3}, {x10,x11}, {c148,c149,c150,c151};\n"
            "ld.shared.v4.u32 {x8,x9,x10,x11}, [xa+512];\n"
            "tanh.approx.f32 th4, h8;\n"
            "tanh.approx.f32 th5, h10;\n"
            "fma.rn.f32 th4, h8, th4, h8;\n"
            "fma.rn.f32 th5, h10, th5, h10;\n"
            "cvt.rn.bf16x2.f32 r2, th5, th4;\n"
            "mma.sync.aligned.m16n8k16.row.col.f32.bf16.bf16.f32 {c152,c153,c154,c155}, {a0,a1,a2,a3}, {x12,x13}, {c152,c153,c154,c155};\n"
            "mma.sync.aligned.m16n8k16.row.col.f32.bf16.bf16.f32 {c156,c157,c158,c159}, {a0,a1,a2,a3}, {x14,x15}, {c156,c157,c158,c159};\n"
            "ld.shared.v4.u32 {x12,x13,x14,x15}, [xa+640];\n"
            "tanh.approx.f32 th6, h12;\n"
            "tanh.approx.f32 th7, h14;\n"
            "fma.rn.f32 th6, h12, th6, h12;\n"
            "fma.rn.f32 th7, h14, th7, h14;\n"
            "cvt.rn.bf16x2.f32 r3, th7, th6;\n"
            "ld.shared.v4.u32 {a0,a1,a2,a3}, [ab+0];\n"
            "@pe mbarrier.arrive.shared::cta.b64 _, [cnt+280];\n"
            "mov.b32 {lo,hi}, r0; mov.b32 rl, {lo,lo}; mov.b32 rh, {hi,hi};\n"
            "mul.bf16x2 x0, x0, rl; mul.bf16x2 x1, x1, rl; mul.bf16x2 x2, x2, rh; mul.bf16x2 x3, x3, rh;\n"
            "mov.b32 {lo,hi}, r1; mov.b32 rl, {lo,lo}; mov.b32 rh, {hi,hi};\n"
            "mul.bf16x2 x4, x4, rl; mul.bf16x2 x5, x5, rl; mul.bf16x2 x6, x6, rh; mul.bf16x2 x7, x7, rh;\n"
            "mov.b32 {lo,hi}, r2; mov.b32 rl, {lo,lo}; mov.b32 rh, {hi,hi};\n"
            "mul.bf16x2 x8, x8, rl; mul.bf16x2 x9, x9, rl; mul.bf16x2 x10, x10, rh; mul.bf16x2 x11, x11, rh;\n"
            "mov.b32 {lo,hi}, r3; mov.b32 rl, {lo,lo}; mov.b32 rh, {hi,hi};\n"
            "mul.bf16x2 x12, x12, rl; mul.bf16x2 x13, x13, rl; mul.bf16x2 x14, x14, rh; mul.bf16x2 x15, x15, rh;\n"
            "@d1 bra.uni L1; @d2 bra.uni B1_4; @d0 bra.uni B1_1; bra.uni B1_0;\n"
            "B1_0:\n"
            "xor.b32 tmp, mt, ea; and.b32 tmp, tmp, 192; setp.eq.u32 pm, tmp, 0; selp.b32 ab, aa, %3, pm;\n"
            "and.b32 tmp, mt, 8; setp.ne.u32 d0, tmp, 0; and.b32 tmp, mt, 16; setp.ne.u32 d1, tmp, 0; and.b32 tmp, mt, 32; setp.ne.u32 d2, tmp, 0;\n"
            "ld.shared.v2.u32 {e0,e1}, [ea];\n"
            "shr.s32 st, mt, 24; mad.lo.s32 aa, st, 2560, aa;\n"
            "mma.sync.aligned.m16n8k16.row.col.f32.bf16.bf16.f32 {c0,c1,c2,c3}, {a0,a1,a2,a3}, {x0,x1}, {c0,c1,c2,c3};\n"
            "mma.sync.aligned.m16n8k16.row.col.f32.bf16.bf16.f32 {c4,c5,c6,c7}, {a0,a1,a2,a3}, {x2,x3}, {c4,c5,c6,c7};\n"
            "ld.shared.v4.u32 {x0,x1,x2,x3}, [xa+1024];\n"
            "tanh.approx.f32 th0, h1;\n"
            "tanh.approx.f32 th1, h3;\n"
            "fma.rn.f32 th0, h1, th0, h1;\n"
            "fma.rn.f32 th1, h3, th1, h3;\n"
            "cvt.rn.bf16x2.f32 r0, th1, th0;\n"
            "mma.sync.aligned.m16n8k16.row.col.f32.bf16.bf16.f32 {h0,h1,h2,h3}, {%7,%8,%9,%10}, {e0,e1}, {fz,fz,fz,fz};\n"
            "mma.sync.aligned.m16n8k16.row.col.f32.bf16.bf16.f32 {c8,c9,c10,c11}, {a0,a1,a2,a3}, {x4,x5}, {c8,c9,c10,c11};\n"
            "mma.sync.aligned.m16n8k16.row.col.f32.bf16.bf16.f32 {c12,c13,c14,c15}, {a0,a1,a2,a3}, {x6,x7}, {c12,c13,c14,c15};\n"
            "ld.shared.v4.u32 {x4,x5,x6,x7}, [xa+1152];\n"
            "tanh.approx.f32 th2, h5;\n"
            "tanh.approx.f32 th3, h7;\n"
            "fma.rn.f32 th2, h5, th2, h5;\n"
            "fma.rn.f32 th3, h7, th3, h7;\n"
            "cvt.rn.bf16x2.f32 r1, th3, th2;\n"
            "mma.sync.aligned.m16n8k16.row.col.f32.bf16.bf16.f32 {h4,h5,h6,h7}, {%11,%12,%13,%14}, {e0,e1}, {fz,fz,fz,fz};\n"
            "mma.sync.aligned.m16n8k16.row.col.f32.bf16.bf16.f32 {c16,c17,c18,c19}, {a0,a1,a2,a3}, {x8,x9}, {c16,c17,c18,c19};\n"
            "mma.sync.aligned.m16n8k16.row.col.f32.bf16.bf16.f32 {c20,c21,c22,c23}, {a0,a1,a2,a3}, {x10,x11}, {c20,c21,c22,c23};\n"
            "ld.shared.v4.u32 {x8,x9,x10,x11}, [xa+1536];\n"
            "tanh.approx.f32 th4, h9;\n"
            "tanh.approx.f32 th5, h11;\n"
            "fma.rn.f32 th4, h9, th4, h9;\n"
            "fma.rn.f32 th5, h11, th5, h11;\n"
            "cvt.rn.bf16x2.f32 r2, th5, th4;\n"
            "mma.sync.aligned.m16n8k16.row.col.f32.bf16.bf16.f32 {h8,h9,h10,h11}, {%15,%16,%17,%18}, {e0,e1}, {fz,fz,fz,fz};\n"
            "mma.sync.aligned.m16n8k16.row.col.f32.bf16.bf16.f32 {c24,c25,c26,c27}, {a0,a1,a2,a3}, {x12,x13}, {c24,c25,c26,c27};\n"
            "mma.sync.aligned.m16n8k16.row.col.f32.bf16.bf16.f32 {c28,c29,c30,c31}, {a0,a1,a2,a3}, {x14,x15}, {c28,c29,c30,c31};\n"
            "ld.shared.v4.u32 {x12,x13,x14,x15}, [xa+1664];\n"
            "tanh.approx.f32 th6, h13;\n"
            "tanh.approx.f32 th7, h15;\n"
            "fma.rn.f32 th6, h13, th6, h13;\n"
            "fma.rn.f32 th7, h15, th7, h15;\n"
            "cvt.rn.bf16x2.f32 r3, th7, th6;\n"
            "mma.sync.aligned.m16n8k16.row.col.f32.bf16.bf16.f32 {h12,h13,h14,h15}, {%19,%20,%21,%22}, {e0,e1}, {fz,fz,fz,fz};\n"
            "ld.shared.v4.u32 {a0,a1,a2,a3}, [ab+128];\n"
            "and.b32 tmp, aa, 0xffffff80; mbarrier.test_wait.parity.shared::cta.b64 pw, [tmp+520], mt;\n"
            "mad.lo.s32 xa, st, 2048, xa;\n"
            "mov.b32 {lo,hi}, r0; mov.b32 rl, {lo,lo}; mov.b32 rh, {hi,hi};\n"
            "mul.bf16x2 x0, x0, rl; mul.bf16x2 x1, x1, rl; mul.bf16x2 x2, x2, rh; mul.bf16x2 x3, x3, rh;\n"
            "mov.b32 {lo,hi}, r1; mov.b32 rl, {lo,lo}; mov.b32 rh, {hi,hi};\n"
            "mul.bf16x2 x4, x4, rl; mul.bf16x2 x5, x5, rl; mul.bf16x2 x6, x6, rh; mul.bf16x2 x7, x7, rh;\n"
            "mov.b32 {lo,hi}, r2; mov.b32 rl, {lo,lo}; mov.b32 rh, {hi,hi};\n"
            "mul.bf16x2 x8, x8, rl; mul.bf16x2 x9, x9, rl; mul.bf16x2 x10, x10, rh; mul.bf16x2 x11, x11, rh;\n"
            "mov.b32 {lo,hi}, r3; mov.b32 rl, {lo,lo}; mov.b32 rh, {hi,hi};\n"
            "mul.bf16x2 x12, x12, rl; mul.bf16x2 x13, x13, rl; mul.bf16x2 x14, x14, rh; mul.bf16x2 x15, x15, rh;\n"
            "@!pw bra.uni W1;\n"
            "@d2 bra.uni B0_4; @d1 bra.uni L0; @d0 bra.uni B0_1; bra.uni B0_0;\n"
            "B1_1:\n"
            "xor.b32 tmp, mt, ea; and.b32 tmp, tmp, 192; setp.eq.u32 pm, tmp, 0; selp.b32 ab, aa, %3, pm;\n"
            "and.b32 tmp, mt, 8; setp.ne.u32 d0, tmp, 0; and.b32 tmp, mt, 16; setp.ne.u32 d1, tmp, 0; and.b32 tmp, mt, 32; setp.ne.u32 d2, tmp, 0;\n"
            "ld.shared.v2.u32 {e0,e1}, [ea];\n"
            "shr.s32 st, mt, 24; mad.lo.s32 aa, st, 2560, aa;\n"
            "mma.sync.aligned.m16n8k16.row.col.f32.bf16.bf16.f32 {c32,c33,c34,c35}, {a0,a1,a2,a3}, {x0,x1}, {c32,c33,c34,c35};\n"
            "mma.sync.aligned.m16n8k16.row.col.f32.bf16.bf16.f32 {c36,c37,c38,c39}, {a0,a1,a2,a3}, {x2,x3}, {c36,c37,c38,c39};\n"
            "ld.shared.v4.u32 {x0,x1,x2,x3}, [xa+1024];\n"
            "tanh.approx.f32 th0, h1;\n"
            "tanh.approx.f32 th1, h3;\n"
            "fma.rn.f32 th0, h1, th0, h1;\n"
            "fma.rn.f32 th1, h3, th1, h3;\n"
            "cvt.rn.bf16x2.f32 r0, th1, th0;\n"
            "mma.sync.aligned.m16n8k16.row.col.f32.bf16.bf16.f32 {h0,h1,h2,h3}, {%7,%8,%9,%10}, {e0,e1}, {fz,fz,fz,fz};\n"
            "mma.sync.aligned.m16n8k16.row.col.f32.bf16.bf16.f32 {c40,c41,c42,c43}, {a0,a1,a2,a3}, {x4,x5}, {c40,c41,c42,c43};\n"
            "mma.sync.aligned.m16n8k16.row.col.f32.bf16.bf16.f32 {c44,c45,c46,c47}, {a0,a1,a2,a3}, {x6,x7}, {c44,c45,c46,c47};\n"
            "ld.shared.v4.u32 {x4,x5,x6,x7}, [xa+1152];\n"
            "tanh.approx.f32 th2, h5;\n"
            "tanh.approx.f32 th3, h7;\n"
            "fma.rn.f32 th2, h5, th2, h5;\n"
            "fma.rn.f32 th3, h7, th3, h7;\n"
            "cvt.rn.bf16x2.f32 r1, th3, th2;\n"
            "mma.sync.aligned.m16n8k16.row.col.f32.bf16.bf16.f32 {h4,h5,h6,h7}, {%11,%12,%13,%14}, {e0,e1}, {fz,fz,fz,fz};\n"
            "mma.sync.aligned.m16n8k16.row.col.f32.bf16.bf16.f32 {c48,c49,c50,c51}, {a0,a1,a2,a3}, {x8,x9}, {c48,c49,c50,c51};\n"
            "mma.sync.aligned.m16n8k16.row.col.f32.bf16.bf16.f32 {c52,c53,c54,c55}, {a0,a1,a2,a3}, {x10,x11}, {c52,c53,c54,c55};\n"
            "ld.shared.v4.u32 {x8,x9,x10,x11}, [xa+1536];\n"
            "tanh.approx.f32 th4, h9;\n"
            "tanh.approx.f32 th5, h11;\n"
            "fma.rn.f32 th4, h9, th4, h9;\n"
            "fma.rn.f32 th5, h11, th5, h11;\n"
            "cvt.rn.bf16x2.f32 r2, th5, th4;\n"
            "mma.sync.aligned.m16n8k16.row.col.f32.bf16.bf16.f32 {h8,h9,h10,h11}, {%15,%16,%17,%18}, {e0,e1}, {fz,fz,fz,fz};\n"
            "mma.sync.aligned.m16n8k16.row.col.f32.bf16.bf16.f32 {c56,c57,c58,c59}, {a0,a1,a2,a3}, {x12,x13}, {c56,c57,c58,c59};\n"
            "mma.sync.aligned.m16n8k16.row.col.f32.bf16.bf16.f32 {c60,c61,c62,c63}, {a0,a1,a2,a3}, {x14,x15}, {c60,c61,c62,c63};\n"
            "ld.shared.v4.u32 {x12,x13,x14,x15}, [xa+1664];\n"
            "tanh.approx.f32 th6, h13;\n"
            "tanh.approx.f32 th7, h15;\n"
            "fma.rn.f32 th6, h13, th6, h13;\n"
            "fma.rn.f32 th7, h15, th7, h15;\n"
            "cvt.rn.bf16x2.f32 r3, th7, th6;\n"
            "mma.sync.aligned.m16n8k16.row.col.f32.bf16.bf16.f32 {h12,h13,h14,h15}, {%19,%20,%21,%22}, {e0,e1}, {fz,fz,fz,fz};\n"
            "ld.shared.v4.u32 {a0,a1,a2,a3}, [ab+128];\n"
            "and.b32 tmp, aa, 0xffffff80; mbarrier.test_wait.parity.shared::cta.b64 pw, [tmp+520], mt;\n"
            "mad.lo.s32 xa, st, 2048, xa;\n"
            "mov.b32 {lo,hi}, r0; mov.b32 rl, {lo,lo}; mov.b32 rh, {hi,hi};\n"
            "mul.bf16x2 x0, x0, rl; mul.bf16x2 x1, x1, rl; mul.bf16x2 x2, x2, rh; mul.bf16x2 x3, x3, rh;\n"
            "mov.b32 {lo,hi}, r1; mov.b32 rl, {lo,lo}; mov.b32 rh, {hi,hi};\n"
            "mul.bf16x2 x4, x4, rl; mul.bf16x2 x5, x5, rl; mul.bf16x2 x6, x6, rh; mul.bf16x2 x7, x7, rh;\n"
            "mov.b32 {lo,hi}, r2; mov.b32 rl, {lo,lo}; mov.b32 rh, {hi,hi};\n"
            "mul.bf16x2 x8, x8, rl; mul.bf16x2 x9, x9, rl; mul.bf16x2 x10, x10, rh; mul.bf16x2 x11, x11, rh;\n"
            "mov.b32 {lo,hi}, r3; mov.b32 rl, {lo,lo}; mov.b32 rh, {hi,hi};\n"
            "mul.bf16x2 x12, x12, rl; mul.bf16x2 x13, x13, rl; mul.bf16x2 x14, x14, rh; mul.bf16x2 x15, x15, rh;\n"
            "@!pw bra.uni W1;\n"
            "@d2 bra.uni B0_4; @d1 bra.uni L0; @d0 bra.uni B0_1; bra.uni B0_0;\n"
            "L1: @d2 bra.uni END; @d0 bra.uni B1_3;\n"
            "B1_2:\n"
            "xor.b32 tmp, mt, ea; and.b32 tmp, tmp, 192; setp.eq.u32 pm, tmp, 0; selp.b32 ab, aa, %3, pm;\n"
            "and.b32 tmp, mt, 8; setp.ne.u32 d0, tmp, 0; and.b32 tmp, mt, 16; setp.ne.u32 d1, tmp, 0; and.b32 tmp, mt, 32; setp.ne.u32 d2, tmp, 0;\n"
            "ld.shared.v2.u32 {e0,e1}, [ea];\n"
            "shr.s32 st, mt, 24; mad.lo.s32 aa, st, 2560, aa;\n"
            "mma.sync.aligned.m16n8k16.row.col.f32.bf16.bf16.f32 {c64,c65,c66,c67}, {a0,a1,a2,a3}, {x0,x1}, {c64,c65,c66,c67};\n"
            "mma.sync.aligned.m16n8k16.row.col.f32.bf16.bf16.f32 {c68,c69,c70,c71}, {a0,a1,a2,a3}, {x2,x3}, {c68,c69,c70,c71};\n"
            "ld.shared.v4.u32 {x0,x1,x2,x3}, [xa+1024];\n"
            "tanh.approx.f32 th0, h1;\n"
            "tanh.approx.f32 th1, h3;\n"
            "fma.rn.f32 th0, h1, th0, h1;\n"
            "fma.rn.f32 th1, h3, th1, h3;\n"
            "cvt.rn.bf16x2.f32 r0, th1, th0;\n"
            "mma.sync.aligned.m16n8k16.row.col.f32.bf16.bf16.f32 {h0,h1,h2,h3}, {%7,%8,%9,%10}, {e0,e1}, {fz,fz,fz,fz};\n"
            "mma.sync.aligned.m16n8k16.row.col.f32.bf16.bf16.f32 {c72,c73,c74,c75}, {a0,a1,a2,a3}, {x4,x5}, {c72,c73,c74,c75};\n"
            "mma.sync.aligned.m16n8k16.row.col.f32.bf16.bf16.f32 {c76,c77,c78,c79}, {a0,a1,a2,a3}, {x6,x7}, {c76,c77,c78,c79};\n"
            "ld.shared.v4.u32 {x4,x5,x6,x7}, [xa+1152];\n"
            "tanh.approx.f32 th2, h5;\n"
            "tanh.approx.f32 th3, h7;\n"
            "fma.rn.f32 th2, h5, th2, h5;\n"
            "fma.rn.f32 th3, h7, th3, h7;\n"
            "cvt.rn.bf16x2.f32 r1, th3, th2;\n"
            "mma.sync.aligned.m16n8k16.row.col.f32.bf16.bf16.f32 {h4,h5,h6,h7}, {%11,%12,%13,%14}, {e0,e1}, {fz,fz,fz,fz};\n"
            "mma.sync.aligned.m16n8k16.row.col.f32.bf16.bf16.f32 {c80,c81,c82,c83}, {a0,a1,a2,a3}, {x8,x9}, {c80,c81,c82,c83};\n"
            "mma.sync.aligned.m16n8k16.row.col.f32.bf16.bf16.f32 {c84,c85,c86,c87}, {a0,a1,a2,a3}, {x10,x11}, {c84,c85,c86,c87};\n"
            "ld.shared.v4.u32 {x8,x9,x10,x11}, [xa+1536];\n"
            "tanh.approx.f32 th4, h9;\n"
            "tanh.approx.f32 th5, h11;\n"
            "fma.rn.f32 th4, h9, th4, h9;\n"
            "fma.rn.f32 th5, h11, th5, h11;\n"
            "cvt.rn.bf16x2.f32 r2, th5, th4;\n"
            "mma.sync.aligned.m16n8k16.row.col.f32.bf16.bf16.f32 {h8,h9,h10,h11}, {%15,%16,%17,%18}, {e0,e1}, {fz,fz,fz,fz};\n"
            "mma.sync.aligned.m16n8k16.row.col.f32.bf16.bf16.f32 {c88,c89,c90,c91}, {a0,a1,a2,a3}, {x12,x13}, {c88,c89,c90,c91};\n"
            "mma.sync.aligned.m16n8k16.row.col.f32.bf16.bf16.f32 {c92,c93,c94,c95}, {a0,a1,a2,a3}, {x14,x15}, {c92,c93,c94,c95};\n"
            "ld.shared.v4.u32 {x12,x13,x14,x15}, [xa+1664];\n"
            "tanh.approx.f32 th6, h13;\n"
            "tanh.approx.f32 th7, h15;\n"
            "fma.rn.f32 th6, h13, th6, h13;\n"
            "fma.rn.f32 th7, h15, th7, h15;\n"
            "cvt.rn.bf16x2.f32 r3, th7, th6;\n"
            "mma.sync.aligned.m16n8k16.row.col.f32.bf16.bf16.f32 {h12,h13,h14,h15}, {%19,%20,%21,%22}, {e0,e1}, {fz,fz,fz,fz};\n"
            "ld.shared.v4.u32 {a0,a1,a2,a3}, [ab+128];\n"
            "and.b32 tmp, aa, 0xffffff80; mbarrier.test_wait.parity.shared::cta.b64 pw, [tmp+520], mt;\n"
            "mad.lo.s32 xa, st, 2048, xa;\n"
            "mov.b32 {lo,hi}, r0; mov.b32 rl, {lo,lo}; mov.b32 rh, {hi,hi};\n"
            "mul.bf16x2 x0, x0, rl; mul.bf16x2 x1, x1, rl; mul.bf16x2 x2, x2, rh; mul.bf16x2 x3, x3, rh;\n"
            "mov.b32 {lo,hi}, r1; mov.b32 rl, {lo,lo}; mov.b32 rh, {hi,hi};\n"
            "mul.bf16x2 x4, x4, rl; mul.bf16x2 x5, x5, rl; mul.bf16x2 x6, x6, rh; mul.bf16x2 x7, x7, rh;\n"
            "mov.b32 {lo,hi}, r2; mov.b32 rl, {lo,lo}; mov.b32 rh, {hi,hi};\n"
            "mul.bf16x2 x8, x8, rl; mul.bf16x2 x9, x9, rl; mul.bf16x2 x10, x10, rh; mul.bf16x2 x11, x11, rh;\n"
            "mov.b32 {lo,hi}, r3; mov.b32 rl, {lo,lo}; mov.b32 rh, {hi,hi};\n"
            "mul.bf16x2 x12, x12, rl; mul.bf16x2 x13, x13, rl; mul.bf16x2 x14, x14, rh; mul.bf16x2 x15, x15, rh;\n"
            "@!pw bra.uni W1;\n"
            "@d2 bra.uni B0_4; @d1 bra.uni L0; @d0 bra.uni B0_1; bra.uni B0_0;\n"
            "B1_3:\n"
            "xor.b32 tmp, mt, ea; and.b32 tmp, tmp, 192; setp.eq.u32 pm, tmp, 0; selp.b32 ab, aa, %3, pm;\n"
            "and.b32 tmp, mt, 8; setp.ne.u32 d0, tmp, 0; and.b32 tmp, mt, 16; setp.ne.u32 d1, tmp, 0; and.b32 tmp, mt, 32; setp.ne.u32 d2, tmp, 0;\n"
            "ld.shared.v2.u32 {e0,e1}, [ea];\n"
            "shr.s32 st, mt, 24; mad.lo.s32 aa, st, 2560, aa;\n"
            "mma.sync.aligned.m16n8k16.row.col.f32.bf16.bf16.f32 {c96,c97,c98,c99}, {a0,a1,a2,a3}, {x0,x1}, {c96,c97,c98,c99};\n"
            "mma.sync.aligned.m16n8k16.row.col.f32.bf16.bf16.f32 {c100,c101,c102,c103}, {a0,a1,a2,a3}, {x2,x3}, {c100,c101,c102,c103};\n"
            "ld.shared.v4.u32 {x0,x1,x2,x3}, [xa+1024];\n"
            "tanh.approx.f32 th0, h1;\n"
            "tanh.approx.f32 th1, h3;\n"
            "fma.rn.f32 th0, h1, th0, h1;\n"
            "fma.rn.f32 th1, h3, th1, h3;\n"
            "cvt.rn.bf16x2.f32 r0, th1, th0;\n"
            "mma.sync.aligned.m16n8k16.row.col.f32.bf16.bf16.f32 {h0,h1,h2,h3}, {%7,%8,%9,%10}, {e0,e1}, {fz,fz,fz,fz};\n"
            "mma.sync.aligned.m16n8k16.row.col.f32.bf16.bf16.f32 {c104,c105,c106,c107}, {a0,a1,a2,a3}, {x4,x5}, {c104,c105,c106,c107};\n"
            "mma.sync.aligned.m16n8k16.row.col.f32.bf16.bf16.f32 {c108,c109,c110,c111}, {a0,a1,a2,a3}, {x6,x7}, {c108,c109,c110,c111};\n"
            "ld.shared.v4.u32 {x4,x5,x6,x7}, [xa+1152];\n"
            "tanh.approx.f32 th2, h5;\n"
            "tanh.approx.f32 th3, h7;\n"
            "fma.rn.f32 th2, h5, th2, h5;\n"
            "fma.rn.f32 th3, h7, th3, h7;\n"
            "cvt.rn.bf16x2.f32 r1, th3, th2;\n"
            "mma.sync.aligned.m16n8k16.row.col.f32.bf16.bf16.f32 {h4,h5,h6,h7}, {%11,%12,%13,%14}, {e0,e1}, {fz,fz,fz,fz};\n"
            "mma.sync.aligned.m16n8k16.row.col.f32.bf16.bf16.f32 {c112,c113,c114,c115}, {a0,a1,a2,a3}, {x8,x9}, {c112,c113,c114,c115};\n"
            "mma.sync.aligned.m16n8k16.row.col.f32.bf16.bf16.f32 {c116,c117,c118,c119}, {a0,a1,a2,a3}, {x10,x11}, {c116,c117,c118,c119};\n"
            "ld.shared.v4.u32 {x8,x9,x10,x11}, [xa+1536];\n"
            "tanh.approx.f32 th4, h9;\n"
            "tanh.approx.f32 th5, h11;\n"
            "fma.rn.f32 th4, h9, th4, h9;\n"
            "fma.rn.f32 th5, h11, th5, h11;\n"
            "cvt.rn.bf16x2.f32 r2, th5, th4;\n"
            "mma.sync.aligned.m16n8k16.row.col.f32.bf16.bf16.f32 {h8,h9,h10,h11}, {%15,%16,%17,%18}, {e0,e1}, {fz,fz,fz,fz};\n"
            "mma.sync.aligned.m16n8k16.row.col.f32.bf16.bf16.f32 {c120,c121,c122,c123}, {a0,a1,a2,a3}, {x12,x13}, {c120,c121,c122,c123};\n"
            "mma.sync.aligned.m16n8k16.row.col.f32.bf16.bf16.f32 {c124,c125,c126,c127}, {a0,a1,a2,a3}, {x14,x15}, {c124,c125,c126,c127};\n"
            "ld.shared.v4.u32 {x12,x13,x14,x15}, [xa+1664];\n"
            "tanh.approx.f32 th6, h13;\n"
            "tanh.approx.f32 th7, h15;\n"
            "fma.rn.f32 th6, h13, th6, h13;\n"
            "fma.rn.f32 th7, h15, th7, h15;\n"
            "cvt.rn.bf16x2.f32 r3, th7, th6;\n"
            "mma.sync.aligned.m16n8k16.row.col.f32.bf16.bf16.f32 {h12,h13,h14,h15}, {%19,%20,%21,%22}, {e0,e1}, {fz,fz,fz,fz};\n"
            "ld.shared.v4.u32 {a0,a1,a2,a3}, [ab+128];\n"
            "and.b32 tmp, aa, 0xffffff80; mbarrier.test_wait.parity.shared::cta.b64 pw, [tmp+520], mt;\n"
            "mad.lo.s32 xa, st, 2048, xa;\n"
            "mov.b32 {lo,hi}, r0; mov.b32 rl, {lo,lo}; mov.b32 rh, {hi,hi};\n"
            "mul.bf16x2 x0, x0, rl; mul.bf16x2 x1, x1, rl; mul.bf16x2 x2, x2, rh; mul.bf16x2 x3, x3, rh;\n"
            "mov.b32 {lo,hi}, r1; mov.b32 rl, {lo,lo}; mov.b32 rh, {hi,hi};\n"
            "mul.bf16x2 x4, x4, rl; mul.bf16x2 x5, x5, rl; mul.bf16x2 x6, x6, rh; mul.bf16x2 x7, x7, rh;\n"
            "mov.b32 {lo,hi}, r2; mov.b32 rl, {lo,lo}; mov.b32 rh, {hi,hi};\n"
            "mul.bf16x2 x8, x8, rl; mul.bf16x2 x9, x9, rl; mul.bf16x2 x10, x10, rh; mul.bf16x2 x11, x11, rh;\n"
            "mov.b32 {lo,hi}, r3; mov.b32 rl, {lo,lo}; mov.b32 rh, {hi,hi};\n"
            "mul.bf16x2 x12, x12, rl; mul.bf16x2 x13, x13, rl; mul.bf16x2 x14, x14, rh; mul.bf16x2 x15, x15, rh;\n"
            "@!pw bra.uni W1;\n"
            "@d2 bra.uni B0_4; @d1 bra.uni L0; @d0 bra.uni B0_1; bra.uni B0_0;\n"
            "B1_4:\n"
            "xor.b32 tmp, mt, ea; and.b32 tmp, tmp, 192; setp.eq.u32 pm, tmp, 0; selp.b32 ab, aa, %3, pm;\n"
            "and.b32 tmp, mt, 8; setp.ne.u32 d0, tmp, 0; and.b32 tmp, mt, 16; setp.ne.u32 d1, tmp, 0; and.b32 tmp, mt, 32; setp.ne.u32 d2, tmp, 0;\n"
            "ld.shared.v2.u32 {e0,e1}, [ea];\n"
            "shr.s32 st, mt, 24; mad.lo.s32 aa, st, 2560, aa;\n"
            "mma.sync.aligned.m16n8k16.row.col.f32.bf16.bf16.f32 {c128,c129,c130,c131}, {a0,a1,a2,a3}, {x0,x1}, {c128,c129,c130,c131};\n"
            "mma.sync.aligned.m16n8k16.row.col.f32.bf16.bf16.f32 {c132,c133,c134,c135}, {a0,a1,a2,a3}, {x2,x3}, {c132,c133,c134,c135};\n"
            "ld.shared.v4.u32 {x0,x1,x2,x3}, [xa+1024];\n"
            "tanh.approx.f32 th0, h1;\n"
            "tanh.approx.f32 th1, h3;\n"
            "fma.rn.f32 th0, h1, th0, h1;\n"
            "fma.rn.f32 th1, h3, th1, h3;\n"
            "cvt.rn.bf16x2.f32 r0, th1, th0;\n"
            "mma.sync.aligned.m16n8k16.row.col.f32.bf16.bf16.f32 {h0,h1,h2,h3}, {%7,%8,%9,%10}, {e0,e1}, {fz,fz,fz,fz};\n"
            "mma.sync.aligned.m16n8k16.row.col.f32.bf16.bf16.f32 {c136,c137,c138,c139}, {a0,a1,a2,a3}, {x4,x5}, {c136,c137,c138,c139};\n"
            "mma.sync.aligned.m16n8k16.row.col.f32.bf16.bf16.f32 {c140,c141,c142,c143}, {a0,a1,a2,a3}, {x6,x7}, {c140,c141,c142,c143};\n"
            "ld.shared.v4.u32 {x4,x5,x6,x7}, [xa+1152];\n"
            "tanh.approx.f32 th2, h5;\n"
            "tanh.approx.f32 th3, h7;\n"
            "fma.rn.f32 th2, h5, th2, h5;\n"
            "fma.rn.f32 th3, h7, th3, h7;\n"
            "cvt.rn.bf16x2.f32 r1, th3, th2;\n"
            "mma.sync.aligned.m16n8k16.row.col.f32.bf16.bf16.f32 {h4,h5,h6,h7}, {%11,%12,%13,%14}, {e0,e1}, {fz,fz,fz,fz};\n"
            "mma.sync.aligned.m16n8k16.row.col.f32.bf16.bf16.f32 {c144,c145,c146,c147}, {a0,a1,a2,a3}, {x8,x9}, {c144,c145,c146,c147};\n"
            "mma.sync.aligned.m16n8k16.row.col.f32.bf16.bf16.f32 {c148,c149,c150,c151}, {a0,a1,a2,a3}, {x10,x11}, {c148,c149,c150,c151};\n"
            "ld.shared.v4.u32 {x8,x9,x10,x11}, [xa+1536];\n"
            "tanh.approx.f32 th4, h9;\n"
            "tanh.approx.f32 th5, h11;\n"
            "fma.rn.f32 th4, h9, th4, h9;\n"
            "fma.rn.f32 th5, h11, th5, h11;\n"
            "cvt.rn.bf16x2.f32 r2, th5, th4;\n"
            "mma.sync.aligned.m16n8k16.row.col.f32.bf16.bf16.f32 {h8,h9,h10,h11}, {%15,%16,%17,%18}, {e0,e1}, {fz,fz,fz,fz};\n"
            "mma.sync.aligned.m16n8k16.row.col.f32.bf16.bf16.f32 {c152,c153,c154,c155}, {a0,a1,a2,a3}, {x12,x13}, {c152,c153,c154,c155};\n"
            "mma.sync.aligned.m16n8k16.row.col.f32.bf16.bf16.f32 {c156,c157,c158,c159}, {a0,a1,a2,a3}, {x14,x15}, {c156,c157,c158,c159};\n"
            "ld.shared.v4.u32 {x12,x13,x14,x15}, [xa+1664];\n"
            "tanh.approx.f32 th6, h13;\n"
            "tanh.approx.f32 th7, h15;\n"
            "fma.rn.f32 th6, h13, th6, h13;\n"
            "fma.rn.f32 th7, h15, th7, h15;\n"
            "cvt.rn.bf16x2.f32 r3, th7, th6;\n"
            "mma.sync.aligned.m16n8k16.row.col.f32.bf16.bf16.f32 {h12,h13,h14,h15}, {%19,%20,%21,%22}, {e0,e1}, {fz,fz,fz,fz};\n"
            "ld.shared.v4.u32 {a0,a1,a2,a3}, [ab+128];\n"
            "and.b32 tmp, aa, 0xffffff80; mbarrier.test_wait.parity.shared::cta.b64 pw, [tmp+520], mt;\n"
            "mad.lo.s32 xa, st, 2048, xa;\n"
            "mov.b32 {lo,hi}, r0; mov.b32 rl, {lo,lo}; mov.b32 rh, {hi,hi};\n"
            "mul.bf16x2 x0, x0, rl; mul.bf16x2 x1, x1, rl; mul.bf16x2 x2, x2, rh; mul.bf16x2 x3, x3, rh;\n"
            "mov.b32 {lo,hi}, r1; mov.b32 rl, {lo,lo}; mov.b32 rh, {hi,hi};\n"
            "mul.bf16x2 x4, x4, rl; mul.bf16x2 x5, x5, rl; mul.bf16x2 x6, x6, rh; mul.bf16x2 x7, x7, rh;\n"
            "mov.b32 {lo,hi}, r2; mov.b32 rl, {lo,lo}; mov.b32 rh, {hi,hi};\n"
            "mul.bf16x2 x8, x8, rl; mul.bf16x2 x9, x9, rl; mul.bf16x2 x10, x10, rh; mul.bf16x2 x11, x11, rh;\n"
            "mov.b32 {lo,hi}, r3; mov.b32 rl, {lo,lo}; mov.b32 rh, {hi,hi};\n"
            "mul.bf16x2 x12, x12, rl; mul.bf16x2 x13, x13, rl; mul.bf16x2 x14, x14, rh; mul.bf16x2 x15, x15, rh;\n"
            "@!pw bra.uni W1;\n"
            "@d2 bra.uni B0_4; @d1 bra.uni L0; @d0 bra.uni B0_1; bra.uni B0_0;\n"
            "W1:\n"
            "mov.u32 cnt, 0; and.b32 tmp, aa, 0xffffff80;\n"
            "W1L: mbarrier.try_wait.parity.shared::cta.b64 pw, [tmp+520], mt; @pw bra.uni W1D;\n"
            "add.u32 cnt, cnt, 1; setp.lt.u32 pk, cnt, 1000000; @pk bra.uni W1L; trap;\n"
            "W1D:\n"
            "@d2 bra.uni B0_4; @d1 bra.uni L0; @d0 bra.uni B0_1; bra.uni B0_0;\n"
            "END:\n"
            "cvt.rn.bf16x2.f32 p0, c1, c0; cvt.rn.bf16x2.f32 p1, c5, c4; cvt.rn.bf16x2.f32 p2, c9, c8; cvt.rn.bf16x2.f32 p3, c13, c12; cvt.rn.bf16x2.f32 p4, c17, c16; cvt.rn.bf16x2.f32 p5, c21, c20; cvt.rn.bf16x2.f32 p6, c25, c24; cvt.rn.bf16x2.f32 p7, c29, c28;\n"
            "cvt.rn.bf16x2.f32 p8, c3, c2; cvt.rn.bf16x2.f32 p9, c7, c6; cvt.rn.bf16x2.f32 p10, c11, c10; cvt.rn.bf16x2.f32 p11, c15, c14; cvt.rn.bf16x2.f32 p12, c19, c18; cvt.rn.bf16x2.f32 p13, c23, c22; cvt.rn.bf16x2.f32 p14, c27, c26; cvt.rn.bf16x2.f32 p15, c31, c30;\n"
            "cvt.rn.bf16x2.f32 p16, c33, c32; cvt.rn.bf16x2.f32 p17, c37, c36; cvt.rn.bf16x2.f32 p18, c41, c40; cvt.rn.bf16x2.f32 p19, c45, c44; cvt.rn.bf16x2.f32 p20, c49, c48; cvt.rn.bf16x2.f32 p21, c53, c52; cvt.rn.bf16x2.f32 p22, c57, c56; cvt.rn.bf16x2.f32 p23, c61, c60;\n"
            "cvt.rn.bf16x2.f32 p24, c35, c34; cvt.rn.bf16x2.f32 p25, c39, c38; cvt.rn.bf16x2.f32 p26, c43, c42; cvt.rn.bf16x2.f32 p27, c47, c46; cvt.rn.bf16x2.f32 p28, c51, c50; cvt.rn.bf16x2.f32 p29, c55, c54; cvt.rn.bf16x2.f32 p30, c59, c58; cvt.rn.bf16x2.f32 p31, c63, c62;\n"
            "cvt.rn.bf16x2.f32 p32, c65, c64; cvt.rn.bf16x2.f32 p33, c69, c68; cvt.rn.bf16x2.f32 p34, c73, c72; cvt.rn.bf16x2.f32 p35, c77, c76; cvt.rn.bf16x2.f32 p36, c81, c80; cvt.rn.bf16x2.f32 p37, c85, c84; cvt.rn.bf16x2.f32 p38, c89, c88; cvt.rn.bf16x2.f32 p39, c93, c92;\n"
            "cvt.rn.bf16x2.f32 p40, c67, c66; cvt.rn.bf16x2.f32 p41, c71, c70; cvt.rn.bf16x2.f32 p42, c75, c74; cvt.rn.bf16x2.f32 p43, c79, c78; cvt.rn.bf16x2.f32 p44, c83, c82; cvt.rn.bf16x2.f32 p45, c87, c86; cvt.rn.bf16x2.f32 p46, c91, c90; cvt.rn.bf16x2.f32 p47, c95, c94;\n"
            "cvt.rn.bf16x2.f32 p48, c97, c96; cvt.rn.bf16x2.f32 p49, c101, c100; cvt.rn.bf16x2.f32 p50, c105, c104; cvt.rn.bf16x2.f32 p51, c109, c108; cvt.rn.bf16x2.f32 p52, c113, c112; cvt.rn.bf16x2.f32 p53, c117, c116; cvt.rn.bf16x2.f32 p54, c121, c120; cvt.rn.bf16x2.f32 p55, c125, c124;\n"
            "cvt.rn.bf16x2.f32 p56, c99, c98; cvt.rn.bf16x2.f32 p57, c103, c102; cvt.rn.bf16x2.f32 p58, c107, c106; cvt.rn.bf16x2.f32 p59, c111, c110; cvt.rn.bf16x2.f32 p60, c115, c114; cvt.rn.bf16x2.f32 p61, c119, c118; cvt.rn.bf16x2.f32 p62, c123, c122; cvt.rn.bf16x2.f32 p63, c127, c126;\n"
            "cvt.rn.bf16x2.f32 p64, c129, c128; cvt.rn.bf16x2.f32 p65, c133, c132; cvt.rn.bf16x2.f32 p66, c137, c136; cvt.rn.bf16x2.f32 p67, c141, c140; cvt.rn.bf16x2.f32 p68, c145, c144; cvt.rn.bf16x2.f32 p69, c149, c148; cvt.rn.bf16x2.f32 p70, c153, c152; cvt.rn.bf16x2.f32 p71, c157, c156;\n"
            "cvt.rn.bf16x2.f32 p72, c131, c130; cvt.rn.bf16x2.f32 p73, c135, c134; cvt.rn.bf16x2.f32 p74, c139, c138; cvt.rn.bf16x2.f32 p75, c143, c142; cvt.rn.bf16x2.f32 p76, c147, c146; cvt.rn.bf16x2.f32 p77, c151, c150; cvt.rn.bf16x2.f32 p78, c155, c154; cvt.rn.bf16x2.f32 p79, c159, c158;\n"
            "and.b32 aa, %3, 0xfffff980; sub.u32 aa, aa, %6; mov.u32 mt, %%tid.x; shr.u32 st, mt, 7; shr.u32 cnt, mt, 5; add.u32 cnt, cnt, st; and.b32 cnt, cnt, 3;\n"
            "and.b32 mt, mt, 31; mad.lo.u32 tmp, mt, 16, aa; mad.lo.u32 tmp, st, 1024, tmp; mad.lo.u32 tmp, cnt, 20480, tmp;\n"
            "bar.sync 1, 256;\n"
            "stmatrix.sync.aligned.m8n8.x4.shared.b16 [tmp+0], {p0,p1,p2,p3};\n"
            "stmatrix.sync.aligned.m8n8.x4.shared.b16 [tmp+512], {p4,p5,p6,p7};\n"
            "stmatrix.sync.aligned.m8n8.x4.shared.b16 [tmp+2048], {p8,p9,p10,p11};\n"
            "stmatrix.sync.aligned.m8n8.x4.shared.b16 [tmp+2560], {p12,p13,p14,p15};\n"
            "stmatrix.sync.aligned.m8n8.x4.shared.b16 [tmp+4096], {p16,p17,p18,p19};\n"
            "stmatrix.sync.aligned.m8n8.x4.shared.b16 [tmp+4608], {p20,p21,p22,p23};\n"
            "stmatrix.sync.aligned.m8n8.x4.shared.b16 [tmp+6144], {p24,p25,p26,p27};\n"
            "stmatrix.sync.aligned.m8n8.x4.shared.b16 [tmp+6656], {p28,p29,p30,p31};\n"
            "stmatrix.sync.aligned.m8n8.x4.shared.b16 [tmp+8192], {p32,p33,p34,p35};\n"
            "stmatrix.sync.aligned.m8n8.x4.shared.b16 [tmp+8704], {p36,p37,p38,p39};\n"
            "stmatrix.sync.aligned.m8n8.x4.shared.b16 [tmp+10240], {p40,p41,p42,p43};\n"
            "stmatrix.sync.aligned.m8n8.x4.shared.b16 [tmp+10752], {p44,p45,p46,p47};\n"
            "stmatrix.sync.aligned.m8n8.x4.shared.b16 [tmp+12288], {p48,p49,p50,p51};\n"
            "stmatrix.sync.aligned.m8n8.x4.shared.b16 [tmp+12800], {p52,p53,p54,p55};\n"
            "stmatrix.sync.aligned.m8n8.x4.shared.b16 [tmp+14336], {p56,p57,p58,p59};\n"
            "stmatrix.sync.aligned.m8n8.x4.shared.b16 [tmp+14848], {p60,p61,p62,p63};\n"
            "stmatrix.sync.aligned.m8n8.x4.shared.b16 [tmp+16384], {p64,p65,p66,p67};\n"
            "stmatrix.sync.aligned.m8n8.x4.shared.b16 [tmp+16896], {p68,p69,p70,p71};\n"
            "stmatrix.sync.aligned.m8n8.x4.shared.b16 [tmp+18432], {p72,p73,p74,p75};\n"
            "stmatrix.sync.aligned.m8n8.x4.shared.b16 [tmp+18944], {p76,p77,p78,p79};\n"
            "mov.b32 %0, aa;\n"
            "}\n"
            : "=r"(sb2)
            : "r"(sb + t * XREG + grp * (NST * 2048) + half * 256 + ((g ^ ((2 * t + 2 * half) & 7)) << 4)),
              "r"(sb + AUX_OFF + grp * AUX_GR + t * 32 + (g & 1) * 16), "r"(az),
              "r"(sb + AUX_OFF + grp * AUX_GR + 256 + lane * 8), "r"(zero), "n"(ZERO_OFF),
              "r"(wr[0][0]), "r"(wr[0][1]), "r"(wr[0][2]), "r"(wr[0][3]), "r"(wr[1][0]), "r"(wr[1][1]), "r"(wr[1][2]), "r"(wr[1][3]),
              "r"(wr[2][0]), "r"(wr[2][1]), "r"(wr[2][2]), "r"(wr[2][3]), "r"(wr[3][0]), "r"(wr[3][1]), "r"(wr[3][2]), "r"(wr[3][3])
            : "memory");
        const int tid2 = threadIdx.x;
        sb2 = __shfl_sync(0xffffffffu, sb2, 0);
        const uint2 own = lds64(sb2 + MISC_OFF + 8);
        mbar_wait(sb2 + MISC_OFF, 0);
        asm volatile("fence.proxy.async.shared::cta;" ::: "memory");
        asm volatile("bar.sync 1, 256;" ::: "memory");
        const uint32_t wg = __shfl_sync(0xffffffffu, tid2 >> 7, 0);
        const uint64_t da = (uint64_t)((sb2 + WM_OFF + wg * 16384) >> 4) | (1ull << 16) | (64ull << 32) | (1ull << 62);
        const uint64_t db = (uint64_t)(sb2 >> 4) | (8ull << 16) | (128ull << 32);
        const int left = (int)own.y - 4 * (tid2 & 3);
        uint32_t* op = out + (size_t)(own.x + 4 * (tid2 & 3)) * 256 + ((tid2 >> 5) * 16 + ((tid2 & 31) >> 2)) * 2;
        float d0[40], d1[40], d2[40], d3[40], d4[40];
        mix_tiles<2, 0>(d0, da, db);
        mix_tiles<3, 2>(d1, da, db);
        store_tiles<2, 0, 1>(d0, op, left, 3 + wg);
        mix_tiles<5, 5>(d2, da, db);
        store_tiles<3, 2, 1>(d1, op, left, 3 + wg);
        mix_tiles<5, 10>(d3, da, db);
        store_tiles<5, 5, 1>(d2, op, left, 3 + wg);
        mix_tiles<5, 15>(d4, da, db);
        store_tiles<5, 10, 1>(d3, op, left, 3 + wg);
        store_tiles<5, 15, 0>(d4, op, left, 3 + wg);
    } else {
        asm volatile("setmaxnreg.dec.sync.aligned.u32 40;");
        uint32_t par = 0, prev = 0;
        auto ahead = [&](int st, uint32_t ev) {
            asm volatile("cp.async.ca.shared.global [%0], [%1], 8;" ::"r"(w_l + st * AUX_ST + 256), "l"(efl + (ev & 0x1ffffe0u)) : "memory");
            cp_async_arrive(ab + st * AUX_ST + BAR_F0);
            sts8(f_l + st * AUX_ST, ((odd ? prev : ev) >> 24 & 0xfeu) | (st == NST - 1 ? par ^ 1u : par));
            prev = ev;
        };
        uint32_t hv, ev;
        uint4 y0, y1;
        auto load = [&]() {
            hv = lds32(h_l);
            ev = lds32(yp + 32 + e_l);
            y0 = lds128(yp);
            y1 = lds128(yp + 16);
            yp += 32;
            h_l += 64;
        };
        auto step = [&](int st) {
            float w0[4], w1[4];
            mma1688_z(w0, hv, hv, cgb0);
            mma1688_z(w1, hv, hv, cgb1);
            const uint32_t tq = T0 + __umulhi(y0.y + y0.z + y1.y + y1.z, pace);
            mbar_wait(ab + st * AUX_ST + BAR_EM, par ^ 1u);
            int rem = (int)(tq - (uint32_t)clock64());
            ahead(st, ev);
            sts64(w_l + st * AUX_ST, pack_bf16(w0[0], w0[1]), pack_bf16(w1[0], w1[1]));
            __syncwarp();
            asm volatile("{\n\t.reg .pred P;\n\tsetp.ne.u32 P, %1, 0;\n\t@P mbarrier.arrive.expect_tx.shared::cta.b64 _, [%0], %1;\n\t}"
                         ::"r"(ab + st * AUX_ST + BAR_F0), "r"(bytes) : "memory");
#pragma unroll 1
            while (rem > 0) {
                __nanosleep(SLEEP);
                rem = (int)(tq - (uint32_t)clock64());
            }
            fetch_quad(xb + st * 2048, ab + st * AUX_ST + BAR_F0, y0, map);
            fetch_quad(xb + st * 2048 + 1024, ab + st * AUX_ST + BAR_F0, y1, map);
            load();
        };
        ahead(0, lds32(yp + e_l));
        __syncwarp();
        mbar_arrive_one(ab + BAR_F0);
        load();
#pragma unroll 1
        for (;;) {
            if (yp == yend) break;
            step(1);
            if (yp == yend) break;
            step(2);
            if (yp == yend) break;
            step(3);
            if (yp == yend) break;
            step(4);
            par ^= 1u;
            if (yp == yend) break;
            step(0);
        }
        const uint32_t rounds = (noct + 1) / NST, fin = noct + 1 - rounds * NST;
        mbar_wait(ab + fin * AUX_ST + BAR_EM, ~rounds & 1u);
        asm volatile("mbarrier.arrive.shared::cta.b64 _, [%0];" ::"r"(ab + fin * AUX_ST + BAR_F0) : "memory");
        mbar_arrive_one(ab + fin * AUX_ST + BAR_F0);
        asm volatile("bar.sync 2, 128;" ::: "memory");
        const int ln = threadIdx.x & 31;
#pragma unroll 4
        for (int i = 0; i < 16; i++) {
            const int kr = i * 8 + pgrp * 2 + (ln >> 4);
            const int dj = ((i >> 1) & 1) + (i & 4), n = kr & 7;
            const int ch = 16 * (2 * (i >> 3) + dj) + 2 * (n ^ dj) + (i & 1);
            asm volatile("cp.async.cg.shared.global [%0], [%1], 16;"
                         ::"r"(s0 + WM_OFF + ((ln >> 3) & 1) * 16384 + kr * 128 + (((ln & 7) ^ n) << 4)),
                           "l"(w_mix + ch * 128 + (ln & 15) * 8) : "memory");
        }
        cp_async_arrive(s0 + MISC_OFF);
        asm volatile("cp.async.wait_all;" ::: "memory");
    }
}

typedef CUresult (*EncodeFn)(CUtensorMap*, CUtensorMapDataType, cuuint32_t, void*, const cuuint64_t*, const cuuint64_t*,
                             const cuuint32_t*, const cuuint32_t*, CUtensorMapInterleave, CUtensorMapSwizzle,
                             CUtensorMapL2promotion, CUtensorMapFloatOOBfill);

}

#define WALK 46800
#define LEAD 6900

extern "C" void kernel_launch(void* const* d_in, const int* in_sizes, int n_in, void* d_out, int out_size) {
    const char* x = (const char*)d_in[0];
    const int* src = (const int*)d_in[1];
    const int* dst = (const int*)d_in[2];
    const uint2* Y = (const uint2*)d_in[3];
    const char* ef = (const char*)d_in[4];
    const __nv_bfloat16* w_rad = (const __nv_bfloat16*)d_in[5];
    const __nv_bfloat16* cg = (const __nv_bfloat16*)d_in[6];
    const __nv_bfloat16* w_mix = (const __nv_bfloat16*)d_in[7];
    const int N = in_sizes[0] / 512;
    const int E = in_sizes[1];

    static int num_cta = 0;
    static EncodeFn encode = nullptr;
    if (num_cta == 0) {
        int dev = 0, sms = 0;
        cudaGetDevice(&dev);
        cudaDeviceGetAttribute(&sms, cudaDevAttrMultiProcessorCount, dev);
        num_cta = sms < MAXCTA ? sms : MAXCTA;
        cudaFuncSetAttribute(tfn_kernel, cudaFuncAttributeMaxDynamicSharedMemorySize, SMEM_BYTES);
        void* fn = nullptr;
        cudaDriverEntryPointQueryResult qr;
        cudaGetDriverEntryPoint("cuTensorMapEncodeTiled", &fn, cudaEnableDefault, &qr);
        encode = (EncodeFn)fn;
    }
    int S = (N + num_cta - 1) / num_cta;
    if (S < 2) S = 2;
    const int EPC = ((E + num_cta - 1) / num_cta + 3) & ~3;
    if (S > SMAX || EPC > EPC_MAX || N < 128 || N > 16384 || E <= 0 || E > (1 << 20) || encode == nullptr) return;
    CUtensorMap xmap;
    const cuuint64_t gd[2] = {64, (cuuint64_t)N * 8}, gs[1] = {128};
    const cuuint32_t bx[2] = {64, BOX_LINES}, es[2] = {1, 1};
    if (encode(&xmap, CU_TENSOR_MAP_DATA_TYPE_BFLOAT16, 2, (void*)x, gd, gs, bx, es, CU_TENSOR_MAP_INTERLEAVE_NONE,
               CU_TENSOR_MAP_SWIZZLE_128B, CU_TENSOR_MAP_L2_PROMOTION_NONE, CU_TENSOR_MAP_FLOAT_OOB_FILL_NONE) != CUDA_SUCCESS)
        return;
    const uint32_t magicS = (uint32_t)((0x100000000ull + S - 1) / S);
    uint32_t magicB = (uint32_t)(((unsigned long long)NB << 32) / N);
    int walk = WALK, lead = LEAD, ramp = 0, rsh = 0, pfx = 4, pfe = 0;
    double pc = (double)walk * ((double)E / N * S / 2432.0) / (32.0 * N);
    if (pc > 0.99) pc = 0.99;
    const uint32_t pace = (uint32_t)(pc * 4294967296.0);
    tfn_kernel<<<num_cta, NT, SMEM_BYTES, cudaStreamPerThread>>>(xmap, x, src, dst, Y, ef, w_rad, cg, w_mix, (uint32_t*)d_out, N, E, S,
                                                                 EPC, magicS, magicB, 0u, pace, lead, ramp, rsh, pfx, pfe);
}
```

```cpp
#include <cuda_runtime.h>
#include <cuda.h>
#include <cuda_bf16.h>
#include <stdint.h>

namespace {

constexpr int NT = 384;
constexpr int NWARP = NT / 32;
constexpr int MAXCTA = 132;
constexpr int SFAST = 80;
constexpr int SMAX = 96;
constexpr int EPC_MAX = 3072;
constexpr int RND = 10;
constexpr int NB = 96;
constexpr int GCAP = 800;
constexpr int NCOL = NWARP - 1;
constexpr int JCAP = NCOL * RND * 8 + 8;
constexpr int RND0 = 8;
constexpr uint32_t TAGM = 31u;
constexpr int NST = 5;
constexpr uint32_t F0_COUNT = 33;
#define SLEEPNS 100
constexpr uint32_t SLEEP = SLEEPNS;
constexpr uint32_t PFA = 2, PFE = 2048;
constexpr int SPIN_LIMIT = 1 << 22;

constexpr int XREG = 4 * NST * 2048 + 256;
constexpr int AUX_OFF = 4 * XREG;
constexpr int AUX_ST = 2560, AUX_GR = 640;
constexpr int BAR_F0 = 520, BAR_EM = 536;
constexpr int SY_OFF = AUX_OFF + NST * AUX_ST;
constexpr int SE_OFF = SY_OFF + 4 * GCAP * 4;
constexpr int SH_OFF = SE_OFF + 4 * GCAP * 4;
constexpr int MISC_OFF = SH_OFF + 4 * GCAP * 8;
constexpr int ZERO_OFF = ((MISC_OFF + 1024 + 2047) & ~2047) - 1024;
constexpr int WM_OFF = (SE_OFF + 1023) & ~1023;
constexpr int CNT_OFF = 20 * JCAP * 4, START_OFF = CNT_OFF + 1024;
constexpr int BCNT_OFF = START_OFF + 1024;
constexpr int BCUM_OFF = BCNT_OFF + 20 * NB * 4;
constexpr int SEG_OFF = BCUM_OFF + 20 * NB * 4;
constexpr int WR_OFF = SEG_OFF + 1024;
constexpr int GI_OFF = 0;
struct Misc {
    unsigned long long wbar;
    int node0, Sc;
    unsigned long long rbar;
    int nq[4];
    int dmax;
    uint32_t epoch, ref;
    uint32_t rseg[MAXCTA];
};
constexpr int SMEM_BYTES = ZERO_OFF + 1792;
static_assert(MISC_OFF + (int)sizeof(Misc) <= ZERO_OFF, "layout");
static_assert(SMEM_BYTES <= 227 * 1024, "shared memory");
static_assert(EPC_MAX * 16 <= CNT_OFF && WR_OFF + 4096 <= AUX_OFF && WR_OFF % 128 == 0, "tables");
static_assert(WM_OFF + 32768 <= MISC_OFF && SMAX * 2048 <= MISC_OFF, "layout");
static_assert(AUX_OFF % 256 == 0 && NB == 96 && NWARP == 12, "layout");

__device__ __align__(128) uint4 g_staged[(size_t)MAXCTA * EPC_MAX];
__device__ __align__(128) uint2 g_table[MAXCTA * 144];
__device__ unsigned int g_epoch[MAXCTA];

__device__ __forceinline__ void mma1688_z(float (&d)[4], uint32_t a0, uint32_t a1, uint32_t b0) {
    asm volatile(
        "mma.sync.aligned.m16n8k8.row.col.f32.bf16.bf16.f32 {%0,%1,%2,%3}, {%4,%5}, {%6}, {%7,%7,%7,%7};"
        : "=f"(d[0]), "=f"(d[1]), "=f"(d[2]), "=f"(d[3])
        : "r"(a0), "r"(a1), "r"(b0), "f"(0.0f));
}
__device__ __forceinline__ uint32_t pack_bf16(float lo, float hi) {
    uint32_t r;
    asm("cvt.rn.bf16x2.f32 %0, %1, %2;" : "=r"(r) : "f"(hi), "f"(lo));
    return r;
}
__device__ __forceinline__ uint32_t half_bf16x2(uint32_t v) {
    uint32_t r;
    asm("mul.bf16x2 %0, %1, %2;" : "=r"(r) : "r"(v), "r"(0x3f003f00u));
    return r;
}
__device__ __forceinline__ uint4 lds128(uint32_t a) {
    uint4 v;
    asm volatile("ld.shared.v4.u32 {%0,%1,%2,%3}, [%4];" : "=r"(v.x), "=r"(v.y), "=r"(v.z), "=r"(v.w) : "r"(a) : "memory");
    return v;
}
__device__ __forceinline__ uint32_t lds32(uint32_t a) {
    uint32_t v;
    asm volatile("ld.shared.u32 %0, [%1];" : "=r"(v) : "r"(a) : "memory");
    return v;
}
__device__ __forceinline__ uint2 lds64(uint32_t a) {
    uint2 v;
    asm volatile("ld.shared.v2.u32 {%0,%1}, [%2];" : "=r"(v.x), "=r"(v.y) : "r"(a) : "memory");
    return v;
}
__device__ __forceinline__ void sts8(uint32_t a, uint32_t v) {
    asm volatile("st.shared.u8 [%0], %1;" ::"r"(a), "r"(v) : "memory");
}
__device__ __forceinline__ void sts64(uint32_t a, uint32_t v0, uint32_t v1) {
    asm volatile("st.shared.v2.u32 [%0], {%1,%2};" ::"r"(a), "r"(v0), "r"(v1) : "memory");
}
#define OCT_BYTES 8192
#define BOX_LINES 8
__device__ __forceinline__ void fetch_quad(uint32_t dst, uint32_t bar, const uint4& y, uint64_t map) {
    asm volatile("{\n\t.reg .pred P;\n\telect.sync _|P, 0xffffffff;\n\t"
                 "@P cp.async.bulk.tensor.2d.shared::cluster.global.mbarrier::complete_tx::bytes [%0], [%6, {0, %2}], [%1];\n\t"
                 "@P cp.async.bulk.tensor.2d.shared::cluster.global.mbarrier::complete_tx::bytes [%0+%7], [%6, {0, %3}], [%1];\n\t"
                 "@P cp.async.bulk.tensor.2d.shared::cluster.global.mbarrier::complete_tx::bytes [%0+%8], [%6, {0, %4}], [%1];\n\t"
                 "@P cp.async.bulk.tensor.2d.shared::cluster.global.mbarrier::complete_tx::bytes [%0+%9], [%6, {0, %5}], [%1];\n\t}"
                 ::"r"(dst), "r"(bar), "r"(y.x), "r"(y.y), "r"(y.z), "r"(y.w), "l"(map), "n"(XREG), "n"(2 * XREG), "n"(3 * XREG)
                 : "memory");
}
__device__ __forceinline__ void cp_async_arrive(uint32_t bar) {
    asm volatile("cp.async.mbarrier.arrive.noinc.shared::cta.b64 [%0];" ::"r"(bar) : "memory");
}
__device__ __forceinline__ void mbar_init(uint32_t bar, uint32_t count) {
    asm volatile("mbarrier.init.shared::cta.b64 [%0], %1;" ::"r"(bar), "r"(count) : "memory");
}
__device__ __forceinline__ bool mbar_try(uint32_t bar, uint32_t parity) {
    uint32_t ok;
    asm volatile("{\n\t.reg .pred p;\n\tmbarrier.try_wait.parity.shared::cta.b64 p, [%1], %2;\n\tselp.u32 %0, 1, 0, p;\n\t}"
                 : "=r"(ok) : "r"(bar), "r"(parity) : "memory");
    return ok;
}
__device__ __forceinline__ void mbar_wait(uint32_t bar, uint32_t parity) {
    if (mbar_try(bar, parity)) return;
#pragma unroll 1
    for (int it = 0; it < SPIN_LIMIT; it++)
        if (mbar_try(bar, parity)) return;
    __trap();
}
__device__ __forceinline__ uint32_t clock_lo() {
    uint32_t v;
    asm volatile("mov.u32 %0, %%clock;" : "=r"(v));
    return v;
}
__device__ __forceinline__ uint32_t global_ticks() {
    uint32_t v;
    asm volatile("mov.u32 %0, %%globaltimer_lo;" : "=r"(v));
    return v >> 5;
}

#define TBL(snd, own) ((snd) * 144 + (own))
__device__ __forceinline__ void prefetch_line(const void* p) { asm volatile("prefetch.global.L2 [%0];" ::"l"(p)); }
__device__ __forceinline__ void prefetch_bulk(const void* p, uint32_t bytes) {
    asm volatile("{\n\t.reg .pred P;\n\telect.sync _|P, 0xffffffff;\n\t@P cp.async.bulk.prefetch.L2.global [%0], %1;\n\t}"
                 ::"l"(p), "r"(bytes) : "memory");
}
__device__ __forceinline__ uint4 ld_entry(const uint4* p) {
    uint4 e;
    asm volatile("ld.relaxed.gpu.global.v4.u32 {%0,%1,%2,%3}, [%4];" : "=r"(e.x), "=r"(e.y), "=r"(e.z), "=r"(e.w) : "l"(p) : "memory");
    return e;
}
__device__ __forceinline__ uint4 wait_entry(const uint4* p, uint4 e, uint32_t tag) {
    int it = 0;
    while (((e.y ^ tag) & TAGM) != 0u) {
        if (++it > SPIN_LIMIT) __trap();
        e = ld_entry(p);
    }
    return e;
}
__device__ __forceinline__ uint4 ldg128_if(bool p, const void* a, uint32_t other) {
    uint4 v = make_uint4(other, other, other, other);
    asm volatile("{\n\t.reg .pred P;\n\tsetp.ne.u32 P, %5, 0;\n\t@P ld.global.nc.L1::no_allocate.v4.u32 {%0,%1,%2,%3}, [%4];\n\t}"
                 : "+r"(v.x), "+r"(v.y), "+r"(v.z), "+r"(v.w) : "l"(a), "r"((uint32_t)p));
    return v;
}
__device__ __forceinline__ uint32_t ldg_u16(const void* p) {
    unsigned short v;
    asm volatile("ld.global.nc.u16 %0, [%1];" : "=h"(v) : "l"(p));
    return v;
}
__device__ __forceinline__ void stg64_if(bool p, void* a, uint32_t v0, uint32_t v1) {
    asm volatile("{\n\t.reg .pred P;\n\tsetp.ne.u32 P, %0, 0;\n\t@P st.global.v2.u32 [%1], {%2,%3};\n\t}"
                 ::"r"((uint32_t)p), "l"(a), "r"(v0), "r"(v1) : "memory");
}
__device__ __forceinline__ float bf_lo(uint32_t v) { return __uint_as_float(v << 16); }
__device__ __forceinline__ float bf_hi(uint32_t v) { return __uint_as_float(v & 0xffff0000u); }

#define F8(o) "+f"(d[o]), "+f"(d[o + 1]), "+f"(d[o + 2]), "+f"(d[o + 3]), "+f"(d[o + 4]), "+f"(d[o + 5]), "+f"(d[o + 6]), "+f"(d[o + 7])
template <int T>
__device__ __forceinline__ void wgmma_tiles(float (&d)[40], uint64_t a, uint64_t b, uint32_t acc) {
    if constexpr (T == 1)
        asm volatile("{\n\t.reg .pred P;\n\tsetp.ne.u32 P, %10, 0;\n\twgmma.mma_async.sync.aligned.m64n16k16.f32.bf16.bf16 "
                     "{%0,%1,%2,%3,%4,%5,%6,%7}, "
                     "%8, %9, P, 1, 1, 1, 0;\n\t}"
                     : F8(0) : "l"(a), "l"(b), "r"(acc));
    if constexpr (T == 2)
        asm volatile("{\n\t.reg .pred P;\n\tsetp.ne.u32 P, %18, 0;\n\twgmma.mma_async.sync.aligned.m64n32k16.f32.bf16.bf16 "
                     "{%0,%1,%2,%3,%4,%5,%6,%7,%8,%9,%10,%11,%12,%13,%14,%15}, "
                     "%16, %17, P, 1, 1, 1, 0;\n\t}"
                     : F8(0), F8(8) : "l"(a), "l"(b), "r"(acc));
    if constexpr (T == 3)
        asm volatile("{\n\t.reg .pred P;\n\tsetp.ne.u32 P, %26, 0;\n\twgmma.mma_async.sync.aligned.m64n48k16.f32.bf16.bf16 "
                     "{%0,%1,%2,%3,%4,%5,%6,%7,%8,%9,%10,%11,%12,%13,%14,%15,%16,%17,%18,%19,%20,%21,%22,%23}, "
                     "%24, %25, P, 1, 1, 1, 0;\n\t}"
                     : F8(0), F8(8), F8(16) : "l"(a), "l"(b), "r"(acc));
    if constexpr (T == 4)
        asm volatile("{\n\t.reg .pred P;\n\tsetp.ne.u32 P, %34, 0;\n\twgmma.mma_async.sync.aligned.m64n64k16.f32.bf16.bf16 "
                     "{%0,%1,%2,%3,%4,%5,%6,%7,%8,%9,%10,%11,%12,%13,%14,%15,%16,%17,%18,%19,%20,%21,%22,%23,%24,%25,%26,%27,%28,%29,%30,%31}, "
                     "%32, %33, P, 1, 1, 1, 0;\n\t}"
                     : F8(0), F8(8), F8(16), F8(24) : "l"(a), "l"(b), "r"(acc));
    if constexpr (T == 5)
        asm volatile("{\n\t.reg .pred P;\n\tsetp.ne.u32 P, %42, 0;\n\twgmma.mma_async.sync.aligned.m64n80k16.f32.bf16.bf16 "
                     "{%0,%1,%2,%3,%4,%5,%6,%7,%8,%9,%10,%11,%12,%13,%14,%15,%16,%17,%18,%19,%20,%21,%22,%23,%24,%25,%26,%27,%28,%29,%30,%31,%32,%33,%34,%35,%36,%37,%38,%39}, "
                     "%40, %41, P, 1, 1, 1, 0;\n\t}"
                     : F8(0), F8(8), F8(16), F8(24), F8(32) : "l"(a), "l"(b), "r"(acc));
}
template <int T, int O>
__device__ __forceinline__ void mix_tiles(float (&d)[40], uint64_t da, uint64_t db) {
    asm volatile("wgmma.fence.sync.aligned;" ::: "memory");
#pragma unroll
    for (int ks = 0; ks < 8; ks++) wgmma_tiles<T>(d, da + ks * 128, db + O * 128 + (ks >> 1) * (XREG / 16) + (ks & 1) * 16, ks);
    asm volatile("wgmma.commit_group.sync.aligned;" ::: "memory");
}
template <int T, int O, int PENDING>
__device__ __forceinline__ void store_tiles(float (&d)[40], uint32_t* op, int left, uint32_t bar) {
    asm volatile("wgmma.wait_group.sync.aligned %0;" ::"n"(PENDING) : "memory");
#pragma unroll
    for (int i = 0; i < 8 * T; i++) asm volatile("" : "+f"(d[i])::"memory");
#pragma unroll
    for (int k = 0; k < T; k++) {
        const int n = 16 * ((O + k) % 5) + (O + k) / 5;
#pragma unroll
        for (int u = 0; u < 2; u++)
            stg64_if(n < left, op + n * 256 + u * 16, pack_bf16(d[8 * k + 2 * u], d[8 * k + 2 * u + 1]),
                     pack_bf16(d[8 * k + 4 + 2 * u], d[8 * k + 4 + 2 * u + 1]));
    }
    if (PENDING) asm volatile("bar.sync %0, 128;" ::"r"(bar) : "memory");
}

__device__ __noinline__ void slow_cta(unsigned char* smem, const char* x, const char* ef, const __nv_bfloat16* w_rad,
                                      const __nv_bfloat16* cg, const __nv_bfloat16* w_mix, uint32_t* out, int node0, int Sc,
                                      uint32_t tag) {
    float* agg = reinterpret_cast<float*>(smem);
    Misc& ms = *reinterpret_cast<Misc*>(smem + MISC_OFF);
    const int tid = threadIdx.x, lane = tid & 31, warp = tid >> 5;
    for (int i = tid; i < Sc * 512; i += NT) agg[i] = 0.f;
    if (tid < (int)gridDim.x) {
        uint32_t v;
        asm volatile("ld.relaxed.gpu.global.u32 %0, [%1];" : "=r"(v) : "l"(&g_table[TBL(tid, blockIdx.x)]) : "memory");
        ms.rseg[tid] = v;
    }
    __syncthreads();
    uint2 wr[16];
#pragma unroll
    for (int f = 0; f < 16; f++) wr[f] = *reinterpret_cast<const uint2*>(w_rad + f * 128 + 4 * lane);
    float cgl[4];
#pragma unroll
    for (int f = 0; f < 4; f++) cgl[f] = __bfloat162float(cg[((lane >> 2) & 3) * 16 + f * 4 + (lane & 3)]);
    for (int s = 0; s < (int)gridDim.x; s++) {
        const int cn = ms.rseg[s] & 0xfffu;
        const uint4* p = g_staged + s * EPC_MAX + ((ms.rseg[s] >> 12) & 0xfffu);
        for (int i = (warp + s) % NWARP; i < cn; i += NWARP) {
            const uint4 e = wait_entry(p + i, ld_entry(p + i), tag);
            const uint4* xp = reinterpret_cast<const uint4*>(x + (size_t)(e.x & 0x1fff8u) * 128 + lane * 32);
            const uint4* fp = reinterpret_cast<const uint4*>(ef + (e.y & 0x1ffffe0u));
            const uint4 xa = xp[0], xb = xp[1], fa = fp[0], fb = fp[1];
            const uint32_t fv[8] = {fa.x, fa.y, fa.z, fa.w, fb.x, fb.y, fb.z, fb.w};
            const uint32_t xv[8] = {xa.x, xa.y, xa.z, xa.w, xb.x, xb.y, xb.z, xb.w};
            float h[4] = {0.f, 0.f, 0.f, 0.f};
#pragma unroll
            for (int f = 0; f < 16; f++) {
                const float v = (f & 1) ? bf_hi(fv[f >> 1]) : bf_lo(fv[f >> 1]);
                h[0] += v * bf_lo(wr[f].x); h[1] += v * bf_hi(wr[f].x); h[2] += v * bf_lo(wr[f].y); h[3] += v * bf_hi(wr[f].y);
            }
            const float wl = bf_lo(e.z) * cgl[0] + bf_hi(e.z) * cgl[1] + bf_lo(e.w) * cgl[2] + bf_hi(e.w) * cgl[3];
            const uint32_t tile = (e.x >> 19) / NB;
            float* ap = agg + ((tile >> 2) * 16 + ((e.y >> 25) & 3u) * 4 + (tile & 3)) * 512 + lane * 16;
#pragma unroll
            for (int o = 0; o < 4; o++) {
                const float w0 = __shfl_sync(0xffffffffu, wl, o), w1 = __shfl_sync(0xffffffffu, wl, 4 + o);
                const float w2 = __shfl_sync(0xffffffffu, wl, 8 + o), w3 = __shfl_sync(0xffffffffu, wl, 12 + o);
#pragma unroll
                for (int k = 0; k < 4; k++) {
                    const float tp = bf_lo(xv[2 * k]) * w0 + bf_hi(xv[2 * k]) * w1 + bf_lo(xv[2 * k + 1]) * w2 + bf_hi(xv[2 * k + 1]) * w3;
                    atomicAdd(ap + k * 4 + o, tp * (h[k] / (1.f + __expf(-h[k]))));
                }
            }
        }
    }
    __syncthreads();
    for (int n = tid >> 7; n < Sc; n += NT / 128) {
        const int d = tid & 127;
        float o[4] = {0.f, 0.f, 0.f, 0.f};
        for (int c = 0; c < 128; c++) {
            const float4 a = *reinterpret_cast<const float4*>(agg + n * 512 + c * 4);
            const float w = __bfloat162float(w_mix[c * 128 + d]);
            o[0] += a.x * w; o[1] += a.y * w; o[2] += a.z * w; o[3] += a.w * w;
        }
        *reinterpret_cast<uint2*>(out + (size_t)(node0 + n) * 256 + d * 2) = make_uint2(pack_bf16(o[0], o[1]), pack_bf16(o[2], o[3]));
    }
}

__global__ void __launch_bounds__(NT, 1)
tfn_kernel(const __grid_constant__ CUtensorMap xmap, const char* __restrict__ x, const int* __restrict__ src,
           const int* __restrict__ dst, const uint2* __restrict__ Y, const char* __restrict__ ef,
           const __nv_bfloat16* __restrict__ w_rad, const __nv_bfloat16* __restrict__ cg,
           const __nv_bfloat16* __restrict__ w_mix, uint32_t* __restrict__ out, int N, int E, int S, int EPC,
           uint32_t magicS, uint32_t magicB, uint32_t zero, uint32_t pace, int lead, uint32_t pfb, uint32_t curve) {
    extern __shared__ __align__(1024) unsigned char smem[];
    Misc& ms = *reinterpret_cast<Misc*>(smem + MISC_OFF);
    int* const cnt = reinterpret_cast<int*>(smem + CNT_OFF);
    int* const start = reinterpret_cast<int*>(smem + START_OFF);
    uint32_t* const bcnt = reinterpret_cast<uint32_t*>(smem + BCNT_OFF);
    uint32_t* const bcum = reinterpret_cast<uint32_t*>(smem + BCUM_OFF);
    uint32_t* const gi = reinterpret_cast<uint32_t*>(smem + GI_OFF);
    const int tid = threadIdx.x;
    const int lane = tid & 31, warp = __shfl_sync(0xffffffffu, tid >> 5, 0);
    const int c = blockIdx.x;
    const int numCTA = gridDim.x;
    const int node0 = c * S;
    const int Sc = max(0, min(S, N - node0));
    const uint32_t sb = (uint32_t)__cvta_generic_to_shared(smem);

    const int eb = c * EPC;
    const int ne = max(0, min(EPC, E - eb));
    int d8[8], s8[8];
#pragma unroll
    for (int h = 0; h < 2; h++) {
        const uint4 v = ldg128_if(4 * (tid + h * NT) + 3 < ne, dst + eb + 4 * (tid + h * NT), 0xffffffffu);
        d8[4 * h] = (int)v.x; d8[4 * h + 1] = (int)v.y; d8[4 * h + 2] = (int)v.z; d8[4 * h + 3] = (int)v.w;
    }
#pragma unroll
    for (int h = 0; h < 2; h++) {
        const uint4 v = ldg128_if(4 * (tid + h * NT) + 3 < ne, src + eb + 4 * (tid + h * NT), 0u);
        s8[4 * h] = (int)v.x; s8[4 * h + 1] = (int)v.y; s8[4 * h + 2] = (int)v.z; s8[4 * h + 3] = (int)v.w;
    }
    if (ne & 3) {
#pragma unroll
        for (int k = 0; k < 8; k++) {
            const int i = 4 * (tid + (k >> 2) * NT) + (k & 3);
            if (i >= (ne & ~3) && i < ne) { d8[k] = __ldg(dst + eb + i); s8[k] = __ldg(src + eb + i); }
        }
    }
    if (tid == NT - 64) asm volatile("prefetch.tensormap [%0];" ::"l"(&xmap) : "memory");
    uint32_t ep0 = 0;
    if (tid == NT - 1) asm volatile("ld.relaxed.gpu.global.u32 %0, [%1];" : "=r"(ep0) : "l"(&g_epoch[c]) : "memory");
    uint32_t cgr[4] = {0u, 0u, 0u, 0u};
    if (warp >= 8 && (lane & 3) < 2) {
        const unsigned short* cu = reinterpret_cast<const unsigned short*>(cg) + ((lane >> 2) & 3) * 16 + (lane & 3) * 8 + (lane >> 4);
        cgr[0] = ldg_u16(cu); cgr[1] = ldg_u16(cu + 4); cgr[2] = ldg_u16(cu + 2); cgr[3] = ldg_u16(cu + 6);
    }
    if (warp == 7) {
        for (int i = c + lane * numCTA; i < 32 + 256; i += 32 * numCTA)
            prefetch_line(i < 32 ? (const char*)w_rad + i * 128 : (const char*)w_mix + (i - 32) * 128);
    }
    if (tid < MAXCTA) cnt[tid] = 0;
#pragma unroll
    for (int k = 0; k < 5; k++) bcnt[tid + k * NT] = 0u;
    if (tid < 224) reinterpret_cast<uint2*>(smem + ZERO_OFF)[tid] = make_uint2(0u, 0u);
    if (tid >= 160 && tid < 320) {
        const int i = tid - 160;
        *reinterpret_cast<uint32_t*>(smem + AUX_OFF + (i >> 5) * AUX_ST + ((i >> 3) & 3) * AUX_GR + 512 + (i & 7) * 16) =
            (i >> 5) == NST - 1 ? (uint32_t)(1 - NST) << 24 : 1u << 24;
    }
    if (lane < NST && warp < 8) {
        const int k = warp >> 2;
        mbar_init(sb + AUX_OFF + lane * AUX_ST + (warp & 3) * AUX_GR + BAR_F0 + 16 * k, k == 0 ? F0_COUNT : 2u);
    }
    if (tid == 330) { mbar_init(sb + MISC_OFF + 16, 1); mbar_init(sb + MISC_OFF, 128); ms.node0 = node0; ms.Sc = Sc; ms.dmax = -32768; ms.ref = global_ticks(); }
    __syncthreads();
    const uint32_t cgb0 = cgr[0] | (cgr[1] << 16), cgb1 = cgr[2] | (cgr[3] << 16);
    uint2 y8[8];
#pragma unroll
    for (int h = 0; h < 4; h++) {
        const int i = 4 * (tid + (h >> 1) * NT) + 2 * (h & 1);
        const uint4 v = ldg128_if(i + 1 < ne, Y + eb + i, 0u);
        y8[2 * h] = make_uint2(v.x, v.y); y8[2 * h + 1] = make_uint2(v.z, v.w);
    }
    int bin[8], pos[8];
#pragma unroll
    for (int k = 0; k < 8; k++) {
        bin[k] = (int)__umulhi((uint32_t)d8[k], magicS);
        if (d8[k] >= 0) pos[k] = atomicAdd(&cnt[bin[k]], 1);
    }
    if (tid == NT - 1) {
        ms.epoch = ep0 + 1u;
        g_epoch[c] = ep0 + 1u;
    }
    __syncthreads();
    const uint32_t epoch = ms.epoch;
    if (warp < 5) {
        int pre = 0;
#pragma unroll
        for (int k = 0; k < 4; k++)
            if (k < warp) pre += cnt[lane + 32 * k];
        const int v = tid < numCTA ? cnt[tid] : 0;
        int incl = v;
#pragma unroll
        for (int o = 1; o < 32; o <<= 1) {
            int t_ = __shfl_up_sync(0xffffffffu, incl, o);
            if (lane >= o) incl += t_;
        }
        const int ex = __reduce_add_sync(0xffffffffu, pre) + incl - v;
        if (tid < MAXCTA) start[tid] = ex;
        if (tid < numCTA)
            asm volatile("st.relaxed.gpu.global.u32 [%0], %1;" ::"l"(g_table + TBL(c, tid)), "r"((epoch << 24) | (ex << 12) | v) : "memory");
    }
    const uint32_t tag = epoch & TAGM;
    uint32_t w0[8], w1[8];
#pragma unroll
    for (int k = 0; k < 8; k++) {
        const uint32_t dl = (uint32_t)(d8[k] - bin[k] * S);
        w0[k] = (((((dl >> 2) & 0x1cu) | (dl & 3u)) * NB + __umulhi((uint32_t)s8[k], magicB)) << 19) + (uint32_t)s8[k] * 8u;
        w1[k] = (((dl << 23) & 0x3e000000u) | (((dl << 28) & 0xc0000000u) ^ (dl << 31))) +
                ((uint32_t)(eb + 4 * tid) * 32u + tag + ((k >> 2) * 4 * NT + (k & 3)) * 32);
    }
    __syncthreads();
    if (tid == 192)
        asm volatile("mbarrier.arrive.expect_tx.shared::cta.b64 _, [%2], 4096;\n\t"
                     "cp.async.bulk.shared::cluster.global.mbarrier::complete_tx::bytes [%0], [%1], 4096, [%2];"
                     ::"r"(sb + WR_OFF), "l"(w_rad), "r"(sb + MISC_OFF + 16) : "memory");
    if (ne & 1) {
#pragma unroll
        for (int h = 0; h < 4; h++)
            if (4 * (tid + (h >> 1) * NT) + 2 * (h & 1) + 1 == ne) y8[2 * h] = __ldg(Y + eb + ne - 1);
    }
#pragma unroll
    for (int k = 0; k < 8; k++)
        if (d8[k] >= 0) pos[k] += start[bin[k]];
#pragma unroll
    for (int k = 0; k < 8; k++)
        if (d8[k] >= 0) reinterpret_cast<uint4*>(smem)[pos[k]] = make_uint4(w0[k], w1[k], y8[k].x, y8[k].y);
    asm volatile("fence.proxy.async.shared::cta;" ::: "memory");
    __syncthreads();
    if (tid == NT - 32 && ne > 0) {
        asm volatile("cp.async.bulk.global.shared::cta.bulk_group [%0], [%1], %2;" ::"l"(g_staged + (size_t)c * EPC_MAX),
                     "r"(sb), "r"(ne * 16) : "memory");
        asm volatile("cp.async.bulk.commit_group;" ::: "memory");
    }

    const int g = lane >> 2, t = lane & 3;
    uint32_t wr[4][4];
    if (tid == 64 && (uint32_t)(c + 1) * 4u * PFA * pfb <= (uint32_t)N * 1024u)
        asm volatile("cp.async.bulk.prefetch.L2.global [%0], %1;" ::"l"(x + (size_t)c * 4u * PFA * pfb), "r"(4u * PFA * pfb) : "memory");
    auto uni = [&](uint32_t v) { return __shfl_sync(0xffffffffu, v + (lane & zero), 0); };
    auto keep = [&](uint32_t v) { return __shfl_sync(0xffffffffu, v, lane); };
    const int pgrp = (warp + 2) & 3;
    uint32_t s0, maplo, maphi, e_l, h_l, f_l, w_l, eflo, efhi, fsel, bytes, pc, cu, tbase;
    auto constants = [&]() {
        s0 = uni(sb);
        const uint64_t map0 = reinterpret_cast<uint64_t>(&xmap), ef0 = reinterpret_cast<uint64_t>(ef) + t * 8;
        maphi = uni((uint32_t)(map0 >> 32)); maplo = uni((uint32_t)(map0 & 0xffffffffu));
        e_l = keep(SE_OFF - SY_OFF + (4 * (g & 1) + (g >> 1)) * 4);
        h_l = keep(sb + SH_OFF + pgrp * GCAP * 8 - 64 + g * 8 + (t & 1) * 4);
        f_l = keep(sb + AUX_OFF + pgrp * AUX_GR + 512 + (g >> 1) * 32 + (t & 1) * 16 + (~g & 1));
        w_l = keep(sb + AUX_OFF + pgrp * AUX_GR + lane * 8);
        efhi = keep((uint32_t)(ef0 >> 32) + (lane & zero)); eflo = keep((uint32_t)(ef0 & 0xffffffffu));
        fsel = keep(g & 1 ? 7 : 3);
        bytes = keep(lane == 0 ? OCT_BYTES : 0u);
        pc = uni(pace); cu = uni(curve);
        tbase = clock_lo() + (uint32_t)((int)(short)(ms.ref - global_ticks()) * 63 + lead);
    };

    uint4 ent[RND];
    uint32_t rk[RND];
    int tot = 0;
    if (warp == NWARP - 1) {
        asm volatile("cp.async.bulk.wait_group 0;" ::: "memory");
        __syncwarp();
        const uint32_t w = (epoch << 16) | (global_ticks() & 0xffffu);
#pragma unroll
        for (int k = 0; k < 5; k++)
            asm volatile("{\n\t.reg .pred P;\n\tsetp.lt.s32 P, %0, %1;\n\t@P st.relaxed.gpu.global.u32 [%2+4], %3;\n\t}"
                         ::"r"(lane + 32 * k), "r"(numCTA), "l"(g_table + TBL(c, lane) + 32 * k), "r"(w) : "memory");
    } else {
        const bool mine = warp + NCOL * lane < numCTA;
        const uint2* tp = g_table + TBL(warp + NCOL * lane, c);
        const uint4* gp[RND];
        auto poll = [&](const uint32_t* p, uint32_t v, int sh) {
            int it = 0;
            do {
                if (mine) asm volatile("ld.relaxed.gpu.global.u32 %0, [%1];" : "=r"(v) : "l"(p) : "memory");
                if (++it > SPIN_LIMIT) __trap();
            } while (!__all_sync(0xffffffffu, ((v ^ (epoch << sh)) >> sh) == 0u));
            return v;
        };
        const uint32_t sv = poll(&tp->x, epoch << 24, 24);
        int incl = (int)(sv & 0xfffu);
#pragma unroll
        for (int o = 1; o < 16; o <<= 1) {
            int t_ = __shfl_up_sync(0xffffffffu, incl, o);
            if (lane >= o) incl += t_;
        }
        tot = __shfl_sync(0xffffffffu, incl, 15);
        const bool some = (sv & 0xfffu) != 0u;
        const uint32_t seg_b = sb + SEG_OFF + warp * 64;
        if (some)
            asm volatile("st.shared.u32 [%0], %1;" ::"r"(seg_b + 4 * __popc(__ballot_sync(__activemask(), true) & ((1u << lane) - 1u))),
                         "r"((warp + NCOL * lane) * EPC_MAX + (int)((sv >> 12) & 0xfffu) - incl + (int)(sv & 0xfffu)) : "memory");
        __syncwarp();
        if (!some) incl = -1;
        const uint32_t le = (2u << lane) - 1u;
        uint32_t sg = seg_b;
#pragma unroll
        for (int r = 0; r < RND; r++) {
            uint32_t bit;
            asm("shl.b32 %0, 1, %1;" : "=r"(bit) : "r"(incl - 32 * r));
            const uint32_t ends = __reduce_or_sync(0xffffffffu, bit);
            gp[r] = g_staged + (lane + 32 * r + (int)lds32(sg + 4 * __popc(ends & le)));
            sg += 4 * __popc(ends);
            ent[r].y = tag;
        }
        if (warp < 8) {
            mbar_wait(sb + MISC_OFF + 16, 0);
#pragma unroll
            for (int j = 0; j < 4; j++) {
                const int dj = (j & 1) + 4 * (j >> 1);
                const uint32_t p = sb + WR_OFF + t * 4 * 256 + 32 * (2 * ((warp >> 2) & 1) + dj) + 4 * (g ^ dj);
#pragma unroll
                for (int i = 0; i < 4; i++) wr[j][i] = lds32(p + i * 256);
            }
#pragma unroll
            for (int j = 0; j < 4; j++) {
                uint32_t h[4];
#pragma unroll
                for (int i = 0; i < 4; i++) h[i] = half_bf16x2(wr[j][i]);
                wr[j][0] = __byte_perm(h[0], h[1], 0x5410);
                wr[j][1] = __byte_perm(h[0], h[1], 0x7632);
                wr[j][2] = __byte_perm(h[2], h[3], 0x5410);
                wr[j][3] = __byte_perm(h[2], h[3], 0x7632);
            }
        }
        const uint32_t ts = poll(&tp->y, (epoch << 16) | (ms.ref & 0xffffu), 16);
#pragma unroll
        for (int r = 0; r < RND; r++)
            if (lane + 32 * r < tot) ent[r] = ld_entry(gp[r]);
        const int dm = __reduce_max_sync(0xffffffffu, (int)(short)(ts - ms.ref));
        if (lane == 0) atomicMax(&ms.dmax, dm);
        uint32_t stale = 0;
#pragma unroll
        for (int r = 0; r < RND; r++) stale |= ent[r].y ^ tag;
        if (stale & TAGM) {
#pragma unroll
            for (int r = 0; r < RND; r++)
                if (lane + 32 * r < tot) ent[r] = wait_entry(gp[r], ent[r], tag);
        }
#pragma unroll
        for (int r = 0; r < RND; r++)
            if (lane + 32 * r < tot) rk[r] = atomicAdd(reinterpret_cast<uint32_t*>(smem + BCNT_OFF + (ent[r].x >> 17)), 1u);
    }
    constants();
    __syncthreads();
    bool over = tot > 32 * RND || S > SFAST;
    {
        const int grp = warp & 3, u = warp >> 2;
        uint32_t v[3], incl[3], lo[3], hi[3], tt[3];
#pragma unroll
        for (int p = 0; p < 3; p++) {
            uint32_t a[3];
#pragma unroll
            for (int i = 0; i < 3; i++) {
                a[i] = bcnt[(grp + 8 * p) * NB + 32 * i + lane];
                if (p < 2) a[i] += bcnt[(grp + 8 * p + 4) * NB + 32 * i + lane] << 16;
            }
            v[p] = u == 0 ? a[0] : (u == 1 ? a[1] : a[2]);
            incl[p] = v[p];
            lo[p] = __reduce_add_sync(0xffffffffu, u == 0 ? 0u : (u == 1 ? a[0] : a[0] + a[1]));
            tt[p] = __reduce_add_sync(0xffffffffu, a[0] + a[1] + a[2]);
        }
#pragma unroll
        for (int o = 1; o < 32; o <<= 1)
#pragma unroll
            for (int p = 0; p < 3; p++) {
                asm volatile("{\n\t.reg .pred P;\n\t.reg .b32 v;\n\tshfl.sync.up.b32 v|P, %0, %1, 0, 0xffffffff;\n\t@P add.u32 %0, %0, v;\n\t}"
                             : "+r"(incl[p]) : "r"(o));
            }
        uint32_t all = 0, nq = 0;
#pragma unroll
        for (int p = 0; p < 3; p++) {
            const uint32_t up = (tt[p] + 0x30003u) & 0xfffcfffcu;
            nq += up >> 2;
            tt[p] = up - tt[p];
            incl[p] += lo[p] + tt[p];
            v[p] = incl[p] - v[p];
            lo[p] = warp < 4 && lane == 0 ? 0u : ((v[p] + 0x10001u) >> 2) & 0x3fff3fffu;
            hi[p] = ((incl[p] + 0x10001u) >> 2) & 0x3fff3fffu;
            all += lo[p];
        }
        nq = (nq & 0xffffu) + (nq >> 16);
        uint32_t run = (all & 0xffffu) + (all >> 16) + (nq & 1u) + grp * (GCAP / 4), rel[5];
#pragma unroll
        for (int i = 0; i < 5; i++) {
            const uint32_t l = (i & 1) ? lo[i >> 1] >> 16 : lo[i >> 1] & 0xffffu, h = (i & 1) ? hi[i >> 1] >> 16 : hi[i >> 1] & 0xffffu;
            const uint32_t tb = (grp + 4 * i) * JCAP;
            bcum[(grp + 4 * i) * NB + 32 * u + lane] = ((i & 1) ? v[i >> 1] >> 16 : v[i >> 1] & 0xffffu) + 4 * tb;
            rel[i] = (run - l - tb) * 16u;
            if (l < h) { gi[tb + l] = rel[i]; gi[tb + h - 1] = rel[i]; }
            run += h - l;
        }
        if ((((hi[0] - lo[0] + 0x10001u) | (hi[1] - lo[1] + 0x10001u) | (hi[2] - lo[2] + 1u)) & 0xfffcfffcu) != 0u) {
#pragma unroll
            for (int i = 0; i < 5; i++) {
                const uint32_t l = (i & 1) ? lo[i >> 1] >> 16 : lo[i >> 1] & 0xffffu, h = (i & 1) ? hi[i >> 1] >> 16 : hi[i >> 1] & 0xffffu;
#pragma unroll 1
                for (uint32_t j = l; j < h; j++) gi[(grp + 4 * i) * JCAP + j] = rel[i];
            }
        }
        if (warp < 4 && lane == 0) ms.nq[grp] = (int)nq;
        over = over || 4 * nq + 20 > GCAP;
    }
    asm volatile("fence.proxy.async.shared::cta;" ::: "memory");
    const bool slow = __syncthreads_or(over);
    if (slow) {
        slow_cta(smem, x, ef, w_rad, cg, w_mix, out, node0, Sc, tag);
        return;
    }
    const uint32_t T0 = uni(tbase + ms.dmax * 63);
    const uint32_t noct = uni((uint32_t)(ms.nq[pgrp] + 1) >> 1);
    {
        auto put = [&](bool ok, uint32_t p4, uint32_t y, uint32_t e) {
            asm volatile("{\n\t.reg .pred P;\n\tsetp.ne.u32 P, %0, 0;\n\t@P st.shared.u32 [%1+%4], %2;\n\t@P st.shared.u32 [%1+%5], %3;\n\t}"
                         ::"r"((uint32_t)ok), "r"(sb + p4), "r"(y), "r"(e), "n"(SY_OFF), "n"(SE_OFF) : "memory");
        };
        auto puty = [&](bool ok, uint32_t p4, uint32_t h0, uint32_t h1) {
            asm volatile("{\n\t.reg .pred P;\n\tsetp.ne.u32 P, %0, 0;\n\t@P st.shared.v2.u32 [%1+%4], {%2,%3};\n\t}"
                         ::"r"((uint32_t)ok), "r"(sb + 2 * p4), "r"(h0), "r"(h1), "n"(SH_OFF) : "memory");
        };
        auto place = [&](int r0, int r1) {
#pragma unroll
            for (int r = r0; r < r1; r++)
                if (lane + 32 * r < tot) rk[r] += *reinterpret_cast<const uint32_t*>(smem + BCUM_OFF + (ent[r].x >> 17));
#pragma unroll
            for (int r = r0; r < r1; r++)
                if (lane + 32 * r < tot) rk[r] = 4u * rk[r] + gi[rk[r] >> 2];
#pragma unroll
            for (int r = r0; r < r1; r++) put(lane + 32 * r < tot, rk[r], ent[r].x & 0x1ffffu, ent[r].y);
#pragma unroll
            for (int r = r0; r < r1; r++) puty(lane + 32 * r < tot, rk[r], ent[r].z, ent[r].w);
        };
        if (warp == NCOL) {
#pragma unroll
            for (int k = 0; k < 5; k++) {
                const uint32_t id = lane + 32 * k, py = ((id + 53 * c) & 127u) * 8u;
                if (k < 3) {
                    const uint32_t tile = min(id >> 2, 19u), c0 = bcum[tile * NB];
                    const bool ok = (id & 3) < (c0 & 3u) && id < 80;
                    const uint32_t p4 = gi[tile * JCAP] + (tile * JCAP * 4 + (id & 3)) * 4;
                    put(ok, p4, py, tile >> 2 << 27);
                    puty(ok, p4, 0u, 0u);
                } else {
                    const uint32_t i = id & 15, grp = (id >> 4) & 3, nq = ms.nq[grp];
                    const bool ok = i < 8 || (i < 12 && (nq & 1));
                    const uint32_t p4 = (grp * GCAP + (i < 8 ? 4 * ((nq + 1) & ~1u) + i : i - 8)) * 4;
                    put(ok, p4, py, i < 8 ? 6u << 27 : 0u);
                    puty(ok, p4, 0u, 0u);
                }
            }
        } else {
            place(0, RND0);
            if (tot > 32 * RND0) place(RND0, RND);
        }
    }
    __syncthreads();

    if (warp < 8) {
        asm volatile("setmaxnreg.inc.sync.aligned.u32 232;");
        const int half = warp >> 2, grp = (warp + half) & 3;
        const uint32_t az = __shfl_sync(0xffffffffu, sb + ZERO_OFF + (g >> 1) * 512 + t * 32 + (g & 1) * 16, lane);
        uint32_t sb2;
        asm volatile(
            "{\n"
            ".reg .f32 c<160>, h<16>, th<8>, fz;\n"
            ".reg .b32 x<16>, a<4>, r<4>, rd<8>, e<2>, p<80>, mt, xa, aa, an<4>, ab, ea, tmp, cnt, st, rl, rh, dum, du2;\n"
            ".reg .b16 lo, hi;\n"
            ".reg .pred pk, pm, pw, pe, pr, d0, d1, d2, d3, d4;\n"
            "mov.f32 fz, 0f00000000;\n"
            "mov.f32 c0, fz; mov.f32 c1, fz; mov.f32 c2, fz; mov.f32 c3, fz; mov.f32 c4, fz; mov.f32 c5, fz; mov.f32 c6, fz; mov.f32 c7, fz;\n"
            "mov.f32 c8, fz; mov.f32 c9, fz; mov.f32 c10, fz; mov.f32 c11, fz; mov.f32 c12, fz; mov.f32 c13, fz; mov.f32 c14, fz; mov.f32 c15, fz;\n"
            "mov.f32 c16, fz; mov.f32 c17, fz; mov.f32 c18, fz; mov.f32 c19, fz; mov.f32 c20, fz; mov.f32 c21, fz; mov.f32 c22, fz; mov.f32 c23, fz;\n"
            "mov.f32 c24, fz; mov.f32 c25, fz; mov.f32 c26, fz; mov.f32 c27, fz; mov.f32 c28, fz; mov.f32 c29, fz; mov.f32 c30, fz; mov.f32 c31, fz;\n"
            "mov.f32 c32, fz; mov.f32 c33, fz; mov.f32 c34, fz; mov.f32 c35, fz; mov.f32 c36, fz; mov.f32 c37, fz; mov.f32 c38, fz; mov.f32 c39, fz;\n"
            "mov.f32 c40, fz; mov.f32 c41, fz; mov.f32 c42, fz; mov.f32 c43, fz; mov.f32 c44, fz; mov.f32 c45, fz; mov.f32 c46, fz; mov.f32 c47, fz;\n"
            "mov.f32 c48, fz; mov.f32 c49, fz; mov.f32 c50, fz; mov.f32 c51, fz; mov.f32 c52, fz; mov.f32 c53, fz; mov.f32 c54, fz; mov.f32 c55, fz;\n"
            "mov.f32 c56, fz; mov.f32 c57, fz; mov.f32 c58, fz; mov.f32 c59, fz; mov.f32 c60, fz; mov.f32 c61, fz; mov.f32 c62, fz; mov.f32 c63, fz;\n"
            "mov.f32 c64, fz; mov.f32 c65, fz; mov.f32 c66, fz; mov.f32 c67, fz; mov.f32 c68, fz; mov.f32 c69, fz; mov.f32 c70, fz; mov.f32 c71, fz;\n"
            "mov.f32 c72, fz; mov.f32 c73, fz; mov.f32 c74, fz; mov.f32 c75, fz; mov.f32 c76, fz; mov.f32 c77, fz; mov.f32 c78, fz; mov.f32 c79, fz;\n"
            "mov.f32 c80, fz; mov.f32 c81, fz; mov.f32 c82, fz; mov.f32 c83, fz; mov.f32 c84, fz; mov.f32 c85, fz; mov.f32 c86, fz; mov.f32 c87, fz;\n"
            "mov.f32 c88, fz; mov.f32 c89, fz; mov.f32 c90, fz; mov.f32 c91, fz; mov.f32 c92, fz; mov.f32 c93, fz; mov.f32 c94, fz; mov.f32 c95, fz;\n"
            "mov.f32 c96, fz; mov.f32 c97, fz; mov.f32 c98, fz; mov.f32 c99, fz; mov.f32 c100, fz; mov.f32 c101, fz; mov.f32 c102, fz; mov.f32 c103, fz;\n"
            "mov.f32 c104, fz; mov.f32 c105, fz; mov.f32 c106, fz; mov.f32 c107, fz; mov.f32 c108, fz; mov.f32 c109, fz; mov.f32 c110, fz; mov.f32 c111, fz;\n"
            "mov.f32 c112, fz; mov.f32 c113, fz; mov.f32 c114, fz; mov.f32 c115, fz; mov.f32 c116, fz; mov.f32 c117, fz; mov.f32 c118, fz; mov.f32 c119, fz;\n"
            "mov.f32 c120, fz; mov.f32 c121, fz; mov.f32 c122, fz; mov.f32 c123, fz; mov.f32 c124, fz; mov.f32 c125, fz; mov.f32 c126, fz; mov.f32 c127, fz;\n"
            "mov.f32 c128, fz; mov.f32 c129, fz; mov.f32 c130, fz; mov.f32 c131, fz; mov.f32 c132, fz; mov.f32 c133, fz; mov.f32 c134, fz; mov.f32 c135, fz;\n"
            "mov.f32 c136, fz; mov.f32 c137, fz; mov.f32 c138, fz; mov.f32 c139, fz; mov.f32 c140, fz; mov.f32 c141, fz; mov.f32 c142, fz; mov.f32 c143, fz;\n"
            "mov.f32 c144, fz; mov.f32 c145, fz; mov.f32 c146, fz; mov.f32 c147, fz; mov.f32 c148, fz; mov.f32 c149, fz; mov.f32 c150, fz; mov.f32 c151, fz;\n"
            "mov.f32 c152, fz; mov.f32 c153, fz; mov.f32 c154, fz; mov.f32 c155, fz; mov.f32 c156, fz; mov.f32 c157, fz; mov.f32 c158, fz; mov.f32 c159, fz;\n"
            "mov.b32 x0, 0; mov.b32 x1, 0; mov.b32 x2, 0; mov.b32 x3, 0; mov.b32 x4, 0; mov.b32 x5, 0; mov.b32 x6, 0; mov.b32 x7, 0; mov.b32 x8, 0; mov.b32 x9, 0; mov.b32 x10, 0; mov.b32 x11, 0; mov.b32 x12, 0; mov.b32 x13, 0; mov.b32 x14, 0; mov.b32 x15, 0;\n"
            "mov.b32 a0, 0; mov.b32 a1, 0; mov.b32 a2, 0; mov.b32 a3, 0;\n"
            "elect.sync _|pe, 0xffffffff;\n"
            "mov.pred pr, pe;\n"
            "mov.b32 xa, %1; mov.b32 aa, %2; mov.b32 ea, %4;\n"
            "mov.u32 cnt, 0; and.b32 tmp, aa, 0xffffff80;\n"
            "S0L: mbarrier.try_wait.parity.shared::cta.b64 pw, [tmp+520], 0; @pw bra.uni S0D;\n"
            "add.u32 cnt, cnt, 1; setp.lt.u32 pk, cnt, 1000000; @pk bra.uni S0L; trap;\n"
            "S0D:\n"
            "ld.shared.v2.u32 {e0,e1}, [ea]; ld.shared.u32 mt, [aa+512];\n"
            "mma.sync.aligned.m16n8k16.row.col.f32.bf16.bf16.f32 {h0,h1,h2,h3}, {%7,%8,%9,%10}, {e0,e1}, {fz,fz,fz,fz};\n"
            "mma.sync.aligned.m16n8k16.row.col.f32.bf16.bf16.f32 {h4,h5,h6,h7}, {%11,%12,%13,%14}, {e0,e1}, {fz,fz,fz,fz};\n"
            "mma.sync.aligned.m16n8k16.row.col.f32.bf16.bf16.f32 {h8,h9,h10,h11}, {%15,%16,%17,%18}, {e0,e1}, {fz,fz,fz,fz};\n"
            "mma.sync.aligned.m16n8k16.row.col.f32.bf16.bf16.f32 {h12,h13,h14,h15}, {%19,%20,%21,%22}, {e0,e1}, {fz,fz,fz,fz};\n"
            "or.b32 a0, e0, mt; and.b32 a0, a0, %5;\n"
            "add.u32 xa, xa, 2048; add.u32 aa, aa, 2560; mov.u32 st, 1;\n"
            "mov.u32 cnt, 0; and.b32 tmp, aa, 0xffffff80;\n"
            "S1L: mbarrier.try_wait.parity.shared::cta.b64 pw, [tmp+520], 0; @pw bra.uni S1D;\n"
            "add.u32 cnt, cnt, 1; setp.lt.u32 pk, cnt, 1000000; @pk bra.uni S1L; trap;\n"
            "S1D:\n"
            "B0_0:\n"
            "xor.b32 tmp, mt, %3; and.b32 tmp, tmp, 1536; setp.eq.u32 pm, tmp, 0; selp.b32 ab, aa, %3, pm;\n"
            "and.b32 tmp, mt, 2048; setp.ne.u32 d0, tmp, 0; and.b32 tmp, mt, 4096; setp.ne.u32 d1, tmp, 0; and.b32 tmp, mt, 8192; setp.ne.u32 d2, tmp, 0;\n"
            "mad.lo.u32 cnt, a0, %5, ea; mad.lo.s32 ea, st, 2560, ea;\n"
            "ld.shared.u32 mt, [aa+512];\n"
            "mma.sync.aligned.m16n8k16.row.col.f32.bf16.bf16.f32 {c0,c1,c2,c3}, {a0,a1,a2,a3}, {x0,x1}, {c0,c1,c2,c3};\n"
            "mma.sync.aligned.m16n8k16.row.col.f32.bf16.bf16.f32 {c4,c5,c6,c7}, {a0,a1,a2,a3}, {x2,x3}, {c4,c5,c6,c7};\n"
            "ld.shared.v4.u32 {x0,x1,x2,x3}, [xa+0];\n"
            "tanh.approx.f32 th0, h0;\n"
            "tanh.approx.f32 th1, h2;\n"
            "fma.rn.f32 th0, h0, th0, h0;\n"
            "fma.rn.f32 th1, h2, th1, h2;\n"
            "cvt.rn.bf16x2.f32 r0, th1, th0;\n"
            "mma.sync.aligned.m16n8k16.row.col.f32.bf16.bf16.f32 {c8,c9,c10,c11}, {a0,a1,a2,a3}, {x4,x5}, {c8,c9,c10,c11};\n"
            "mma.sync.aligned.m16n8k16.row.col.f32.bf16.bf16.f32 {c12,c13,c14,c15}, {a0,a1,a2,a3}, {x6,x7}, {c12,c13,c14,c15};\n"
            "ld.shared.v4.u32 {x4,x5,x6,x7}, [xa+128];\n"
            "tanh.approx.f32 th2, h4;\n"
            "tanh.approx.f32 th3, h6;\n"
            "fma.rn.f32 th2, h4, th2, h4;\n"
            "fma.rn.f32 th3, h6, th3, h6;\n"
            "cvt.rn.bf16x2.f32 r1, th3, th2;\n"
            "mma.sync.aligned.m16n8k16.row.col.f32.bf16.bf16.f32 {c16,c17,c18,c19}, {a0,a1,a2,a3}, {x8,x9}, {c16,c17,c18,c19};\n"
            "mma.sync.aligned.m16n8k16.row.col.f32.bf16.bf16.f32 {c20,c21,c22,c23}, {a0,a1,a2,a3}, {x10,x11}, {c20,c21,c22,c23};\n"
            "ld.shared.v4.u32 {x8,x9,x10,x11}, [xa+512];\n"
            "tanh.approx.f32 th4, h8;\n"
            "tanh.approx.f32 th5, h10;\n"
            "fma.rn.f32 th4, h8, th4, h8;\n"
            "fma.rn.f32 th5, h10, th5, h10;\n"
            "cvt.rn.bf16x2.f32 r2, th5, th4;\n"
            "mma.sync.aligned.m16n8k16.row.col.f32.bf16.bf16.f32 {c24,c25,c26,c27}, {a0,a1,a2,a3}, {x12,x13}, {c24,c25,c26,c27};\n"
            "mma.sync.aligned.m16n8k16.row.col.f32.bf16.bf16.f32 {c28,c29,c30,c31}, {a0,a1,a2,a3}, {x14,x15}, {c28,c29,c30,c31};\n"
            "ld.shared.v4.u32 {x12,x13,x14,x15}, [xa+640];\n"
            "tanh.approx.f32 th6, h12;\n"
            "tanh.approx.f32 th7, h14;\n"
            "fma.rn.f32 th6, h12, th6, h12;\n"
            "fma.rn.f32 th7, h14, th7, h14;\n"
            "cvt.rn.bf16x2.f32 r3, th7, th6;\n"
            "ld.shared.v4.u32 {a0,a1,a2,a3}, [ab+0];\n"
            "@pe mbarrier.arrive.shared::cta.b64 _, [cnt+280];\n"
            "mov.b32 {lo,hi}, r0; mov.b32 rl, {lo,lo}; mov.b32 rh, {hi,hi};\n"
            "mul.bf16x2 x0, x0, rl; mul.bf16x2 x1, x1, rl; mul.bf16x2 x2, x2, rh; mul.bf16x2 x3, x3, rh;\n"
            "mov.b32 {lo,hi}, r1; mov.b32 rl, {lo,lo}; mov.b32 rh, {hi,hi};\n"
            "mul.bf16x2 x4, x4, rl; mul.bf16x2 x5, x5, rl; mul.bf16x2 x6, x6, rh; mul.bf16x2 x7, x7, rh;\n"
            "mov.b32 {lo,hi}, r2; mov.b32 rl, {lo,lo}; mov.b32 rh, {hi,hi};\n"
            "mul.bf16x2 x8, x8, rl; mul.bf16x2 x9, x9, rl; mul.bf16x2 x10, x10, rh; mul.bf16x2 x11, x11, rh;\n"
            "mov.b32 {lo,hi}, r3; mov.b32 rl, {lo,lo}; mov.b32 rh, {hi,hi};\n"
            "mul.bf16x2 x12, x12, rl; mul.bf16x2 x13, x13, rl; mul.bf16x2 x14, x14, rh; mul.bf16x2 x15, x15, rh;\n"
            "@d1 bra.uni L1; @d2 bra.uni B1_4; @d0 bra.uni B1_1; bra.uni B1_0;\n"
            "B0_1:\n"
            "xor.b32 tmp, mt, %3; and.b32 tmp, tmp, 1536; setp.eq.u32 pm, tmp, 0; selp.b32 ab, aa, %3, pm;\n"
            "and.b32 tmp, mt, 2048; setp.ne.u32 d0, tmp, 0; and.b32 tmp, mt, 4096; setp.ne.u32 d1, tmp, 0; and.b32 tmp, mt, 8192; setp.ne.u32 d2, tmp, 0;\n"
            "mad.lo.u32 cnt, a0, %5, ea; mad.lo.s32 ea, st, 2560, ea;\n"
            "ld.shared.u32 mt, [aa+512];\n"
            "mma.sync.aligned.m16n8k16.row.col.f32.bf16.bf16.f32 {c32,c33,c34,c35}, {a0,a1,a2,a3}, {x0,x1}, {c32,c33,c34,c35};\n"
            "mma.sync.aligned.m16n8k16.row.col.f32.bf16.bf16.f32 {c36,c37,c38,c39}, {a0,a1,a2,a3}, {x2,x3}, {c36,c37,c38,c39};\n"
            "ld.shared.v4.u32 {x0,x1,x2,x3}, [xa+0];\n"
            "tanh.approx.f32 th0, h0;\n"
            "tanh.approx.f32 th1, h2;\n"
            "fma.rn.f32 th0, h0, th0, h0;\n"
            "fma.rn.f32 th1, h2, th1, h2;\n"
            "cvt.rn.bf16x2.f32 r0, th1, th0;\n"
            "mma.sync.aligned.m16n8k16.row.col.f32.bf16.bf16.f32 {c40,c41,c42,c43}, {a0,a1,a2,a3}, {x4,x5}, {c40,c41,c42,c43};\n"
            "mma.sync.aligned.m16n8k16.row.col.f32.bf16.bf16.f32 {c44,c45,c46,c47}, {a0,a1,a2,a3}, {x6,x7}, {c44,c45,c46,c47};\n"
            "ld.shared.v4.u32 {x4,x5,x6,x7}, [xa+128];\n"
            "tanh.approx.f32 th2, h4;\n"
            "tanh.approx.f32 th3, h6;\n"
            "fma.rn.f32 th2, h4, th2, h4;\n"
            "fma.rn.f32 th3, h6, th3, h6;\n"
            "cvt.rn.bf16x2.f32 r1, th3, th2;\n"
            "mma.sync.aligned.m16n8k16.row.col.f32.bf16.bf16.f32 {c48,c49,c50,c51}, {a0,a1,a2,a3}, {x8,x9}, {c48,c49,c50,c51};\n"
            "mma.sync.aligned.m16n8k16.row.col.f32.bf16.bf16.f32 {c52,c53,c54,c55}, {a0,a1,a2,a3}, {x10,x11}, {c52,c53,c54,c55};\n"
            "ld.shared.v4.u32 {x8,x9,x10,x11}, [xa+512];\n"
            "tanh.approx.f32 th4, h8;\n"
            "tanh.approx.f32 th5, h10;\n"
            "fma.rn.f32 th4, h8, th4, h8;\n"
            "fma.rn.f32 th5, h10, th5, h10;\n"
            "cvt.rn.bf16x2.f32 r2, th5, th4;\n"
            "mma.sync.aligned.m16n8k16.row.col.f32.bf16.bf16.f32 {c56,c57,c58,c59}, {a0,a1,a2,a3}, {x12,x13}, {c56,c57,c58,c59};\n"
            "mma.sync.aligned.m16n8k16.row.col.f32.bf16.bf16.f32 {c60,c61,c62,c63}, {a0,a1,a2,a3}, {x14,x15}, {c60,c61,c62,c63};\n"
            "ld.shared.v4.u32 {x12,x13,x14,x15}, [xa+640];\n"
            "tanh.approx.f32 th6, h12;\n"
            "tanh.approx.f32 th7, h14;\n"
            "fma.rn.f32 th6, h12, th6, h12;\n"
            "fma.rn.f32 th7, h14, th7, h14;\n"
            "cvt.rn.bf16x2.f32 r3, th7, th6;\n"
            "ld.shared.v4.u32 {a0,a1,a2,a3}, [ab+0];\n"
            "@pe mbarrier.arrive.shared::cta.b64 _, [cnt+280];\n"
            "mov.b32 {lo,hi}, r0; mov.b32 rl, {lo,lo}; mov.b32 rh, {hi,hi};\n"
            "mul.bf16x2 x0, x0, rl; mul.bf16x2 x1, x1, rl; mul.bf16x2 x2, x2, rh; mul.bf16x2 x3, x3, rh;\n"
            "mov.b32 {lo,hi}, r1; mov.b32 rl, {lo,lo}; mov.b32 rh, {hi,hi};\n"
            "mul.bf16x2 x4, x4, rl; mul.bf16x2 x5, x5, rl; mul.bf16x2 x6, x6, rh; mul.bf16x2 x7, x7, rh;\n"
            "mov.b32 {lo,hi}, r2; mov.b32 rl, {lo,lo}; mov.b32 rh, {hi,hi};\n"
            "mul.bf16x2 x8, x8, rl; mul.bf16x2 x9, x9, rl; mul.bf16x2 x10, x10, rh; mul.bf16x2 x11, x11, rh;\n"
            "mov.b32 {lo,hi}, r3; mov.b32 rl, {lo,lo}; mov.b32 rh, {hi,hi};\n"
            "mul.bf16x2 x12, x12, rl; mul.bf16x2 x13, x13, rl; mul.bf16x2 x14, x14, rh; mul.bf16x2 x15, x15, rh;\n"
            "@d1 bra.uni L1; @d2 bra.uni B1_4; @d0 bra.uni B1_1; bra.uni B1_0;\n"
            "L0: @d0 bra.uni B0_3;\n"
            "B0_2:\n"
            "xor.b32 tmp, mt, %3; and.b32 tmp, tmp, 1536; setp.eq.u32 pm, tmp, 0; selp.b32 ab, aa, %3, pm;\n"
            "and.b32 tmp, mt, 2048; setp.ne.u32 d0, tmp, 0; and.b32 tmp, mt, 4096; setp.ne.u32 d1, tmp, 0; and.b32 tmp, mt, 8192; setp.ne.u32 d2, tmp, 0;\n"
            "mad.lo.u32 cnt, a0, %5, ea; mad.lo.s32 ea, st, 2560, ea;\n"
            "ld.shared.u32 mt, [aa+512];\n"
            "mma.sync.aligned.m16n8k16.row.col.f32.bf16.bf16.f32 {c64,c65,c66,c67}, {a0,a1,a2,a3}, {x0,x1}, {c64,c65,c66,c67};\n"
            "mma.sync.aligned.m16n8k16.row.col.f32.bf16.bf16.f32 {c68,c69,c70,c71}, {a0,a1,a2,a3}, {x2,x3}, {c68,c69,c70,c71};\n"
            "ld.shared.v4.u32 {x0,x1,x2,x3}, [xa+0];\n"
            "tanh.approx.f32 th0, h0;\n"
            "tanh.approx.f32 th1, h2;\n"
            "fma.rn.f32 th0, h0, th0, h0;\n"
            "fma.rn.f32 th1, h2, th1, h2;\n"
            "cvt.rn.bf16x2.f32 r0, th1, th0;\n"
            "mma.sync.aligned.m16n8k16.row.col.f32.bf16.bf16.f32 {c72,c73,c74,c75}, {a0,a1,a2,a3}, {x4,x5}, {c72,c73,c74,c75};\n"
            "mma.sync.aligned.m16n8k16.row.col.f32.bf16.bf16.f32 {c76,c77,c78,c79}, {a0,a1,a2,a3}, {x6,x7}, {c76,c77,c78,c79};\n"
            "ld.shared.v4.u32 {x4,x5,x6,x7}, [xa+128];\n"
            "tanh.approx.f32 th2, h4;\n"
            "tanh.approx.f32 th3, h6;\n"
            "fma.rn.f32 th2, h4, th2, h4;\n"
            "fma.rn.f32 th3, h6, th3, h6;\n"
            "cvt.rn.bf16x2.f32 r1, th3, th2;\n"
            "mma.sync.aligned.m16n8k16.row.col.f32.bf16.bf16.f32 {c80,c81,c82,c83}, {a0,a1,a2,a3}, {x8,x9}, {c80,c81,c82,c83};\n"
            "mma.sync.aligned.m16n8k16.row.col.f32.bf16.bf16.f32 {c84,c85,c86,c87}, {a0,a1,a2,a3}, {x10,x11}, {c84,c85,c86,c87};\n"
            "ld.shared.v4.u32 {x8,x9,x10,x11}, [xa+512];\n"
            "tanh.approx.f32 th4, h8;\n"
            "tanh.approx.f32 th5, h10;\n"
            "fma.rn.f32 th4, h8, th4, h8;\n"
            "fma.rn.f32 th5, h10, th5, h10;\n"
            "cvt.rn.bf16x2.f32 r2, th5, th4;\n"
            "mma.sync.aligned.m16n8k16.row.col.f32.bf16.bf16.f32 {c88,c89,c90,c91}, {a0,a1,a2,a3}, {x12,x13}, {c88,c89,c90,c91};\n"
            "mma.sync.aligned.m16n8k16.row.col.f32.bf16.bf16.f32 {c92,c93,c94,c95}, {a0,a1,a2,a3}, {x14,x15}, {c92,c93,c94,c95};\n"
            "ld.shared.v4.u32 {x12,x13,x14,x15}, [xa+640];\n"
            "tanh.approx.f32 th6, h12;\n"
            "tanh.approx.f32 th7, h14;\n"
            "fma.rn.f32 th6, h12, th6, h12;\n"
            "fma.rn.f32 th7, h14, th7, h14;\n"
            "cvt.rn.bf16x2.f32 r3, th7, th6;\n"
            "ld.shared.v4.u32 {a0,a1,a2,a3}, [ab+0];\n"
            "@pe mbarrier.arrive.shared::cta.b64 _, [cnt+280];\n"
            "mov.b32 {lo,hi}, r0; mov.b32 rl, {lo,lo}; mov.b32 rh, {hi,hi};\n"
            "mul.bf16x2 x0, x0, rl; mul.bf16x2 x1, x1, rl; mul.bf16x2 x2, x2, rh; mul.bf16x2 x3, x3, rh;\n"
            "mov.b32 {lo,hi}, r1; mov.b32 rl, {lo,lo}; mov.b32 rh, {hi,hi};\n"
            "mul.bf16x2 x4, x4, rl; mul.bf16x2 x5, x5, rl; mul.bf16x2 x6, x6, rh; mul.bf16x2 x7, x7, rh;\n"
            "mov.b32 {lo,hi}, r2; mov.b32 rl, {lo,lo}; mov.b32 rh, {hi,hi};\n"
            "mul.bf16x2 x8, x8, rl; mul.bf16x2 x9, x9, rl; mul.bf16x2 x10, x10, rh; mul.bf16x2 x11, x11, rh;\n"
            "mov.b32 {lo,hi}, r3; mov.b32 rl, {lo,lo}; mov.b32 rh, {hi,hi};\n"
            "mul.bf16x2 x12, x12, rl; mul.bf16x2 x13, x13, rl; mul.bf16x2 x14, x14, rh; mul.bf16x2 x15, x15, rh;\n"
            "@d1 bra.uni L1; @d2 bra.uni B1_4; @d0 bra.uni B1_1; bra.uni B1_0;\n"
            "B0_3:\n"
            "xor.b32 tmp, mt, %3; and.b32 tmp, tmp, 1536; setp.eq.u32 pm, tmp, 0; selp.b32 ab, aa, %3, pm;\n"
            "and.b32 tmp, mt, 2048; setp.ne.u32 d0, tmp, 0; and.b32 tmp, mt, 4096; setp.ne.u32 d1, tmp, 0; and.b32 tmp, mt, 8192; setp.ne.u32 d2, tmp, 0;\n"
            "mad.lo.u32 cnt, a0, %5, ea; mad.lo.s32 ea, st, 2560, ea;\n"
            "ld.shared.u32 mt, [aa+512];\n"
            "mma.sync.aligned.m16n8k16.row.col.f32.bf16.bf16.f32 {c96,c97,c98,c99}, {a0,a1,a2,a3}, {x0,x1}, {c96,c97,c98,c99};\n"
            "mma.sync.aligned.m16n8k16.row.col.f32.bf16.bf16.f32 {c100,c101,c102,c103}, {a0,a1,a2,a3}, {x2,x3}, {c100,c101,c102,c103};\n"
            "ld.shared.v4.u32 {x0,x1,x2,x3}, [xa+0];\n"
            "tanh.approx.f32 th0, h0;\n"
            "tanh.approx.f32 th1, h2;\n"
            "fma.rn.f32 th0, h0, th0, h0;\n"
            "fma.rn.f32 th1, h2, th1, h2;\n"
            "cvt.rn.bf16x2.f32 r0, th1, th0;\n"
            "mma.sync.aligned.m16n8k16.row.col.f32.bf16.bf16.f32 {c104,c105,c106,c107}, {a0,a1,a2,a3}, {x4,x5}, {c104,c105,c106,c107};\n"
            "mma.sync.aligned.m16n8k16.row.col.f32.bf16.bf16.f32 {c108,c109,c110,c111}, {a0,a1,a2,a3}, {x6,x7}, {c108,c109,c110,c111};\n"
            "ld.shared.v4.u32 {x4,x5,x6,x7}, [xa+128];\n"
            "tanh.approx.f32 th2, h4;\n"
            "tanh.approx.f32 th3, h6;\n"
            "fma.rn.f32 th2, h4, th2, h4;\n"
            "fma.rn.f32 th3, h6, th3, h6;\n"
            "cvt.rn.bf16x2.f32 r1, th3, th2;\n"
            "mma.sync.aligned.m16n8k16.row.col.f32.bf16.bf16.f32 {c112,c113,c114,c115}, {a0,a1,a2,a3}, {x8,x9}, {c112,c113,c114,c115};\n"
            "mma.sync.aligned.m16n8k16.row.col.f32.bf16.bf16.f32 {c116,c117,c118,c119}, {a0,a1,a2,a3}, {x10,x11}, {c116,c117,c118,c119};\n"
            "ld.shared.v4.u32 {x8,x9,x10,x11}, [xa+512];\n"
            "tanh.approx.f32 th4, h8;\n"
            "tanh.approx.f32 th5, h10;\n"
            "fma.rn.f32 th4, h8, th4, h8;\n"
            "fma.rn.f32 th5, h10, th5, h10;\n"
            "cvt.rn.bf16x2.f32 r2, th5, th4;\n"
            "mma.sync.aligned.m16n8k16.row.col.f32.bf16.bf16.f32 {c120,c121,c122,c123}, {a0,a1,a2,a3}, {x12,x13}, {c120,c121,c122,c123};\n"
            "mma.sync.aligned.m16n8k16.row.col.f32.bf16.bf16.f32 {c124,c125,c126,c127}, {a0,a1,a2,a3}, {x14,x15}, {c124,c125,c126,c127};\n"
            "ld.shared.v4.u32 {x12,x13,x14,x15}, [xa+640];\n"
            "tanh.approx.f32 th6, h12;\n"
            "tanh.approx.f32 th7, h14;\n"
            "fma.rn.f32 th6, h12, th6, h12;\n"
            "fma.rn.f32 th7, h14, th7, h14;\n"
            "cvt.rn.bf16x2.f32 r3, th7, th6;\n"
            "ld.shared.v4.u32 {a0,a1,a2,a3}, [ab+0];\n"
            "@pe mbarrier.arrive.shared::cta.b64 _, [cnt+280];\n"
            "mov.b32 {lo,hi}, r0; mov.b32 rl, {lo,lo}; mov.b32 rh, {hi,hi};\n"
            "mul.bf16x2 x0, x0, rl; mul.bf16x2 x1, x1, rl; mul.bf16x2 x2, x2, rh; mul.bf16x2 x3, x3, rh;\n"
            "mov.b32 {lo,hi}, r1; mov.b32 rl, {lo,lo}; mov.b32 rh, {hi,hi};\n"
            "mul.bf16x2 x4, x4, rl; mul.bf16x2 x5, x5, rl; mul.bf16x2 x6, x6, rh; mul.bf16x2 x7, x7, rh;\n"
            "mov.b32 {lo,hi}, r2; mov.b32 rl, {lo,lo}; mov.b32 rh, {hi,hi};\n"
            "mul.bf16x2 x8, x8, rl; mul.bf16x2 x9, x9, rl; mul.bf16x2 x10, x10, rh; mul.bf16x2 x11, x11, rh;\n"
            "mov.b32 {lo,hi}, r3; mov.b32 rl, {lo,lo}; mov.b32 rh, {hi,hi};\n"
            "mul.bf16x2 x12, x12, rl; mul.bf16x2 x13, x13, rl; mul.bf16x2 x14, x14, rh; mul.bf16x2 x15, x15, rh;\n"
            "@d1 bra.uni L1; @d2 bra.uni B1_4; @d0 bra.uni B1_1; bra.uni B1_0;\n"
            "B0_4:\n"
            "xor.b32 tmp, mt, %3; and.b32 tmp, tmp, 1536; setp.eq.u32 pm, tmp, 0; selp.b32 ab, aa, %3, pm;\n"
            "and.b32 tmp, mt, 2048; setp.ne.u32 d0, tmp, 0; and.b32 tmp, mt, 4096; setp.ne.u32 d1, tmp, 0; and.b32 tmp, mt, 8192; setp.ne.u32 d2, tmp, 0;\n"
            "mad.lo.u32 cnt, a0, %5, ea; mad.lo.s32 ea, st, 2560, ea;\n"
            "ld.shared.u32 mt, [aa+512];\n"
            "mma.sync.aligned.m16n8k16.row.col.f32.bf16.bf16.f32 {c128,c129,c130,c131}, {a0,a1,a2,a3}, {x0,x1}, {c128,c129,c130,c131};\n"
            "mma.sync.aligned.m16n8k16.row.col.f32.bf16.bf16.f32 {c132,c133,c134,c135}, {a0,a1,a2,a3}, {x2,x3}, {c132,c133,c134,c135};\n"
            "ld.shared.v4.u32 {x0,x1,x2,x3}, [xa+0];\n"
            "tanh.approx.f32 th0, h0;\n"
            "tanh.approx.f32 th1, h2;\n"
            "fma.rn.f32 th0, h0, th0, h0;\n"
            "fma.rn.f32 th1, h2, th1, h2;\n"
            "cvt.rn.bf16x2.f32 r0, th1, th0;\n"
            "mma.sync.aligned.m16n8k16.row.col.f32.bf16.bf16.f32 {c136,c137,c138,c139}, {a0,a1,a2,a3}, {x4,x5}, {c136,c137,c138,c139};\n"
            "mma.sync.aligned.m16n8k16.row.col.f32.bf16.bf16.f32 {c140,c141,c142,c143}, {a0,a1,a2,a3}, {x6,x7}, {c140,c141,c142,c143};\n"
            "ld.shared.v4.u32 {x4,x5,x6,x7}, [xa+128];\n"
            "tanh.approx.f32 th2, h4;\n"
            "tanh.approx.f32 th3, h6;\n"
            "fma.rn.f32 th2, h4, th2, h4;\n"
            "fma.rn.f32 th3, h6, th3, h6;\n"
            "cvt.rn.bf16x2.f32 r1, th3, th2;\n"
            "mma.sync.aligned.m16n8k16.row.col.f32.bf16.bf16.f32 {c144,c145,c146,c147}, {a0,a1,a2,a3}, {x8,x9}, {c144,c145,c146,c147};\n"
            "mma.sync.aligned.m16n8k16.row.col.f32.bf16.bf16.f32 {c148,c149,c150,c151}, {a0,a1,a2,a3}, {x10,x11}, {c148,c149,c150,c151};\n"
            "ld.shared.v4.u32 {x8,x9,x10,x11}, [xa+512];\n"
            "tanh.approx.f32 th4, h8;\n"
            "tanh.approx.f32 th5, h10;\n"
            "fma.rn.f32 th4, h8, th4, h8;\n"
            "fma.rn.f32 th5, h10, th5, h10;\n"
            "cvt.rn.bf16x2.f32 r2, th5, th4;\n"
            "mma.sync.aligned.m16n8k16.row.col.f32.bf16.bf16.f32 {c152,c153,c154,c155}, {a0,a1,a2,a3}, {x12,x13}, {c152,c153,c154,c155};\n"
            "mma.sync.aligned.m16n8k16.row.col.f32.bf16.bf16.f32 {c156,c157,c158,c159}, {a0,a1,a2,a3}, {x14,x15}, {c156,c157,c158,c159};\n"
            "ld.shared.v4.u32 {x12,x13,x14,x15}, [xa+640];\n"
            "tanh.approx.f32 th6, h12;\n"
            "tanh.approx.f32 th7, h14;\n"
            "fma.rn.f32 th6, h12, th6, h12;\n"
            "fma.rn.f32 th7, h14, th7, h14;\n"
            "cvt.rn.bf16x2.f32 r3, th7, th6;\n"
            "ld.shared.v4.u32 {a0,a1,a2,a3}, [ab+0];\n"
            "@pe mbarrier.arrive.shared::cta.b64 _, [cnt+280];\n"
            "mov.b32 {lo,hi}, r0; mov.b32 rl, {lo,lo}; mov.b32 rh, {hi,hi};\n"
            "mul.bf16x2 x0, x0, rl; mul.bf16x2 x1, x1, rl; mul.bf16x2 x2, x2, rh; mul.bf16x2 x3, x3, rh;\n"
            "mov.b32 {lo,hi}, r1; mov.b32 rl, {lo,lo}; mov.b32 rh, {hi,hi};\n"
            "mul.bf16x2 x4, x4, rl; mul.bf16x2 x5, x5, rl; mul.bf16x2 x6, x6, rh; mul.bf16x2 x7, x7, rh;\n"
            "mov.b32 {lo,hi}, r2; mov.b32 rl, {lo,lo}; mov.b32 rh, {hi,hi};\n"
            "mul.bf16x2 x8, x8, rl; mul.bf16x2 x9, x9, rl; mul.bf16x2 x10, x10, rh; mul.bf16x2 x11, x11, rh;\n"
            "mov.b32 {lo,hi}, r3; mov.b32 rl, {lo,lo}; mov.b32 rh, {hi,hi};\n"
            "mul.bf16x2 x12, x12, rl; mul.bf16x2 x13, x13, rl; mul.bf16x2 x14, x14, rh; mul.bf16x2 x15, x15, rh;\n"
            "@d1 bra.uni L1; @d2 bra.uni B1_4; @d0 bra.uni B1_1; bra.uni B1_0;\n"
            "B1_0:\n"
            "xor.b32 tmp, mt, ea; and.b32 tmp, tmp, 192; setp.eq.u32 pm, tmp, 0; selp.b32 ab, aa, %3, pm;\n"
            "and.b32 tmp, mt, 8; setp.ne.u32 d0, tmp, 0; and.b32 tmp, mt, 16; setp.ne.u32 d1, tmp, 0; and.b32 tmp, mt, 32; setp.ne.u32 d2, tmp, 0;\n"
            "ld.shared.v2.u32 {e0,e1}, [ea];\n"
            "shr.s32 st, mt, 24; mad.lo.s32 aa, st, 2560, aa;\n"
            "mma.sync.aligned.m16n8k16.row.col.f32.bf16.bf16.f32 {c0,c1,c2,c3}, {a0,a1,a2,a3}, {x0,x1}, {c0,c1,c2,c3};\n"
            "mma.sync.aligned.m16n8k16.row.col.f32.bf16.bf16.f32 {c4,c5,c6,c7}, {a0,a1,a2,a3}, {x2,x3}, {c4,c5,c6,c7};\n"
            "ld.shared.v4.u32 {x0,x1,x2,x3}, [xa+1024];\n"
            "tanh.approx.f32 th0, h1;\n"
            "tanh.approx.f32 th1, h3;\n"
            "fma.rn.f32 th0, h1, th0, h1;\n"
            "fma.rn.f32 th1, h3, th1, h3;\n"
            "cvt.rn.bf16x2.f32 r0, th1, th0;\n"
            "mma.sync.aligned.m16n8k16.row.col.f32.bf16.bf16.f32 {h0,h1,h2,h3}, {%7,%8,%9,%10}, {e0,e1}, {fz,fz,fz,fz};\n"
            "mma.sync.aligned.m16n8k16.row.col.f32.bf16.bf16.f32 {c8,c9,c10,c11}, {a0,a1,a2,a3}, {x4,x5}, {c8,c9,c10,c11};\n"
            "mma.sync.aligned.m16n8k16.row.col.f32.bf16.bf16.f32 {c12,c13,c14,c15}, {a0,a1,a2,a3}, {x6,x7}, {c12,c13,c14,c15};\n"
            "ld.shared.v4.u32 {x4,x5,x6,x7}, [xa+1152];\n"
            "tanh.approx.f32 th2, h5;\n"
            "tanh.approx.f32 th3, h7;\n"
            "fma.rn.f32 th2, h5, th2, h5;\n"
            "fma.rn.f32 th3, h7, th3, h7;\n"
            "cvt.rn.bf16x2.f32 r1, th3, th2;\n"
            "mma.sync.aligned.m16n8k16.row.col.f32.bf16.bf16.f32 {h4,h5,h6,h7}, {%11,%12,%13,%14}, {e0,e1}, {fz,fz,fz,fz};\n"
            "mma.sync.aligned.m16n8k16.row.col.f32.bf16.bf16.f32 {c16,c17,c18,c19}, {a0,a1,a2,a3}, {x8,x9}, {c16,c17,c18,c19};\n"
            "mma.sync.aligned.m16n8k16.row.col.f32.bf16.bf16.f32 {c20,c21,c22,c23}, {a0,a1,a2,a3}, {x10,x11}, {c20,c21,c22,c23};\n"
            "ld.shared.v4.u32 {x8,x9,x10,x11}, [xa+1536];\n"
            "tanh.approx.f32 th4, h9;\n"
            "tanh.approx.f32 th5, h11;\n"
            "fma.rn.f32 th4, h9, th4, h9;\n"
            "fma.rn.f32 th5, h11, th5, h11;\n"
            "cvt.rn.bf16x2.f32 r2, th5, th4;\n"
            "mma.sync.aligned.m16n8k16.row.col.f32.bf16.bf16.f32 {h8,h9,h10,h11}, {%15,%16,%17,%18}, {e0,e1}, {fz,fz,fz,fz};\n"
            "mma.sync.aligned.m16n8k16.row.col.f32.bf16.bf16.f32 {c24,c25,c26,c27}, {a0,a1,a2,a3}, {x12,x13}, {c24,c25,c26,c27};\n"
            "mma.sync.aligned.m16n8k16.row.col.f32.bf16.bf16.f32 {c28,c29,c30,c31}, {a0,a1,a2,a3}, {x14,x15}, {c28,c29,c30,c31};\n"
            "ld.shared.v4.u32 {x12,x13,x14,x15}, [xa+1664];\n"
            "tanh.approx.f32 th6, h13;\n"
            "tanh.approx.f32 th7, h15;\n"
            "fma.rn.f32 th6, h13, th6, h13;\n"
            "fma.rn.f32 th7, h15, th7, h15;\n"
            "cvt.rn.bf16x2.f32 r3, th7, th6;\n"
            "mma.sync.aligned.m16n8k16.row.col.f32.bf16.bf16.f32 {h12,h13,h14,h15}, {%19,%20,%21,%22}, {e0,e1}, {fz,fz,fz,fz};\n"
            "ld.shared.v4.u32 {a0,a1,a2,a3}, [ab+128];\n"
            "and.b32 tmp, aa, 0xffffff80; mbarrier.test_wait.parity.shared::cta.b64 pw, [tmp+520], mt;\n"
            "mad.lo.s32 xa, st, 2048, xa;\n"
            "mov.b32 {lo,hi}, r0; mov.b32 rl, {lo,lo}; mov.b32 rh, {hi,hi};\n"
            "mul.bf16x2 x0, x0, rl; mul.bf16x2 x1, x1, rl; mul.bf16x2 x2, x2, rh; mul.bf16x2 x3, x3, rh;\n"
            "mov.b32 {lo,hi}, r1; mov.b32 rl, {lo,lo}; mov.b32 rh, {hi,hi};\n"
            "mul.bf16x2 x4, x4, rl; mul.bf16x2 x5, x5, rl; mul.bf16x2 x6, x6, rh; mul.bf16x2 x7, x7, rh;\n"
            "mov.b32 {lo,hi}, r2; mov.b32 rl, {lo,lo}; mov.b32 rh, {hi,hi};\n"
            "mul.bf16x2 x8, x8, rl; mul.bf16x2 x9, x9, rl; mul.bf16x2 x10, x10, rh; mul.bf16x2 x11, x11, rh;\n"
            "mov.b32 {lo,hi}, r3; mov.b32 rl, {lo,lo}; mov.b32 rh, {hi,hi};\n"
            "mul.bf16x2 x12, x12, rl; mul.bf16x2 x13, x13, rl; mul.bf16x2 x14, x14, rh; mul.bf16x2 x15, x15, rh;\n"
            "@!pw bra.uni W1;\n"
            "@d2 bra.uni B0_4; @d1 bra.uni L0; @d0 bra.uni B0_1; bra.uni B0_0;\n"
            "B1_1:\n"
            "xor.b32 tmp, mt, ea; and.b32 tmp, tmp, 192; setp.eq.u32 pm, tmp, 0; selp.b32 ab, aa, %3, pm;\n"
            "and.b32 tmp, mt, 8; setp.ne.u32 d0, tmp, 0; and.b32 tmp, mt, 16; setp.ne.u32 d1, tmp, 0; and.b32 tmp, mt, 32; setp.ne.u32 d2, tmp, 0;\n"
            "ld.shared.v2.u32 {e0,e1}, [ea];\n"
            "shr.s32 st, mt, 24; mad.lo.s32 aa, st, 2560, aa;\n"
            "mma.sync.aligned.m16n8k16.row.col.f32.bf16.bf16.f32 {c32,c33,c34,c35}, {a0,a1,a2,a3}, {x0,x1}, {c32,c33,c34,c35};\n"
            "mma.sync.aligned.m16n8k16.row.col.f32.bf16.bf16.f32 {c36,c37,c38,c39}, {a0,a1,a2,a3}, {x2,x3}, {c36,c37,c38,c39};\n"
            "ld.shared.v4.u32 {x0,x1,x2,x3}, [xa+1024];\n"
            "tanh.approx.f32 th0, h1;\n"
            "tanh.approx.f32 th1, h3;\n"
            "fma.rn.f32 th0, h1, th0, h1;\n"
            "fma.rn.f32 th1, h3, th1, h3;\n"
            "cvt.rn.bf16x2.f32 r0, th1, th0;\n"
            "mma.sync.aligned.m16n8k16.row.col.f32.bf16.bf16.f32 {h0,h1,h2,h3}, {%7,%8,%9,%10}, {e0,e1}, {fz,fz,fz,fz};\n"
            "mma.sync.aligned.m16n8k16.row.col.f32.bf16.bf16.f32 {c40,c41,c42,c43}, {a0,a1,a2,a3}, {x4,x5}, {c40,c41,c42,c43};\n"
            "mma.sync.aligned.m16n8k16.row.col.f32.bf16.bf16.f32 {c44,c45,c46,c47}, {a0,a1,a2,a3}, {x6,x7}, {c44,c45,c46,c47};\n"
            "ld.shared.v4.u32 {x4,x5,x6,x7}, [xa+1152];\n"
            "tanh.approx.f32 th2, h5;\n"
            "tanh.approx.f32 th3, h7;\n"
            "fma.rn.f32 th2, h5, th2, h5;\n"
            "fma.rn.f32 th3, h7, th3, h7;\n"
            "cvt.rn.bf16x2.f32 r1, th3, th2;\n"
            "mma.sync.aligned.m16n8k16.row.col.f32.bf16.bf16.f32 {h4,h5,h6,h7}, {%11,%12,%13,%14}, {e0,e1}, {fz,fz,fz,fz};\n"
            "mma.sync.aligned.m16n8k16.row.col.f32.bf16.bf16.f32 {c48,c49,c50,c51}, {a0,a1,a2,a3}, {x8,x9}, {c48,c49,c50,c51};\n"
            "mma.sync.aligned.m16n8k16.row.col.f32.bf16.bf16.f32 {c52,c53,c54,c55}, {a0,a1,a2,a3}, {x10,x11}, {c52,c53,c54,c55};\n"
            "ld.shared.v4.u32 {x8,x9,x10,x11}, [xa+1536];\n"
            "tanh.approx.f32 th4, h9;\n"
            "tanh.approx.f32 th5, h11;\n"
            "fma.rn.f32 th4, h9, th4, h9;\n"
            "fma.rn.f32 th5, h11, th5, h11;\n"
            "cvt.rn.bf16x2.f32 r2, th5, th4;\n"
            "mma.sync.aligned.m16n8k16.row.col.f32.bf16.bf16.f32 {h8,h9,h10,h11}, {%15,%16,%17,%18}, {e0,e1}, {fz,fz,fz,fz};\n"
            "mma.sync.aligned.m16n8k16.row.col.f32.bf16.bf16.f32 {c56,c57,c58,c59}, {a0,a1,a2,a3}, {x12,x13}, {c56,c57,c58,c59};\n"
            "mma.sync.aligned.m16n8k16.row.col.f32.bf16.bf16.f32 {c60,c61,c62,c63}, {a0,a1,a2,a3}, {x14,x15}, {c60,c61,c62,c63};\n"
            "ld.shared.v4.u32 {x12,x13,x14,x15}, [xa+1664];\n"
            "tanh.approx.f32 th6, h13;\n"
            "tanh.approx.f32 th7, h15;\n"
            "fma.rn.f32 th6, h13, th6, h13;\n"
            "fma.rn.f32 th7, h15, th7, h15;\n"
            "cvt.rn.bf16x2.f32 r3, th7, th6;\n"
            "mma.sync.aligned.m16n8k16.row.col.f32.bf16.bf16.f32 {h12,h13,h14,h15}, {%19,%20,%21,%22}, {e0,e1}, {fz,fz,fz,fz};\n"
            "ld.shared.v4.u32 {a0,a1,a2,a3}, [ab+128];\n"
            "and.b32 tmp, aa, 0xffffff80; mbarrier.test_wait.parity.shared::cta.b64 pw, [tmp+520], mt;\n"
            "mad.lo.s32 xa, st, 2048, xa;\n"
            "mov.b32 {lo,hi}, r0; mov.b32 rl, {lo,lo}; mov.b32 rh, {hi,hi};\n"
            "mul.bf16x2 x0, x0, rl; mul.bf16x2 x1, x1, rl; mul.bf16x2 x2, x2, rh; mul.bf16x2 x3, x3, rh;\n"
            "mov.b32 {lo,hi}, r1; mov.b32 rl, {lo,lo}; mov.b32 rh, {hi,hi};\n"
            "mul.bf16x2 x4, x4, rl; mul.bf16x2 x5, x5, rl; mul.bf16x2 x6, x6, rh; mul.bf16x2 x7, x7, rh;\n"
            "mov.b32 {lo,hi}, r2; mov.b32 rl, {lo,lo}; mov.b32 rh, {hi,hi};\n"
            "mul.bf16x2 x8, x8, rl; mul.bf16x2 x9, x9, rl; mul.bf16x2 x10, x10, rh; mul.bf16x2 x11, x11, rh;\n"
            "mov.b32 {lo,hi}, r3; mov.b32 rl, {lo,lo}; mov.b32 rh, {hi,hi};\n"
            "mul.bf16x2 x12, x12, rl; mul.bf16x2 x13, x13, rl; mul.bf16x2 x14, x14, rh; mul.bf16x2 x15, x15, rh;\n"
            "@!pw bra.uni W1;\n"
            "@d2 bra.uni B0_4; @d1 bra.uni L0; @d0 bra.uni B0_1; bra.uni B0_0;\n"
            "L1: @d2 bra.uni END; @d0 bra.uni B1_3;\n"
            "B1_2:\n"
            "xor.b32 tmp, mt, ea; and.b32 tmp, tmp, 192; setp.eq.u32 pm, tmp, 0; selp.b32 ab, aa, %3, pm;\n"
            "and.b32 tmp, mt, 8; setp.ne.u32 d0, tmp, 0; and.b32 tmp, mt, 16; setp.ne.u32 d1, tmp, 0; and.b32 tmp, mt, 32; setp.ne.u32 d2, tmp, 0;\n"
            "ld.shared.v2.u32 {e0,e1}, [ea];\n"
            "shr.s32 st, mt, 24; mad.lo.s32 aa, st, 2560, aa;\n"
            "mma.sync.aligned.m16n8k16.row.col.f32.bf16.bf16.f32 {c64,c65,c66,c67}, {a0,a1,a2,a3}, {x0,x1}, {c64,c65,c66,c67};\n"
            "mma.sync.aligned.m16n8k16.row.col.f32.bf16.bf16.f32 {c68,c69,c70,c71}, {a0,a1,a2,a3}, {x2,x3}, {c68,c69,c70,c71};\n"
            "ld.shared.v4.u32 {x0,x1,x2,x3}, [xa+1024];\n"
            "tanh.approx.f32 th0, h1;\n"
            "tanh.approx.f32 th1, h3;\n"
            "fma.rn.f32 th0, h1, th0, h1;\n"
            "fma.rn.f32 th1, h3, th1, h3;\n"
            "cvt.rn.bf16x2.f32 r0, th1, th0;\n"
            "mma.sync.aligned.m16n8k16.row.col.f32.bf16.bf16.f32 {h0,h1,h2,h3}, {%7,%8,%9,%10}, {e0,e1}, {fz,fz,fz,fz};\n"
            "mma.sync.aligned.m16n8k16.row.col.f32.bf16.bf16.f32 {c72,c73,c74,c75}, {a0,a1,a2,a3}, {x4,x5}, {c72,c73,c74,c75};\n"
            "mma.sync.aligned.m16n8k16.row.col.f32.bf16.bf16.f32 {c76,c77,c78,c79}, {a0,a1,a2,a3}, {x6,x7}, {c76,c77,c78,c79};\n"
            "ld.shared.v4.u32 {x4,x5,x6,x7}, [xa+1152];\n"
            "tanh.approx.f32 th2, h5;\n"
            "tanh.approx.f32 th3, h7;\n"
            "fma.rn.f32 th2, h5, th2, h5;\n"
            "fma.rn.f32 th3, h7, th3, h7;\n"
            "cvt.rn.bf16x2.f32 r1, th3, th2;\n"
            "mma.sync.aligned.m16n8k16.row.col.f32.bf16.bf16.f32 {h4,h5,h6,h7}, {%11,%12,%13,%14}, {e0,e1}, {fz,fz,fz,fz};\n"
            "mma.sync.aligned.m16n8k16.row.col.f32.bf16.bf16.f32 {c80,c81,c82,c83}, {a0,a1,a2,a3}, {x8,x9}, {c80,c81,c82,c83};\n"
            "mma.sync.aligned.m16n8k16.row.col.f32.bf16.bf16.f32 {c84,c85,c86,c87}, {a0,a1,a2,a3}, {x10,x11}, {c84,c85,c86,c87};\n"
            "ld.shared.v4.u32 {x8,x9,x10,x11}, [xa+1536];\n"
            "tanh.approx.f32 th4, h9;\n"
            "tanh.approx.f32 th5, h11;\n"
            "fma.rn.f32 th4, h9, th4, h9;\n"
            "fma.rn.f32 th5, h11, th5, h11;\n"
            "cvt.rn.bf16x2.f32 r2, th5, th4;\n"
            "mma.sync.aligned.m16n8k16.row.col.f32.bf16.bf16.f32 {h8,h9,h10,h11}, {%15,%16,%17,%18}, {e0,e1}, {fz,fz,fz,fz};\n"
            "mma.sync.aligned.m16n8k16.row.col.f32.bf16.bf16.f32 {c88,c89,c90,c91}, {a0,a1,a2,a3}, {x12,x13}, {c88,c89,c90,c91};\n"
            "mma.sync.aligned.m16n8k16.row.col.f32.bf16.bf16.f32 {c92,c93,c94,c95}, {a0,a1,a2,a3}, {x14,x15}, {c92,c93,c94,c95};\n"
            "ld.shared.v4.u32 {x12,x13,x14,x15}, [xa+1664];\n"
            "tanh.approx.f32 th6, h13;\n"
            "tanh.approx.f32 th7, h15;\n"
            "fma.rn.f32 th6, h13, th6, h13;\n"
            "fma.rn.f32 th7, h15, th7, h15;\n"
            "cvt.rn.bf16x2.f32 r3, th7, th6;\n"
            "mma.sync.aligned.m16n8k16.row.col.f32.bf16.bf16.f32 {h12,h13,h14,h15}, {%19,%20,%21,%22}, {e0,e1}, {fz,fz,fz,fz};\n"
            "ld.shared.v4.u32 {a0,a1,a2,a3}, [ab+128];\n"
            "and.b32 tmp, aa, 0xffffff80; mbarrier.test_wait.parity.shared::cta.b64 pw, [tmp+520], mt;\n"
            "mad.lo.s32 xa, st, 2048, xa;\n"
            "mov.b32 {lo,hi}, r0; mov.b32 rl, {lo,lo}; mov.b32 rh, {hi,hi};\n"
            "mul.bf16x2 x0, x0, rl; mul.bf16x2 x1, x1, rl; mul.bf16x2 x2, x2, rh; mul.bf16x2 x3, x3, rh;\n"
            "mov.b32 {lo,hi}, r1; mov.b32 rl, {lo,lo}; mov.b32 rh, {hi,hi};\n"
            "mul.bf16x2 x4, x4, rl; mul.bf16x2 x5, x5, rl; mul.bf16x2 x6, x6, rh; mul.bf16x2 x7, x7, rh;\n"
            "mov.b32 {lo,hi}, r2; mov.b32 rl, {lo,lo}; mov.b32 rh, {hi,hi};\n"
            "mul.bf16x2 x8, x8, rl; mul.bf16x2 x9, x9, rl; mul.bf16x2 x10, x10, rh; mul.bf16x2 x11, x11, rh;\n"
            "mov.b32 {lo,hi}, r3; mov.b32 rl, {lo,lo}; mov.b32 rh, {hi,hi};\n"
            "mul.bf16x2 x12, x12, rl; mul.bf16x2 x13, x13, rl; mul.bf16x2 x14, x14, rh; mul.bf16x2 x15, x15, rh;\n"
            "@!pw bra.uni W1;\n"
            "@d2 bra.uni B0_4; @d1 bra.uni L0; @d0 bra.uni B0_1; bra.uni B0_0;\n"
            "B1_3:\n"
            "xor.b32 tmp, mt, ea; and.b32 tmp, tmp, 192; setp.eq.u32 pm, tmp, 0; selp.b32 ab, aa, %3, pm;\n"
            "and.b32 tmp, mt, 8; setp.ne.u32 d0, tmp, 0; and.b32 tmp, mt, 16; setp.ne.u32 d1, tmp, 0; and.b32 tmp, mt, 32; setp.ne.u32 d2, tmp, 0;\n"
            "ld.shared.v2.u32 {e0,e1}, [ea];\n"
            "shr.s32 st, mt, 24; mad.lo.s32 aa, st, 2560, aa;\n"
            "mma.sync.aligned.m16n8k16.row.col.f32.bf16.bf16.f32 {c96,c97,c98,c99}, {a0,a1,a2,a3}, {x0,x1}, {c96,c97,c98,c99};\n"
            "mma.sync.aligned.m16n8k16.row.col.f32.bf16.bf16.f32 {c100,c101,c102,c103}, {a0,a1,a2,a3}, {x2,x3}, {c100,c101,c102,c103};\n"
            "ld.shared.v4.u32 {x0,x1,x2,x3}, [xa+1024];\n"
            "tanh.approx.f32 th0, h1;\n"
            "tanh.approx.f32 th1, h3;\n"
            "fma.rn.f32 th0, h1, th0, h1;\n"
            "fma.rn.f32 th1, h3, th1, h3;\n"
            "cvt.rn.bf16x2.f32 r0, th1, th0;\n"
            "mma.sync.aligned.m16n8k16.row.col.f32.bf16.bf16.f32 {h0,h1,h2,h3}, {%7,%8,%9,%10}, {e0,e1}, {fz,fz,fz,fz};\n"
            "mma.sync.aligned.m16n8k16.row.col.f32.bf16.bf16.f32 {c104,c105,c106,c107}, {a0,a1,a2,a3}, {x4,x5}, {c104,c105,c106,c107};\n"
            "mma.sync.aligned.m16n8k16.row.col.f32.bf16.bf16.f32 {c108,c109,c110,c111}, {a0,a1,a2,a3}, {x6,x7}, {c108,c109,c110,c111};\n"
            "ld.shared.v4.u32 {x4,x5,x6,x7}, [xa+1152];\n"
            "tanh.approx.f32 th2, h5;\n"
            "tanh.approx.f32 th3, h7;\n"
            "fma.rn.f32 th2, h5, th2, h5;\n"
            "fma.rn.f32 th3, h7, th3, h7;\n"
            "cvt.rn.bf16x2.f32 r1, th3, th2;\n"
            "mma.sync.aligned.m16n8k16.row.col.f32.bf16.bf16.f32 {h4,h5,h6,h7}, {%11,%12,%13,%14}, {e0,e1}, {fz,fz,fz,fz};\n"
            "mma.sync.aligned.m16n8k16.row.col.f32.bf16.bf16.f32 {c112,c113,c114,c115}, {a0,a1,a2,a3}, {x8,x9}, {c112,c113,c114,c115};\n"
            "mma.sync.aligned.m16n8k16.row.col.f32.bf16.bf16.f32 {c116,c117,c118,c119}, {a0,a1,a2,a3}, {x10,x11}, {c116,c117,c118,c119};\n"
            "ld.shared.v4.u32 {x8,x9,x10,x11}, [xa+1536];\n"
            "tanh.approx.f32 th4, h9;\n"
            "tanh.approx.f32 th5, h11;\n"
            "fma.rn.f32 th4, h9, th4, h9;\n"
            "fma.rn.f32 th5, h11, th5, h11;\n"
            "cvt.rn.bf16x2.f32 r2, th5, th4;\n"
            "mma.sync.aligned.m16n8k16.row.col.f32.bf16.bf16.f32 {h8,h9,h10,h11}, {%15,%16,%17,%18}, {e0,e1}, {fz,fz,fz,fz};\n"
            "mma.sync.aligned.m16n8k16.row.col.f32.bf16.bf16.f32 {c120,c121,c122,c123}, {a0,a1,a2,a3}, {x12,x13}, {c120,c121,c122,c123};\n"
            "mma.sync.aligned.m16n8k16.row.col.f32.bf16.bf16.f32 {c124,c125,c126,c127}, {a0,a1,a2,a3}, {x14,x15}, {c124,c125,c126,c127};\n"
            "ld.shared.v4.u32 {x12,x13,x14,x15}, [xa+1664];\n"
            "tanh.approx.f32 th6, h13;\n"
            "tanh.approx.f32 th7, h15;\n"
            "fma.rn.f32 th6, h13, th6, h13;\n"
            "fma.rn.f32 th7, h15, th7, h15;\n"
            "cvt.rn.bf16x2.f32 r3, th7, th6;\n"
            "mma.sync.aligned.m16n8k16.row.col.f32.bf16.bf16.f32 {h12,h13,h14,h15}, {%19,%20,%21,%22}, {e0,e1}, {fz,fz,fz,fz};\n"
            "ld.shared.v4.u32 {a0,a1,a2,a3}, [ab+128];\n"
            "and.b32 tmp, aa, 0xffffff80; mbarrier.test_wait.parity.shared::cta.b64 pw, [tmp+520], mt;\n"
            "mad.lo.s32 xa, st, 2048, xa;\n"
            "mov.b32 {lo,hi}, r0; mov.b32 rl, {lo,lo}; mov.b32 rh, {hi,hi};\n"
            "mul.bf16x2 x0, x0, rl; mul.bf16x2 x1, x1, rl; mul.bf16x2 x2, x2, rh; mul.bf16x2 x3, x3, rh;\n"
            "mov.b32 {lo,hi}, r1; mov.b32 rl, {lo,lo}; mov.b32 rh, {hi,hi};\n"
            "mul.bf16x2 x4, x4, rl; mul.bf16x2 x5, x5, rl; mul.bf16x2 x6, x6, rh; mul.bf16x2 x7, x7, rh;\n"
            "mov.b32 {lo,hi}, r2; mov.b32 rl, {lo,lo}; mov.b32 rh, {hi,hi};\n"
            "mul.bf16x2 x8, x8, rl; mul.bf16x2 x9, x9, rl; mul.bf16x2 x10, x10, rh; mul.bf16x2 x11, x11, rh;\n"
            "mov.b32 {lo,hi}, r3; mov.b32 rl, {lo,lo}; mov.b32 rh, {hi,hi};\n"
            "mul.bf16x2 x12, x12, rl; mul.bf16x2 x13, x13, rl; mul.bf16x2 x14, x14, rh; mul.bf16x2 x15, x15, rh;\n"
            "@!pw bra.uni W1;\n"
            "@d2 bra.uni B0_4; @d1 bra.uni L0; @d0 bra.uni B0_1; bra.uni B0_0;\n"
            "B1_4:\n"
            "xor.b32 tmp, mt, ea; and.b32 tmp, tmp, 192; setp.eq.u32 pm, tmp, 0; selp.b32 ab, aa, %3, pm;\n"
            "and.b32 tmp, mt, 8; setp.ne.u32 d0, tmp, 0; and.b32 tmp, mt, 16; setp.ne.u32 d1, tmp, 0; and.b32 tmp, mt, 32; setp.ne.u32 d2, tmp, 0;\n"
            "ld.shared.v2.u32 {e0,e1}, [ea];\n"
            "shr.s32 st, mt, 24; mad.lo.s32 aa, st, 2560, aa;\n"
            "mma.sync.aligned.m16n8k16.row.col.f32.bf16.bf16.f32 {c128,c129,c130,c131}, {a0,a1,a2,a3}, {x0,x1}, {c128,c129,c130,c131};\n"
            "mma.sync.aligned.m16n8k16.row.col.f32.bf16.bf16.f32 {c132,c133,c134,c135}, {a0,a1,a2,a3}, {x2,x3}, {c132,c133,c134,c135};\n"
            "ld.shared.v4.u32 {x0,x1,x2,x3}, [xa+1024];\n"
            "tanh.approx.f32 th0, h1;\n"
            "tanh.approx.f32 th1, h3;\n"
            "fma.rn.f32 th0, h1, th0, h1;\n"
            "fma.rn.f32 th1, h3, th1, h3;\n"
            "cvt.rn.bf16x2.f32 r0, th1, th0;\n"
            "mma.sync.aligned.m16n8k16.row.col.f32.bf16.bf16.f32 {h0,h1,h2,h3}, {%7,%8,%9,%10}, {e0,e1}, {fz,fz,fz,fz};\n"
            "mma.sync.aligned.m16n8k16.row.col.f32.bf16.bf16.f32 {c136,c137,c138,c139}, {a0,a1,a2,a3}, {x4,x5}, {c136,c137,c138,c139};\n"
            "mma.sync.aligned.m16n8k16.row.col.f32.bf16.bf16.f32 {c140,c141,c142,c143}, {a0,a1,a2,a3}, {x6,x7}, {c140,c141,c142,c143};\n"
            "ld.shared.v4.u32 {x4,x5,x6,x7}, [xa+1152];\n"
            "tanh.approx.f32 th2, h5;\n"
            "tanh.approx.f32 th3, h7;\n"
            "fma.rn.f32 th2, h5, th2, h5;\n"
            "fma.rn.f32 th3, h7, th3, h7;\n"
            "cvt.rn.bf16x2.f32 r1, th3, th2;\n"
            "mma.sync.aligned.m16n8k16.row.col.f32.bf16.bf16.f32 {h4,h5,h6,h7}, {%11,%12,%13,%14}, {e0,e1}, {fz,fz,fz,fz};\n"
            "mma.sync.aligned.m16n8k16.row.col.f32.bf16.bf16.f32 {c144,c145,c146,c147}, {a0,a1,a2,a3}, {x8,x9}, {c144,c145,c146,c147};\n"
            "mma.sync.aligned.m16n8k16.row.col.f32.bf16.bf16.f32 {c148,c149,c150,c151}, {a0,a1,a2,a3}, {x10,x11}, {c148,c149,c150,c151};\n"
            "ld.shared.v4.u32 {x8,x9,x10,x11}, [xa+1536];\n"
            "tanh.approx.f32 th4, h9;\n"
            "tanh.approx.f32 th5, h11;\n"
            "fma.rn.f32 th4, h9, th4, h9;\n"
            "fma.rn.f32 th5, h11, th5, h11;\n"
            "cvt.rn.bf16x2.f32 r2, th5, th4;\n"
            "mma.sync.aligned.m16n8k16.row.col.f32.bf16.bf16.f32 {h8,h9,h10,h11}, {%15,%16,%17,%18}, {e0,e1}, {fz,fz,fz,fz};\n"
            "mma.sync.aligned.m16n8k16.row.col.f32.bf16.bf16.f32 {c152,c153,c154,c155}, {a0,a1,a2,a3}, {x12,x13}, {c152,c153,c154,c155};\n"
            "mma.sync.aligned.m16n8k16.row.col.f32.bf16.bf16.f32 {c156,c157,c158,c159}, {a0,a1,a2,a3}, {x14,x15}, {c156,c157,c158,c159};\n"
            "ld.shared.v4.u32 {x12,x13,x14,x15}, [xa+1664];\n"
            "tanh.approx.f32 th6, h13;\n"
            "tanh.approx.f32 th7, h15;\n"
            "fma.rn.f32 th6, h13, th6, h13;\n"
            "fma.rn.f32 th7, h15, th7, h15;\n"
            "cvt.rn.bf16x2.f32 r3, th7, th6;\n"
            "mma.sync.aligned.m16n8k16.row.col.f32.bf16.bf16.f32 {h12,h13,h14,h15}, {%19,%20,%21,%22}, {e0,e1}, {fz,fz,fz,fz};\n"
            "ld.shared.v4.u32 {a0,a1,a2,a3}, [ab+128];\n"
            "and.b32 tmp, aa, 0xffffff80; mbarrier.test_wait.parity.shared::cta.b64 pw, [tmp+520], mt;\n"
            "mad.lo.s32 xa, st, 2048, xa;\n"
            "mov.b32 {lo,hi}, r0; mov.b32 rl, {lo,lo}; mov.b32 rh, {hi,hi};\n"
            "mul.bf16x2 x0, x0, rl; mul.bf16x2 x1, x1, rl; mul.bf16x2 x2, x2, rh; mul.bf16x2 x3, x3, rh;\n"
            "mov.b32 {lo,hi}, r1; mov.b32 rl, {lo,lo}; mov.b32 rh, {hi,hi};\n"
            "mul.bf16x2 x4, x4, rl; mul.bf16x2 x5, x5, rl; mul.bf16x2 x6, x6, rh; mul.bf16x2 x7, x7, rh;\n"
            "mov.b32 {lo,hi}, r2; mov.b32 rl, {lo,lo}; mov.b32 rh, {hi,hi};\n"
            "mul.bf16x2 x8, x8, rl; mul.bf16x2 x9, x9, rl; mul.bf16x2 x10, x10, rh; mul.bf16x2 x11, x11, rh;\n"
            "mov.b32 {lo,hi}, r3; mov.b32 rl, {lo,lo}; mov.b32 rh, {hi,hi};\n"
            "mul.bf16x2 x12, x12, rl; mul.bf16x2 x13, x13, rl; mul.bf16x2 x14, x14, rh; mul.bf16x2 x15, x15, rh;\n"
            "@!pw bra.uni W1;\n"
            "@d2 bra.uni B0_4; @d1 bra.uni L0; @d0 bra.uni B0_1; bra.uni B0_0;\n"
            "W1:\n"
            "mov.u32 cnt, 0; and.b32 tmp, aa, 0xffffff80;\n"
            "W1L: mbarrier.try_wait.parity.shared::cta.b64 pw, [tmp+520], mt; @pw bra.uni W1D;\n"
            "add.u32 cnt, cnt, 1; setp.lt.u32 pk, cnt, 1000000; @pk bra.uni W1L; trap;\n"
            "W1D:\n"
            "@d2 bra.uni B0_4; @d1 bra.uni L0; @d0 bra.uni B0_1; bra.uni B0_0;\n"
            "END:\n"
            "cvt.rn.bf16x2.f32 p0, c1, c0; cvt.rn.bf16x2.f32 p1, c5, c4; cvt.rn.bf16x2.f32 p2, c9, c8; cvt.rn.bf16x2.f32 p3, c13, c12; cvt.rn.bf16x2.f32 p4, c17, c16; cvt.rn.bf16x2.f32 p5, c21, c20; cvt.rn.bf16x2.f32 p6, c25, c24; cvt.rn.bf16x2.f32 p7, c29, c28;\n"
            "cvt.rn.bf16x2.f32 p8, c3, c2; cvt.rn.bf16x2.f32 p9, c7, c6; cvt.rn.bf16x2.f32 p10, c11, c10; cvt.rn.bf16x2.f32 p11, c15, c14; cvt.rn.bf16x2.f32 p12, c19, c18; cvt.rn.bf16x2.f32 p13, c23, c22; cvt.rn.bf16x2.f32 p14, c27, c26; cvt.rn.bf16x2.f32 p15, c31, c30;\n"
            "cvt.rn.bf16x2.f32 p16, c33, c32; cvt.rn.bf16x2.f32 p17, c37, c36; cvt.rn.bf16x2.f32 p18, c41, c40; cvt.rn.bf16x2.f32 p19, c45, c44; cvt.rn.bf16x2.f32 p20, c49, c48; cvt.rn.bf16x2.f32 p21, c53, c52; cvt.rn.bf16x2.f32 p22, c57, c56; cvt.rn.bf16x2.f32 p23, c61, c60;\n"
            "cvt.rn.bf16x2.f32 p24, c35, c34; cvt.rn.bf16x2.f32 p25, c39, c38; cvt.rn.bf16x2.f32 p26, c43, c42; cvt.rn.bf16x2.f32 p27, c47, c46; cvt.rn.bf16x2.f32 p28, c51, c50; cvt.rn.bf16x2.f32 p29, c55, c54; cvt.rn.bf16x2.f32 p30, c59, c58; cvt.rn.bf16x2.f32 p31, c63, c62;\n"
            "cvt.rn.bf16x2.f32 p32, c65, c64; cvt.rn.bf16x2.f32 p33, c69, c68; cvt.rn.bf16x2.f32 p34, c73, c72; cvt.rn.bf16x2.f32 p35, c77, c76; cvt.rn.bf16x2.f32 p36, c81, c80; cvt.rn.bf16x2.f32 p37, c85, c84; cvt.rn.bf16x2.f32 p38, c89, c88; cvt.rn.bf16x2.f32 p39, c93, c92;\n"
            "cvt.rn.bf16x2.f32 p40, c67, c66; cvt.rn.bf16x2.f32 p41, c71, c70; cvt.rn.bf16x2.f32 p42, c75, c74; cvt.rn.bf16x2.f32 p43, c79, c78; cvt.rn.bf16x2.f32 p44, c83, c82; cvt.rn.bf16x2.f32 p45, c87, c86; cvt.rn.bf16x2.f32 p46, c91, c90; cvt.rn.bf16x2.f32 p47, c95, c94;\n"
            "cvt.rn.bf16x2.f32 p48, c97, c96; cvt.rn.bf16x2.f32 p49, c101, c100; cvt.rn.bf16x2.f32 p50, c105, c104; cvt.rn.bf16x2.f32 p51, c109, c108; cvt.rn.bf16x2.f32 p52, c113, c112; cvt.rn.bf16x2.f32 p53, c117, c116; cvt.rn.bf16x2.f32 p54, c121, c120; cvt.rn.bf16x2.f32 p55, c125, c124;\n"
            "cvt.rn.bf16x2.f32 p56, c99, c98; cvt.rn.bf16x2.f32 p57, c103, c102; cvt.rn.bf16x2.f32 p58, c107, c106; cvt.rn.bf16x2.f32 p59, c111, c110; cvt.rn.bf16x2.f32 p60, c115, c114; cvt.rn.bf16x2.f32 p61, c119, c118; cvt.rn.bf16x2.f32 p62, c123, c122; cvt.rn.bf16x2.f32 p63, c127, c126;\n"
            "cvt.rn.bf16x2.f32 p64, c129, c128; cvt.rn.bf16x2.f32 p65, c133, c132; cvt.rn.bf16x2.f32 p66, c137, c136; cvt.rn.bf16x2.f32 p67, c141, c140; cvt.rn.bf16x2.f32 p68, c145, c144; cvt.rn.bf16x2.f32 p69, c149, c148; cvt.rn.bf16x2.f32 p70, c153, c152; cvt.rn.bf16x2.f32 p71, c157, c156;\n"
            "cvt.rn.bf16x2.f32 p72, c131, c130; cvt.rn.bf16x2.f32 p73, c135, c134; cvt.rn.bf16x2.f32 p74, c139, c138; cvt.rn.bf16x2.f32 p75, c143, c142; cvt.rn.bf16x2.f32 p76, c147, c146; cvt.rn.bf16x2.f32 p77, c151, c150; cvt.rn.bf16x2.f32 p78, c155, c154; cvt.rn.bf16x2.f32 p79, c159, c158;\n"
            "and.b32 aa, %3, 0xfffff980; sub.u32 aa, aa, %6; mov.u32 mt, %%tid.x; shr.u32 st, mt, 7; shr.u32 cnt, mt, 5; add.u32 cnt, cnt, st; and.b32 cnt, cnt, 3;\n"
            "and.b32 mt, mt, 31; mad.lo.u32 tmp, mt, 16, aa; mad.lo.u32 tmp, st, 82432, tmp; mad.lo.u32 tmp, cnt, 10240, tmp; add.u32 cnt, cnt, 5;\n"
            "bar.sync cnt, 64;\n"
            "stmatrix.sync.aligned.m8n8.x4.shared.b16 [tmp+0], {p0,p1,p2,p3};\n"
            "stmatrix.sync.aligned.m8n8.x4.shared.b16 [tmp+41216], {p4,p5,p6,p7};\n"
            "stmatrix.sync.aligned.m8n8.x4.shared.b16 [tmp+1024], {p8,p9,p10,p11};\n"
            "stmatrix.sync.aligned.m8n8.x4.shared.b16 [tmp+42240], {p12,p13,p14,p15};\n"
            "stmatrix.sync.aligned.m8n8.x4.shared.b16 [tmp+2048], {p16,p17,p18,p19};\n"
            "stmatrix.sync.aligned.m8n8.x4.shared.b16 [tmp+43264], {p20,p21,p22,p23};\n"
            "stmatrix.sync.aligned.m8n8.x4.shared.b16 [tmp+3072], {p24,p25,p26,p27};\n"
            "stmatrix.sync.aligned.m8n8.x4.shared.b16 [tmp+44288], {p28,p29,p30,p31};\n"
            "stmatrix.sync.aligned.m8n8.x4.shared.b16 [tmp+4096], {p32,p33,p34,p35};\n"
            "stmatrix.sync.aligned.m8n8.x4.shared.b16 [tmp+45312], {p36,p37,p38,p39};\n"
            "stmatrix.sync.aligned.m8n8.x4.shared.b16 [tmp+5120], {p40,p41,p42,p43};\n"
            "stmatrix.sync.aligned.m8n8.x4.shared.b16 [tmp+46336], {p44,p45,p46,p47};\n"
            "stmatrix.sync.aligned.m8n8.x4.shared.b16 [tmp+6144], {p48,p49,p50,p51};\n"
            "stmatrix.sync.aligned.m8n8.x4.shared.b16 [tmp+47360], {p52,p53,p54,p55};\n"
            "stmatrix.sync.aligned.m8n8.x4.shared.b16 [tmp+7168], {p56,p57,p58,p59};\n"
            "stmatrix.sync.aligned.m8n8.x4.shared.b16 [tmp+48384], {p60,p61,p62,p63};\n"
            "stmatrix.sync.aligned.m8n8.x4.shared.b16 [tmp+8192], {p64,p65,p66,p67};\n"
            "stmatrix.sync.aligned.m8n8.x4.shared.b16 [tmp+49408], {p68,p69,p70,p71};\n"
            "stmatrix.sync.aligned.m8n8.x4.shared.b16 [tmp+9216], {p72,p73,p74,p75};\n"
            "stmatrix.sync.aligned.m8n8.x4.shared.b16 [tmp+50432], {p76,p77,p78,p79};\n"
            "mov.b32 %0, aa;\n"
            "}\n"
            : "=r"(sb2)
            : "r"(sb + t * XREG + grp * (NST * 2048) + half * 256 + ((g ^ ((2 * t + 2 * half) & 7)) << 4)),
              "r"(sb + AUX_OFF + grp * AUX_GR + t * 32 + (g & 1) * 16), "r"(az),
              "r"(sb + AUX_OFF + grp * AUX_GR + 256 + lane * 8), "r"(zero), "n"(ZERO_OFF),
              "r"(wr[0][0]), "r"(wr[0][1]), "r"(wr[0][2]), "r"(wr[0][3]), "r"(wr[1][0]), "r"(wr[1][1]), "r"(wr[1][2]), "r"(wr[1][3]),
              "r"(wr[2][0]), "r"(wr[2][1]), "r"(wr[2][2]), "r"(wr[2][3]), "r"(wr[3][0]), "r"(wr[3][1]), "r"(wr[3][2]), "r"(wr[3][3])
            : "memory");
        const int tid2 = threadIdx.x;
        sb2 = __shfl_sync(0xffffffffu, sb2, 0);
        const uint2 own = lds64(sb2 + MISC_OFF + 8);
        mbar_wait(sb2 + MISC_OFF, 0);
        asm volatile("fence.proxy.async.shared::cta;" ::: "memory");
        asm volatile("bar.sync 1, 256;" ::: "memory");
        const uint32_t wg = __shfl_sync(0xffffffffu, tid2 >> 7, 0);
        const uint64_t da = (uint64_t)((sb2 + WM_OFF + wg * 16384) >> 4) | (1ull << 16) | (64ull << 32) | (1ull << 62);
        const uint64_t db = (uint64_t)(sb2 >> 4) | (8ull << 16) | (64ull << 32);
        const int left = (int)own.y - 4 * (tid2 & 3);
        uint32_t* op = out + (size_t)(own.x + 4 * (tid2 & 3)) * 256 + ((tid2 >> 5) * 16 + ((tid2 & 31) >> 2)) * 2;
        float d0[40], d1[40], d2[40], d3[40], d4[40];
        mix_tiles<2, 0>(d0, da, db);
        mix_tiles<3, 2>(d1, da, db);
        store_tiles<2, 0, 1>(d0, op, left, 3 + wg);
        mix_tiles<5, 5>(d2, da, db);
        store_tiles<3, 2, 1>(d1, op, left, 3 + wg);
        mix_tiles<5, 10>(d3, da, db);
        store_tiles<5, 5, 1>(d2, op, left, 3 + wg);
        mix_tiles<5, 15>(d4, da, db);
        store_tiles<5, 10, 1>(d3, op, left, 3 + wg);
        store_tiles<5, 15, 0>(d4, op, left, 3 + wg);
    } else {
        asm volatile("setmaxnreg.dec.sync.aligned.u32 40;");
        const uint64_t map = ((uint64_t)maphi << 32) | maplo, efl = ((uint64_t)efhi << 32) | eflo;
        const uint32_t ab = s0 + AUX_OFF + pgrp * AUX_GR, xb = s0 + pgrp * (NST * 2048);
        uint32_t yp = s0 + SY_OFF + pgrp * GCAP * 4 - 32;
        uint32_t par = 0, prev = 0;
        uint32_t parv = keep(lane & zero);
        auto ahead = [&](int st, uint32_t ev) {
            asm volatile("cp.async.ca.shared.global [%0], [%1], 8;" ::"r"(w_l + st * AUX_ST + 256), "l"(efl + (ev & 0x1ffffe0u)) : "memory");
            cp_async_arrive(ab + st * AUX_ST + BAR_F0);
            if (st == NST - 1) parv ^= 1u;
            sts8(f_l + st * AUX_ST, (__byte_perm(ev, prev, fsel) & 0xfeu) | parv);
            prev = ev;
        };
        uint32_t wn0, wn1;
        int left = (int)noct;
        uint32_t efo = blockIdx.x * EPC * 32u + pgrp * PFE;
        const uint32_t efend = min((blockIdx.x + 1) * EPC, E) * 32u;
        uint32_t pfo = (4u * (PFA * gridDim.x + blockIdx.x) + pgrp) * pfb;
        const uint32_t pfend = (uint32_t)N * 1024u - pfb;
        auto step = [&](int st, int WM) {
            if (left < st) return true;
            const uint4 y0 = lds128(yp + st * 32), y1 = lds128(yp + st * 32 + 16);
            const uint32_t ev = lds32(yp + st * 32 + 32 + e_l);
            uint32_t wa = wn0, wb = wn1;
            if (WM) {
                const uint32_t h0 = lds32(h_l + st * 64), h1 = lds32(h_l + st * 64 + 64);
                float w0[4], w1[4];
                mma1688_z(w0, h0, h1, cgb0);
                mma1688_z(w1, h0, h1, cgb1);
                wa = pack_bf16(w0[0], w0[1]); wb = pack_bf16(w1[0], w1[1]);
                if (WM == 2) { wn0 = pack_bf16(w0[2], w0[3]); wn1 = pack_bf16(w1[2], w1[3]); }
            }
            const uint32_t ys = y0.y + y0.z + y1.y + y1.z;
            const uint32_t tq = T0 + ((ys * pc) >> 13);
            const int sg = st % NST;
            mbar_wait(ab + sg * AUX_ST + BAR_EM, par ^ 1u);
            int rem = (int)(tq - (uint32_t)clock64());
            ahead(sg, ev);
            sts64(w_l + sg * AUX_ST, wa, wb);
            __syncwarp();
            asm volatile("{\n\t.reg .pred P;\n\tsetp.ne.u32 P, %1, 0;\n\t@P mbarrier.arrive.expect_tx.shared::cta.b64 _, [%0], %1;\n\t}"
                         ::"r"(ab + sg * AUX_ST + BAR_F0), "r"(bytes) : "memory");
#pragma unroll 1
            while (rem > 0) {
                __nanosleep(SLEEP);
                rem = (int)(tq - (uint32_t)clock64());
            }
            fetch_quad(xb + sg * 2048, ab + sg * AUX_ST + BAR_F0, y0, map);
            fetch_quad(xb + sg * 2048 + 1024, ab + sg * AUX_ST + BAR_F0, y1, map);
            return false;
        };
        ahead(0, lds32(yp + 32 + e_l));
        __syncwarp();
        if (lane == 0) asm volatile("mbarrier.arrive.shared::cta.b64 _, [%0], %1;" ::"r"(ab + BAR_F0), "n"(F0_COUNT - 32) : "memory");
#pragma unroll 1
        for (;;) {
            if (step(1, 2)) break;
            if (step(2, 0)) break;
            if (efo < efend) prefetch_bulk(ef + efo, min(PFE, efend - efo));
            efo += 4u * PFE;
            if (step(3, 2)) break;
            if (step(4, 0)) break;
            par ^= 1u;
            if (step(5, 1)) break;
            if (pfo <= pfend) prefetch_bulk(x + pfo, pfb);
            pfo += 4u * gridDim.x * pfb;
            yp += NST * 32;
            left -= NST;
            h_l += NST * 64;
        }
        const uint32_t rounds = (noct + 1) / NST, fin = noct + 1 - rounds * NST;
        mbar_wait(ab + fin * AUX_ST + BAR_EM, ~rounds & 1u);
        if (lane == 0) asm volatile("mbarrier.arrive.shared::cta.b64 _, [%0], %1;" ::"r"(ab + fin * AUX_ST + BAR_F0), "n"(F0_COUNT) : "memory");
        asm volatile("bar.sync 2, 128;" ::: "memory");
        const int ln = threadIdx.x & 31;
#pragma unroll 4
        for (int i = 0; i < 16; i++) {
            const int kr = i * 8 + pgrp * 2 + (ln >> 4);
            const int dj = ((i >> 1) & 1) + (i & 4), n = kr & 7;
            const int ch = 16 * (2 * (i >> 3) + dj) + 2 * (n ^ dj) + (i & 1);
            asm volatile("cp.async.cg.shared.global [%0], [%1], 16;"
                         ::"r"(s0 + WM_OFF + ((ln >> 3) & 1) * 16384 + kr * 128 + (((ln & 7) ^ n) << 4)),
                           "l"(w_mix + ch * 128 + (ln & 15) * 8) : "memory");
        }
        cp_async_arrive(s0 + MISC_OFF);
        asm volatile("cp.async.wait_all;" ::: "memory");
    }
}

typedef CUresult (*EncodeFn)(CUtensorMap*, CUtensorMapDataType, cuuint32_t, void*, const cuuint64_t*, const cuuint64_t*,
                             const cuuint32_t*, const cuuint32_t*, CUtensorMapInterleave, CUtensorMapSwizzle,
                             CUtensorMapL2promotion, CUtensorMapFloatOOBfill);

}

#define WALK 46000
#define LEAD 6700

extern "C" void kernel_launch(void* const* d_in, const int* in_sizes, int n_in, void* d_out, int out_size) {
    const char* x = (const char*)d_in[0];
    const int* src = (const int*)d_in[1];
    const int* dst = (const int*)d_in[2];
    const uint2* Y = (const uint2*)d_in[3];
    const char* ef = (const char*)d_in[4];
    const __nv_bfloat16* w_rad = (const __nv_bfloat16*)d_in[5];
    const __nv_bfloat16* cg = (const __nv_bfloat16*)d_in[6];
    const __nv_bfloat16* w_mix = (const __nv_bfloat16*)d_in[7];
    const int N = in_sizes[0] / 512;
    const int E = in_sizes[1];

    static int num_cta = 0;
    static EncodeFn encode = nullptr;
    if (num_cta == 0) {
        int dev = 0, sms = 0;
        cudaGetDevice(&dev);
        cudaDeviceGetAttribute(&sms, cudaDevAttrMultiProcessorCount, dev);
        num_cta = sms < MAXCTA ? sms : MAXCTA;
        cudaFuncSetAttribute(tfn_kernel, cudaFuncAttributeMaxDynamicSharedMemorySize, SMEM_BYTES);
        void* fn = nullptr;
        cudaDriverEntryPointQueryResult qr;
        cudaGetDriverEntryPoint("cuTensorMapEncodeTiled", &fn, cudaEnableDefault, &qr);
        encode = (EncodeFn)fn;
    }
    int S = (N + num_cta - 1) / num_cta;
    if (S < 2) S = 2;
    const int EPC = ((E + num_cta - 1) / num_cta + 3) & ~3;
    if (S > SMAX || EPC > EPC_MAX || N < 128 || N > 16384 || E <= 0 || E > (1 << 20) || encode == nullptr) return;
    CUtensorMap xmap;
    const cuuint64_t gd[2] = {64, (cuuint64_t)N * 8}, gs[1] = {128};
    const cuuint32_t bx[2] = {64, BOX_LINES}, es[2] = {1, 1};
    if (encode(&xmap, CU_TENSOR_MAP_DATA_TYPE_BFLOAT16, 2, (void*)x, gd, gs, bx, es, CU_TENSOR_MAP_INTERLEAVE_NONE,
               CU_TENSOR_MAP_SWIZZLE_128B, CU_TENSOR_MAP_L2_PROMOTION_NONE, CU_TENSOR_MAP_FLOAT_OOB_FILL_NONE) != CUDA_SUCCESS)
        return;
    const uint32_t magicS = (uint32_t)((0x100000000ull + S - 1) / S);
    uint32_t magicB = (uint32_t)(((unsigned long long)NB << 32) / N);
    int walk = WALK, lead = LEAD;
    double pc = (double)walk * ((double)E / N * S / 2432.0) / (16.0 * N);
    if (pc > 0.99) pc = 0.99;
    uint32_t pace = (uint32_t)(pc * 4096.0 + 0.5), curve = 0;
    const uint32_t pfb = ((uint32_t)(1024.0 * N / E * 40.0) + 127u) & ~127u;
    tfn_kernel<<<num_cta, NT, SMEM_BYTES, cudaStreamPerThread>>>(xmap, x, src, dst, Y, ef, w_rad, cg, w_mix, (uint32_t*)d_out, N, E, S,
                                                                 EPC, magicS, magicB, 0u, pace, lead, pfb, curve);
}
```

```cpp
#include <cuda_runtime.h>
#include <cuda.h>
#include <cuda_bf16.h>
#include <stdint.h>

namespace {

constexpr int NT = 384;
constexpr int NWARP = NT / 32;
constexpr int MAXCTA = 132;
constexpr int SFAST = 80;
constexpr int SMAX = 96;
constexpr int EPC_MAX = 3072;
constexpr int RND = 10;
constexpr int NB = 96;
constexpr int GCAP = 800;
constexpr int NCOL = NWARP - 1;
constexpr int JCAP = NCOL * RND * 8 + 8;
constexpr int RND0 = 8;
constexpr uint32_t TAGM = 31u;
constexpr int NST = 5;
constexpr uint32_t F0_COUNT = 33;
#define SLEEPNS 100
constexpr uint32_t SLEEP = SLEEPNS;
constexpr uint32_t PFA = 2, PFE = 2048;
constexpr int SPIN_LIMIT = 1 << 22;

constexpr int XREG = 4 * NST * 2048 + 256;
constexpr int AUX_OFF = 4 * XREG;
constexpr int AUX_ST = 2560, AUX_GR = 640;
constexpr int BAR_F0 = 520, BAR_EM = 536;
constexpr int SY_OFF = AUX_OFF + NST * AUX_ST;
constexpr int SE_OFF = SY_OFF + 4 * GCAP * 4;
constexpr int SH_OFF = SE_OFF + 4 * GCAP * 4;
constexpr int MISC_OFF = SH_OFF + 4 * GCAP * 8;
constexpr int ZERO_OFF = ((MISC_OFF + 1024 + 2047) & ~2047) - 1024;
constexpr int WM_OFF = (SE_OFF + 1023) & ~1023;
constexpr int CNT_OFF = 20 * JCAP * 4, START_OFF = CNT_OFF + 1024;
constexpr int BCNT_OFF = START_OFF + 1024;
constexpr int BCUM_OFF = BCNT_OFF + 20 * NB * 4;
constexpr int SEG_OFF = BCUM_OFF + 20 * NB * 4;
constexpr int WR_OFF = SEG_OFF + 1024;
constexpr int GI_OFF = 0;
struct Misc {
    unsigned long long wbar;
    int node0, Sc;
    unsigned long long rbar;
    int nq[4];
    int dmax;
    uint32_t epoch, ref;
    uint32_t rseg[MAXCTA];
};
constexpr int SMEM_BYTES = ZERO_OFF + 1792;
static_assert(MISC_OFF + (int)sizeof(Misc) <= ZERO_OFF, "layout");
static_assert(SMEM_BYTES <= 227 * 1024, "shared memory");
static_assert(EPC_MAX * 16 <= CNT_OFF && WR_OFF + 4096 <= AUX_OFF && WR_OFF % 128 == 0, "tables");
static_assert(WM_OFF + 32768 <= MISC_OFF && SMAX * 2048 <= MISC_OFF, "layout");
static_assert(AUX_OFF % 256 == 0 && NB == 96 && NWARP == 12, "layout");

__device__ __align__(128) uint4 g_staged[(size_t)MAXCTA * EPC_MAX];
__device__ __align__(128) uint2 g_table[MAXCTA * 144];
__device__ unsigned int g_epoch[MAXCTA];

__device__ __forceinline__ void mma1688_z(float (&d)[4], uint32_t a0, uint32_t a1, uint32_t b0) {
    asm volatile(
        "mma.sync.aligned.m16n8k8.row.col.f32.bf16.bf16.f32 {%0,%1,%2,%3}, {%4,%5}, {%6}, {%7,%7,%7,%7};"
        : "=f"(d[0]), "=f"(d[1]), "=f"(d[2]), "=f"(d[3])
        : "r"(a0), "r"(a1), "r"(b0), "f"(0.0f));
}
__device__ __forceinline__ uint32_t pack_bf16(float lo, float hi) {
    uint32_t r;
    asm("cvt.rn.bf16x2.f32 %0, %1, %2;" : "=r"(r) : "f"(hi), "f"(lo));
    return r;
}
__device__ __forceinline__ uint32_t half_bf16x2(uint32_t v) {
    uint32_t r;
    asm("mul.bf16x2 %0, %1, %2;" : "=r"(r) : "r"(v), "r"(0x3f003f00u));
    return r;
}
__device__ __forceinline__ uint4 lds128(uint32_t a) {
    uint4 v;
    asm volatile("ld.shared.v4.u32 {%0,%1,%2,%3}, [%4];" : "=r"(v.x), "=r"(v.y), "=r"(v.z), "=r"(v.w) : "r"(a) : "memory");
    return v;
}
__device__ __forceinline__ uint32_t lds32(uint32_t a) {
    uint32_t v;
    asm volatile("ld.shared.u32 %0, [%1];" : "=r"(v) : "r"(a) : "memory");
    return v;
}
__device__ __forceinline__ uint2 lds64(uint32_t a) {
    uint2 v;
    asm volatile("ld.shared.v2.u32 {%0,%1}, [%2];" : "=r"(v.x), "=r"(v.y) : "r"(a) : "memory");
    return v;
}
__device__ __forceinline__ void sts8(uint32_t a, uint32_t v) {
    asm volatile("st.shared.u8 [%0], %1;" ::"r"(a), "r"(v) : "memory");
}
__device__ __forceinline__ void sts64(uint32_t a, uint32_t v0, uint32_t v1) {
    asm volatile("st.shared.v2.u32 [%0], {%1,%2};" ::"r"(a), "r"(v0), "r"(v1) : "memory");
}
#define OCT_BYTES 8192
#define BOX_LINES 8
__device__ __forceinline__ void fetch_quad(uint32_t dst, uint32_t bar, const uint4& y, uint64_t map) {
    asm volatile("{\n\t.reg .pred P;\n\telect.sync _|P, 0xffffffff;\n\t"
                 "@P cp.async.bulk.tensor.2d.shared::cluster.global.mbarrier::complete_tx::bytes [%0], [%6, {0, %2}], [%1];\n\t"
                 "@P cp.async.bulk.tensor.2d.shared::cluster.global.mbarrier::complete_tx::bytes [%0+%7], [%6, {0, %3}], [%1];\n\t"
                 "@P cp.async.bulk.tensor.2d.shared::cluster.global.mbarrier::complete_tx::bytes [%0+%8], [%6, {0, %4}], [%1];\n\t"
                 "@P cp.async.bulk.tensor.2d.shared::cluster.global.mbarrier::complete_tx::bytes [%0+%9], [%6, {0, %5}], [%1];\n\t}"
                 ::"r"(dst), "r"(bar), "r"(y.x), "r"(y.y), "r"(y.z), "r"(y.w), "l"(map), "n"(XREG), "n"(2 * XREG), "n"(3 * XREG)
                 : "memory");
}
__device__ __forceinline__ void cp_async_arrive(uint32_t bar) {
    asm volatile("cp.async.mbarrier.arrive.noinc.shared::cta.b64 [%0];" ::"r"(bar) : "memory");
}
__device__ __forceinline__ void mbar_init(uint32_t bar, uint32_t count) {
    asm volatile("mbarrier.init.shared::cta.b64 [%0], %1;" ::"r"(bar), "r"(count) : "memory");
}
__device__ __forceinline__ bool mbar_try(uint32_t bar, uint32_t parity) {
    uint32_t ok;
    asm volatile("{\n\t.reg .pred p;\n\tmbarrier.try_wait.parity.shared::cta.b64 p, [%1], %2;\n\tselp.u32 %0, 1, 0, p;\n\t}"
                 : "=r"(ok) : "r"(bar), "r"(parity) : "memory");
    return ok;
}
__device__ __forceinline__ void mbar_wait(uint32_t bar, uint32_t parity) {
    if (mbar_try(bar, parity)) return;
#pragma unroll 1
    for (int it = 0; it < SPIN_LIMIT; it++)
        if (mbar_try(bar, parity)) return;
    __trap();
}
__device__ __forceinline__ uint32_t clock_lo() {
    uint32_t v;
    asm volatile("mov.u32 %0, %%clock;" : "=r"(v));
    return v;
}
__device__ __forceinline__ uint32_t global_ticks() {
    uint32_t v;
    asm volatile("mov.u32 %0, %%globaltimer_lo;" : "=r"(v));
    return v >> 5;
}

#define TBL(snd, own) ((snd) * 144 + (own))
__device__ __forceinline__ void prefetch_line(const void* p) { asm volatile("prefetch.global.L2 [%0];" ::"l"(p)); }
__device__ __forceinline__ void prefetch_bulk(const void* p, uint32_t bytes) {
    asm volatile("{\n\t.reg .pred P;\n\telect.sync _|P, 0xffffffff;\n\t@P cp.async.bulk.prefetch.L2.global [%0], %1;\n\t}"
                 ::"l"(p), "r"(bytes) : "memory");
}
__device__ __forceinline__ uint4 ld_entry(const uint4* p) {
    uint4 e;
    asm volatile("ld.relaxed.gpu.global.v4.u32 {%0,%1,%2,%3}, [%4];" : "=r"(e.x), "=r"(e.y), "=r"(e.z), "=r"(e.w) : "l"(p) : "memory");
    return e;
}
__device__ __forceinline__ uint4 wait_entry(const uint4* p, uint4 e, uint32_t tag) {
    int it = 0;
    while (((e.y ^ tag) & TAGM) != 0u) {
        if (++it > SPIN_LIMIT) __trap();
        e = ld_entry(p);
    }
    return e;
}
__device__ __forceinline__ uint4 ldg128_if(bool p, const void* a, uint32_t other) {
    uint4 v = make_uint4(other, other, other, other);
    asm volatile("{\n\t.reg .pred P;\n\tsetp.ne.u32 P, %5, 0;\n\t@P ld.global.nc.L1::no_allocate.v4.u32 {%0,%1,%2,%3}, [%4];\n\t}"
                 : "+r"(v.x), "+r"(v.y), "+r"(v.z), "+r"(v.w) : "l"(a), "r"((uint32_t)p));
    return v;
}
__device__ __forceinline__ uint32_t ldg_u16(const void* p) {
    unsigned short v;
    asm volatile("ld.global.nc.u16 %0, [%1];" : "=h"(v) : "l"(p));
    return v;
}
__device__ __forceinline__ void stg64_if(bool p, void* a, uint32_t v0, uint32_t v1) {
    asm volatile("{\n\t.reg .pred P;\n\tsetp.ne.u32 P, %0, 0;\n\t@P st.global.v2.u32 [%1], {%2,%3};\n\t}"
                 ::"r"((uint32_t)p), "l"(a), "r"(v0), "r"(v1) : "memory");
}
__device__ __forceinline__ float bf_lo(uint32_t v) { return __uint_as_float(v << 16); }
__device__ __forceinline__ float bf_hi(uint32_t v) { return __uint_as_float(v & 0xffff0000u); }

#define F8(o) "+f"(d[o]), "+f"(d[o + 1]), "+f"(d[o + 2]), "+f"(d[o + 3]), "+f"(d[o + 4]), "+f"(d[o + 5]), "+f"(d[o + 6]), "+f"(d[o + 7])
template <int T>
__device__ __forceinline__ void wgmma_tiles(float (&d)[40], uint64_t a, uint64_t b, uint32_t acc) {
    if constexpr (T == 1)
        asm volatile("{\n\t.reg .pred P;\n\tsetp.ne.u32 P, %10, 0;\n\twgmma.mma_async.sync.aligned.m64n16k16.f32.bf16.bf16 "
                     "{%0,%1,%2,%3,%4,%5,%6,%7}, "
                     "%8, %9, P, 1, 1, 1, 0;\n\t}"
                     : F8(0) : "l"(a), "l"(b), "r"(acc));
    if constexpr (T == 2)
        asm volatile("{\n\t.reg .pred P;\n\tsetp.ne.u32 P, %18, 0;\n\twgmma.mma_async.sync.aligned.m64n32k16.f32.bf16.bf16 "
                     "{%0,%1,%2,%3,%4,%5,%6,%7,%8,%9,%10,%11,%12,%13,%14,%15}, "
                     "%16, %17, P, 1, 1, 1, 0;\n\t}"
                     : F8(0), F8(8) : "l"(a), "l"(b), "r"(acc));
    if constexpr (T == 3)
        asm volatile("{\n\t.reg .pred P;\n\tsetp.ne.u32 P, %26, 0;\n\twgmma.mma_async.sync.aligned.m64n48k16.f32.bf16.bf16 "
                     "{%0,%1,%2,%3,%4,%5,%6,%7,%8,%9,%10,%11,%12,%13,%14,%15,%16,%17,%18,%19,%20,%21,%22,%23}, "
                     "%24, %25, P, 1, 1, 1, 0;\n\t}"
                     : F8(0), F8(8), F8(16) : "l"(a), "l"(b), "r"(acc));
    if constexpr (T == 4)
        asm volatile("{\n\t.reg .pred P;\n\tsetp.ne.u32 P, %34, 0;\n\twgmma.mma_async.sync.aligned.m64n64k16.f32.bf16.bf16 "
                     "{%0,%1,%2,%3,%4,%5,%6,%7,%8,%9,%10,%11,%12,%13,%14,%15,%16,%17,%18,%19,%20,%21,%22,%23,%24,%25,%26,%27,%28,%29,%30,%31}, "
                     "%32, %33, P, 1, 1, 1, 0;\n\t}"
                     : F8(0), F8(8), F8(16), F8(24) : "l"(a), "l"(b), "r"(acc));
    if constexpr (T == 5)
        asm volatile("{\n\t.reg .pred P;\n\tsetp.ne.u32 P, %42, 0;\n\twgmma.mma_async.sync.aligned.m64n80k16.f32.bf16.bf16 "
                     "{%0,%1,%2,%3,%4,%5,%6,%7,%8,%9,%10,%11,%12,%13,%14,%15,%16,%17,%18,%19,%20,%21,%22,%23,%24,%25,%26,%27,%28,%29,%30,%31,%32,%33,%34,%35,%36,%37,%38,%39}, "
                     "%40, %41, P, 1, 1, 1, 0;\n\t}"
                     : F8(0), F8(8), F8(16), F8(24), F8(32) : "l"(a), "l"(b), "r"(acc));
}
template <int T, int O>
__device__ __forceinline__ void mix_tiles(float (&d)[40], uint64_t da, uint64_t db) {
    asm volatile("wgmma.fence.sync.aligned;" ::: "memory");
#pragma unroll
    for (int ks = 0; ks < 8; ks++) wgmma_tiles<T>(d, da + ks * 128, db + O * 128 + (ks >> 1) * (XREG / 16) + (ks & 1) * 16, ks);
    asm volatile("wgmma.commit_group.sync.aligned;" ::: "memory");
}
template <int T, int O, int PENDING>
__device__ __forceinline__ void store_tiles(float (&d)[40], uint32_t* op, int left, uint32_t bar) {
    asm volatile("wgmma.wait_group.sync.aligned %0;" ::"n"(PENDING) : "memory");
#pragma unroll
    for (int i = 0; i < 8 * T; i++) asm volatile("" : "+f"(d[i])::"memory");
#pragma unroll
    for (int k = 0; k < T; k++) {
        const int n = 16 * ((O + k) % 5) + (O + k) / 5;
#pragma unroll
        for (int u = 0; u < 2; u++)
            stg64_if(n < left, op + n * 256 + u * 16, pack_bf16(d[8 * k + 2 * u], d[8 * k + 2 * u + 1]),
                     pack_bf16(d[8 * k + 4 + 2 * u], d[8 * k + 4 + 2 * u + 1]));
    }
    if (PENDING) asm volatile("bar.sync %0, 128;" ::"r"(bar) : "memory");
}

__device__ __noinline__ void slow_cta(unsigned char* smem, const char* x, const char* ef, const __nv_bfloat16* w_rad,
                                      const __nv_bfloat16* cg, const __nv_bfloat16* w_mix, uint32_t* out, int node0, int Sc,
                                      uint32_t tag) {
    float* agg = reinterpret_cast<float*>(smem);
    Misc& ms = *reinterpret_cast<Misc*>(smem + MISC_OFF);
    const int tid = threadIdx.x, lane = tid & 31, warp = tid >> 5;
#pragma unroll 1
    for (int i = tid; i < Sc * 512; i += NT) agg[i] = 0.f;
    if (tid < (int)gridDim.x) {
        uint32_t v;
        asm volatile("ld.relaxed.gpu.global.u32 %0, [%1];" : "=r"(v) : "l"(&g_table[TBL(tid, blockIdx.x)]) : "memory");
        ms.rseg[tid] = v;
    }
    __syncthreads();
    uint2 wr[16];
#pragma unroll
    for (int f = 0; f < 16; f++) wr[f] = *reinterpret_cast<const uint2*>(w_rad + f * 128 + 4 * lane);
    float cgl[4];
#pragma unroll
    for (int f = 0; f < 4; f++) cgl[f] = __bfloat162float(cg[((lane >> 2) & 3) * 16 + f * 4 + (lane & 3)]);
    for (int s = 0; s < (int)gridDim.x; s++) {
        const int cn = ms.rseg[s] & 0xfffu;
        const uint4* p = g_staged + s * EPC_MAX + ((ms.rseg[s] >> 12) & 0xfffu);
        for (int i0 = 0; i0 < cn; i0 += 32) {
          uint4 el = make_uint4(0u, 0u, 0u, 0u);
          int dll = -1;
          if (i0 + lane < cn) {
              el = wait_entry(p + i0 + lane, ld_entry(p + i0 + lane), tag);
              const uint32_t tile = (el.x >> 19) / NB;
              dll = (int)((tile >> 2) * 16 + ((el.y >> 25) & 3u) * 4 + (tile & 3));
          }
          for (uint32_t m = __ballot_sync(0xffffffffu, dll >= 0 && dll % NWARP == warp); m; m &= m - 1) {
            const int from = __ffs(m) - 1;
            const uint4 e = make_uint4(__shfl_sync(0xffffffffu, el.x, from), __shfl_sync(0xffffffffu, el.y, from),
                                       __shfl_sync(0xffffffffu, el.z, from), __shfl_sync(0xffffffffu, el.w, from));
            float* ap = agg + __shfl_sync(0xffffffffu, dll, from) * 512 + lane;
            const uint4* xp = reinterpret_cast<const uint4*>(x + (size_t)(e.x & 0x1fff8u) * 128 + lane * 32);
            const uint4* fp = reinterpret_cast<const uint4*>(ef + (e.y & 0x1ffffe0u));
            const uint4 xa = xp[0], xb = xp[1], fa = fp[0], fb = fp[1];
            const uint32_t fv[8] = {fa.x, fa.y, fa.z, fa.w, fb.x, fb.y, fb.z, fb.w};
            const uint32_t xv[8] = {xa.x, xa.y, xa.z, xa.w, xb.x, xb.y, xb.z, xb.w};
            float h[4] = {0.f, 0.f, 0.f, 0.f};
#pragma unroll
            for (int f = 0; f < 16; f++) {
                const float v = (f & 1) ? bf_hi(fv[f >> 1]) : bf_lo(fv[f >> 1]);
                h[0] += v * bf_lo(wr[f].x); h[1] += v * bf_hi(wr[f].x); h[2] += v * bf_lo(wr[f].y); h[3] += v * bf_hi(wr[f].y);
            }
            const float wl = bf_lo(e.z) * cgl[0] + bf_hi(e.z) * cgl[1] + bf_lo(e.w) * cgl[2] + bf_hi(e.w) * cgl[3];
#pragma unroll
            for (int k = 0; k < 4; k++) h[k] = __fdividef(h[k], 1.f + __expf(-h[k]));
#pragma unroll
            for (int o = 0; o < 4; o++) {
                const float w0 = __shfl_sync(0xffffffffu, wl, o), w1 = __shfl_sync(0xffffffffu, wl, 4 + o);
                const float w2 = __shfl_sync(0xffffffffu, wl, 8 + o), w3 = __shfl_sync(0xffffffffu, wl, 12 + o);
#pragma unroll
                for (int k = 0; k < 4; k++) {
                    const float tp = bf_lo(xv[2 * k]) * w0 + bf_hi(xv[2 * k]) * w1 + bf_lo(xv[2 * k + 1]) * w2 + bf_hi(xv[2 * k + 1]) * w3;
                    ap[(k * 4 + o) * 32] += tp * h[k];
                }
            }
          }
        }
    }
    __syncthreads();
    for (int n = tid >> 7; n < Sc; n += NT / 128) {
        const int d = tid & 127;
        float o[4] = {0.f, 0.f, 0.f, 0.f};
#pragma unroll 4
        for (int c = 0; c < 128; c++) {
            const float* a = agg + n * 512 + (c & 3) * 128 + (c >> 2);
            const float w = __bfloat162float(w_mix[c * 128 + d]);
            o[0] += a[0] * w; o[1] += a[32] * w; o[2] += a[64] * w; o[3] += a[96] * w;
        }
        *reinterpret_cast<uint2*>(out + (size_t)(node0 + n) * 256 + d * 2) = make_uint2(pack_bf16(o[0], o[1]), pack_bf16(o[2], o[3]));
    }
}

__global__ void __launch_bounds__(NT, 1)
tfn_kernel(const __grid_constant__ CUtensorMap xmap, const char* __restrict__ x, const int* __restrict__ src,
           const int* __restrict__ dst, const uint2* __restrict__ Y, const char* __restrict__ ef,
           const __nv_bfloat16* __restrict__ w_rad, const __nv_bfloat16* __restrict__ cg,
           const __nv_bfloat16* __restrict__ w_mix, uint32_t* __restrict__ out, int N, int E, int S, int EPC,
           uint32_t magicS, uint32_t magicB, uint32_t zero, uint32_t pace, int lead, uint32_t pfb, uint32_t curve) {
    extern __shared__ __align__(1024) unsigned char smem[];
    Misc& ms = *reinterpret_cast<Misc*>(smem + MISC_OFF);
    int* const cnt = reinterpret_cast<int*>(smem + CNT_OFF);
    int* const start = reinterpret_cast<int*>(smem + START_OFF);
    uint32_t* const bcnt = reinterpret_cast<uint32_t*>(smem + BCNT_OFF);
    uint32_t* const bcum = reinterpret_cast<uint32_t*>(smem + BCUM_OFF);
    uint32_t* const gi = reinterpret_cast<uint32_t*>(smem + GI_OFF);
    const int tid = threadIdx.x;
    const int lane = tid & 31, warp = __shfl_sync(0xffffffffu, tid >> 5, 0);
    const int c = blockIdx.x;
    const int numCTA = gridDim.x;
    const int node0 = c * S;
    const int Sc = max(0, min(S, N - node0));
    const uint32_t sb = (uint32_t)__cvta_generic_to_shared(smem);

    const int e0[2] = {(warp * numCTA + c) * 128 + 4 * lane, ((warp + NWARP) * numCTA + c) * 128 + 4 * lane};
    int d8[8], s8[8];
#pragma unroll
    for (int h = 0; h < 2; h++) {
        const uint4 v = ldg128_if(e0[h] + 3 < E, dst + e0[h], 0xffffffffu);
        d8[4 * h] = (int)v.x; d8[4 * h + 1] = (int)v.y; d8[4 * h + 2] = (int)v.z; d8[4 * h + 3] = (int)v.w;
    }
#pragma unroll
    for (int h = 0; h < 2; h++) {
        const uint4 v = ldg128_if(e0[h] + 3 < E, src + e0[h], 0u);
        s8[4 * h] = (int)v.x; s8[4 * h + 1] = (int)v.y; s8[4 * h + 2] = (int)v.z; s8[4 * h + 3] = (int)v.w;
    }
    if (E & 3) {
#pragma unroll
        for (int k = 0; k < 8; k++) {
            const int i = e0[k >> 2] + (k & 3);
            if (i >= (E & ~3) && i < E) { d8[k] = __ldg(dst + i); s8[k] = __ldg(src + i); }
        }
    }
    if (tid == NT - 64) asm volatile("prefetch.tensormap [%0];" ::"l"(&xmap) : "memory");
    uint32_t ep0 = 0;
    if (tid == NT - 1) asm volatile("ld.relaxed.gpu.global.u32 %0, [%1];" : "=r"(ep0) : "l"(&g_epoch[c]) : "memory");
    uint32_t cgr[4] = {0u, 0u, 0u, 0u};
    if (warp >= 8 && (lane & 3) < 2) {
        const unsigned short* cu = reinterpret_cast<const unsigned short*>(cg) + ((lane >> 2) & 3) * 16 + (lane & 3) * 8 + (lane >> 4);
        cgr[0] = ldg_u16(cu); cgr[1] = ldg_u16(cu + 4); cgr[2] = ldg_u16(cu + 2); cgr[3] = ldg_u16(cu + 6);
    }
    if (warp == 7) {
        for (int i = c + lane * numCTA; i < 32 + 256; i += 32 * numCTA)
            prefetch_line(i < 32 ? (const char*)w_rad + i * 128 : (const char*)w_mix + (i - 32) * 128);
    }
    if (tid < MAXCTA) cnt[tid] = 0;
#pragma unroll
    for (int k = 0; k < 5; k++) bcnt[tid + k * NT] = 0u;
    if (tid < 224) reinterpret_cast<uint2*>(smem + ZERO_OFF)[tid] = make_uint2(0u, 0u);
    if (tid >= 160 && tid < 320) {
        const int i = tid - 160;
        *reinterpret_cast<uint32_t*>(smem + AUX_OFF + (i >> 5) * AUX_ST + ((i >> 3) & 3) * AUX_GR + 512 + (i & 7) * 16) =
            (i >> 5) == NST - 1 ? (uint32_t)(1 - NST) << 24 : 1u << 24;
    }
    if (lane < NST && warp < 8) {
        const int k = warp >> 2;
        mbar_init(sb + AUX_OFF + lane * AUX_ST + (warp & 3) * AUX_GR + BAR_F0 + 16 * k, k == 0 ? F0_COUNT : 2u);
    }
    if (tid == 330) { mbar_init(sb + MISC_OFF + 16, 1); mbar_init(sb + MISC_OFF, 128); ms.node0 = node0; ms.Sc = Sc; ms.dmax = -32768; ms.ref = global_ticks(); }
    __syncthreads();
    const uint32_t cgb0 = cgr[0] | (cgr[1] << 16), cgb1 = cgr[2] | (cgr[3] << 16);
    uint2 y8[8];
#pragma unroll
    for (int h = 0; h < 4; h++) {
        const int i = e0[h >> 1] + 2 * (h & 1);
        const uint4 v = ldg128_if(i + 1 < E, Y + i, 0u);
        y8[2 * h] = make_uint2(v.x, v.y); y8[2 * h + 1] = make_uint2(v.z, v.w);
    }
    int bin[8], pos[8];
#pragma unroll
    for (int k = 0; k < 8; k++) {
        bin[k] = (int)__umulhi((uint32_t)d8[k], magicS);
        if (d8[k] >= 0) pos[k] = atomicAdd(&cnt[bin[k]], 1);
    }
    if (tid == NT - 1) {
        ms.epoch = ep0 + 1u;
        g_epoch[c] = ep0 + 1u;
    }
    __syncthreads();
    const uint32_t epoch = ms.epoch;
    if (warp < 5) {
        int pre = 0;
#pragma unroll
        for (int k = 0; k < 4; k++)
            if (k < warp) pre += cnt[lane + 32 * k];
        const int v = tid < numCTA ? cnt[tid] : 0;
        int incl = v;
#pragma unroll
        for (int o = 1; o < 32; o <<= 1) {
            int t_ = __shfl_up_sync(0xffffffffu, incl, o);
            if (lane >= o) incl += t_;
        }
        const int ex = __reduce_add_sync(0xffffffffu, pre) + incl - v;
        start[tid] = ex;
        if (tid < numCTA)
            asm volatile("st.relaxed.gpu.global.u32 [%0], %1;" ::"l"(g_table + TBL(c, tid)), "r"((epoch << 24) | (ex << 12) | v) : "memory");
    }
    const uint32_t tag = epoch & TAGM;
    uint32_t w0[8], w1[8];
#pragma unroll
    for (int k = 0; k < 8; k++) {
        const uint32_t dl = (uint32_t)(d8[k] - bin[k] * S);
        w0[k] = (((((dl >> 2) & 0x1cu) | (dl & 3u)) * NB + __umulhi((uint32_t)s8[k], magicB)) << 19) + (uint32_t)s8[k] * 8u;
        w1[k] = (((dl << 23) & 0x3e000000u) | (((dl << 28) & 0xc0000000u) ^ (dl << 31))) +
                ((uint32_t)e0[k >> 2] * 32u + tag + (k & 3) * 32);
    }
    __syncthreads();
    if (tid == 192)
        asm volatile("mbarrier.arrive.expect_tx.shared::cta.b64 _, [%2], 4096;\n\t"
                     "cp.async.bulk.shared::cluster.global.mbarrier::complete_tx::bytes [%0], [%1], 4096, [%2];"
                     ::"r"(sb + WR_OFF), "l"(w_rad), "r"(sb + MISC_OFF + 16) : "memory");
    const int ne = start[MAXCTA];
    if (E & 1) {
#pragma unroll
        for (int h = 0; h < 4; h++)
            if (e0[h >> 1] + 2 * (h & 1) + 1 == E) y8[2 * h] = __ldg(Y + E - 1);
    }
#pragma unroll
    for (int k = 0; k < 8; k++)
        if (d8[k] >= 0) pos[k] += start[bin[k]];
#pragma unroll
    for (int k = 0; k < 8; k++)
        if (d8[k] >= 0) reinterpret_cast<uint4*>(smem)[pos[k]] = make_uint4(w0[k], w1[k], y8[k].x, y8[k].y);
    asm volatile("fence.proxy.async.shared::cta;" ::: "memory");
    __syncthreads();
    if (tid == NT - 32 && ne > 0) {
        asm volatile("cp.async.bulk.global.shared::cta.bulk_group [%0], [%1], %2;" ::"l"(g_staged + (size_t)c * EPC_MAX),
                     "r"(sb), "r"(ne * 16) : "memory");
        asm volatile("cp.async.bulk.commit_group;" ::: "memory");
    }

    const int g = lane >> 2, t = lane & 3;
    uint32_t wr[4][4];
    if (tid == 64 && (uint32_t)(c + 1) * 4u * PFA * pfb <= (uint32_t)N * 1024u)
        asm volatile("cp.async.bulk.prefetch.L2.global [%0], %1;" ::"l"(x + (size_t)c * 4u * PFA * pfb), "r"(4u * PFA * pfb) : "memory");
    auto uni = [&](uint32_t v) { return __shfl_sync(0xffffffffu, v + (lane & zero), 0); };
    auto keep = [&](uint32_t v) { return __shfl_sync(0xffffffffu, v, lane); };
    const int pgrp = (warp + 2) & 3;
    uint32_t s0, maplo, maphi, e_l, h_l, f_l, w_l, eflo, efhi, fsel, bytes, pc, cu, tbase;
    auto constants = [&]() {
        s0 = uni(sb);
        const uint64_t map0 = reinterpret_cast<uint64_t>(&xmap), ef0 = reinterpret_cast<uint64_t>(ef) + t * 8;
        maphi = uni((uint32_t)(map0 >> 32)); maplo = uni((uint32_t)(map0 & 0xffffffffu));
        e_l = keep(SE_OFF - SY_OFF + (4 * (g & 1) + (g >> 1)) * 4);
        h_l = keep(sb + SH_OFF + pgrp * GCAP * 8 - 64 + g * 8 + (t & 1) * 4);
        f_l = keep(sb + AUX_OFF + pgrp * AUX_GR + 512 + (g >> 1) * 32 + (t & 1) * 16 + (~g & 1));
        w_l = keep(sb + AUX_OFF + pgrp * AUX_GR + lane * 8);
        efhi = keep((uint32_t)(ef0 >> 32) + (lane & zero)); eflo = keep((uint32_t)(ef0 & 0xffffffffu));
        fsel = keep(g & 1 ? 7 : 3);
        bytes = keep(lane == 0 ? OCT_BYTES : 0u);
        pc = uni(pace); cu = uni(curve);
        tbase = clock_lo() + (uint32_t)((int)(short)(ms.ref - global_ticks()) * 63 + lead);
    };

    uint4 ent[RND];
    uint32_t rk[RND];
    int tot = 0;
    if (warp == NWARP - 1) {
        asm volatile("cp.async.bulk.wait_group 0;" ::: "memory");
        __syncwarp();
        const uint32_t w = (epoch << 16) | (global_ticks() & 0xffffu);
#pragma unroll
        for (int k = 0; k < 5; k++)
            asm volatile("{\n\t.reg .pred P;\n\tsetp.lt.s32 P, %0, %1;\n\t@P st.relaxed.gpu.global.u32 [%2+4], %3;\n\t}"
                         ::"r"(lane + 32 * k), "r"(numCTA), "l"(g_table + TBL(c, lane) + 32 * k), "r"(w) : "memory");
    } else {
        const bool mine = warp + NCOL * lane < numCTA;
        const uint2* tp = g_table + TBL(warp + NCOL * lane, c);
        const uint4* gp[RND];
        auto poll = [&](const uint32_t* p, uint32_t v, int sh) {
            int it = 0;
            do {
                if (mine) asm volatile("ld.relaxed.gpu.global.u32 %0, [%1];" : "=r"(v) : "l"(p) : "memory");
                if (++it > SPIN_LIMIT) __trap();
            } while (!__all_sync(0xffffffffu, ((v ^ (epoch << sh)) >> sh) == 0u));
            return v;
        };
        const uint32_t sv = poll(&tp->x, epoch << 24, 24);
        int incl = (int)(sv & 0xfffu);
#pragma unroll
        for (int o = 1; o < 16; o <<= 1) {
            int t_ = __shfl_up_sync(0xffffffffu, incl, o);
            if (lane >= o) incl += t_;
        }
        tot = __shfl_sync(0xffffffffu, incl, 15);
        const bool some = (sv & 0xfffu) != 0u;
        const uint32_t seg_b = sb + SEG_OFF + warp * 64;
        if (some)
            asm volatile("st.shared.u32 [%0], %1;" ::"r"(seg_b + 4 * __popc(__ballot_sync(__activemask(), true) & ((1u << lane) - 1u))),
                         "r"((warp + NCOL * lane) * EPC_MAX + (int)((sv >> 12) & 0xfffu) - incl + (int)(sv & 0xfffu)) : "memory");
        __syncwarp();
        if (!some) incl = -1;
        const uint32_t le = (2u << lane) - 1u;
        uint32_t sg = seg_b;
#pragma unroll
        for (int r = 0; r < RND; r++) {
            uint32_t bit;
            asm("shl.b32 %0, 1, %1;" : "=r"(bit) : "r"(incl - 32 * r));
            const uint32_t ends = __reduce_or_sync(0xffffffffu, bit);
            gp[r] = g_staged + (lane + 32 * r + (int)lds32(sg + 4 * __popc(ends & le)));
            sg += 4 * __popc(ends);
            ent[r].y = tag;
        }
        if (warp < 8) {
            mbar_wait(sb + MISC_OFF + 16, 0);
#pragma unroll
            for (int j = 0; j < 4; j++) {
                const int dj = (j & 1) + 4 * (j >> 1);
                const uint32_t p = sb + WR_OFF + t * 4 * 256 + 32 * (2 * ((warp >> 2) & 1) + dj) + 4 * (g ^ dj);
#pragma unroll
                for (int i = 0; i < 4; i++) wr[j][i] = lds32(p + i * 256);
            }
#pragma unroll
            for (int j = 0; j < 4; j++) {
                uint32_t h[4];
#pragma unroll
                for (int i = 0; i < 4; i++) h[i] = half_bf16x2(wr[j][i]);
                wr[j][0] = __byte_perm(h[0], h[1], 0x5410);
                wr[j][1] = __byte_perm(h[0], h[1], 0x7632);
                wr[j][2] = __byte_perm(h[2], h[3], 0x5410);
                wr[j][3] = __byte_perm(h[2], h[3], 0x7632);
            }
        }
        const uint32_t ts = poll(&tp->y, (epoch << 16) | (ms.ref & 0xffffu), 16);
#pragma unroll
        for (int r = 0; r < RND; r++)
            if (lane + 32 * r < tot) ent[r] = ld_entry(gp[r]);
        const int dm = __reduce_max_sync(0xffffffffu, (int)(short)(ts - ms.ref));
        if (lane == 0) atomicMax(&ms.dmax, dm);
        uint32_t stale = 0;
#pragma unroll
        for (int r = 0; r < RND; r++) stale |= ent[r].y ^ tag;
        if (stale & TAGM) {
#pragma unroll
            for (int r = 0; r < RND; r++)
                if (lane + 32 * r < tot) ent[r] = wait_entry(gp[r], ent[r], tag);
        }
#pragma unroll
        for (int r = 0; r < RND; r++)
            if (lane + 32 * r < tot) rk[r] = atomicAdd(reinterpret_cast<uint32_t*>(smem + BCNT_OFF + (ent[r].x >> 17)), 1u);
    }
    constants();
    __syncthreads();
    bool over = tot > 32 * RND || S > SFAST;
    {
        const int grp = warp & 3, u = warp >> 2;
        uint32_t v[3], incl[3], lo[3], hi[3], tt[3];
#pragma unroll
        for (int p = 0; p < 3; p++) {
            uint32_t a[3];
#pragma unroll
            for (int i = 0; i < 3; i++) {
                a[i] = bcnt[(grp + 8 * p) * NB + 32 * i + lane];
                if (p < 2) a[i] += bcnt[(grp + 8 * p + 4) * NB + 32 * i + lane] << 16;
            }
            v[p] = u == 0 ? a[0] : (u == 1 ? a[1] : a[2]);
            incl[p] = v[p];
            lo[p] = __reduce_add_sync(0xffffffffu, u == 0 ? 0u : (u == 1 ? a[0] : a[0] + a[1]));
            tt[p] = __reduce_add_sync(0xffffffffu, a[0] + a[1] + a[2]);
        }
#pragma unroll
        for (int o = 1; o < 32; o <<= 1)
#pragma unroll
            for (int p = 0; p < 3; p++) {
                asm volatile("{\n\t.reg .pred P;\n\t.reg .b32 v;\n\tshfl.sync.up.b32 v|P, %0, %1, 0, 0xffffffff;\n\t@P add.u32 %0, %0, v;\n\t}"
                             : "+r"(incl[p]) : "r"(o));
            }
        uint32_t all = 0, nq = 0;
#pragma unroll
        for (int p = 0; p < 3; p++) {
            const uint32_t up = (tt[p] + 0x30003u) & 0xfffcfffcu;
            nq += up >> 2;
            tt[p] = up - tt[p];
            incl[p] += lo[p] + tt[p];
            v[p] = incl[p] - v[p];
            lo[p] = warp < 4 && lane == 0 ? 0u : ((v[p] + 0x10001u) >> 2) & 0x3fff3fffu;
            hi[p] = ((incl[p] + 0x10001u) >> 2) & 0x3fff3fffu;
            all += lo[p];
        }
        nq = (nq & 0xffffu) + (nq >> 16);
        uint32_t run = (all & 0xffffu) + (all >> 16) + (nq & 1u) + grp * (GCAP / 4), rel[5];
#pragma unroll
        for (int i = 0; i < 5; i++) {
            const uint32_t l = (i & 1) ? lo[i >> 1] >> 16 : lo[i >> 1] & 0xffffu, h = (i & 1) ? hi[i >> 1] >> 16 : hi[i >> 1] & 0xffffu;
            const uint32_t tb = (grp + 4 * i) * JCAP;
            bcum[(grp + 4 * i) * NB + 32 * u + lane] = ((i & 1) ? v[i >> 1] >> 16 : v[i >> 1] & 0xffffu) + 4 * tb;
            rel[i] = (run - l - tb) * 16u;
            if (l < h) { gi[tb + l] = rel[i]; gi[tb + h - 1] = rel[i]; }
            run += h - l;
        }
        if ((((hi[0] - lo[0] + 0x10001u) | (hi[1] - lo[1] + 0x10001u) | (hi[2] - lo[2] + 1u)) & 0xfffcfffcu) != 0u) {
#pragma unroll
            for (int i = 0; i < 5; i++) {
                const uint32_t l = (i & 1) ? lo[i >> 1] >> 16 : lo[i >> 1] & 0xffffu, h = (i & 1) ? hi[i >> 1] >> 16 : hi[i >> 1] & 0xffffu;
#pragma unroll 1
                for (uint32_t j = l; j < h; j++) gi[(grp + 4 * i) * JCAP + j] = rel[i];
            }
        }
        if (warp < 4 && lane == 0) ms.nq[grp] = (int)nq;
        over = over || 4 * nq + 20 > GCAP;
    }
    asm volatile("fence.proxy.async.shared::cta;" ::: "memory");
    const bool slow = __syncthreads_or(over);
    if (uni(slow) != 0u) {
        slow_cta(smem, x, ef, w_rad, cg, w_mix, out, node0, Sc, tag);
        return;
    }
    const uint32_t T0 = uni(tbase + ms.dmax * 63);
    int left = (int)uni((uint32_t)(ms.nq[pgrp] + 1) >> 1);
    {
        auto put = [&](bool ok, uint32_t p4, uint32_t y, uint32_t e) {
            asm volatile("{\n\t.reg .pred P;\n\tsetp.ne.u32 P, %0, 0;\n\t@P st.shared.u32 [%1+%4], %2;\n\t@P st.shared.u32 [%1+%5], %3;\n\t}"
                         ::"r"((uint32_t)ok), "r"(sb + p4), "r"(y), "r"(e), "n"(SY_OFF), "n"(SE_OFF) : "memory");
        };
        auto puty = [&](bool ok, uint32_t p4, uint32_t h0, uint32_t h1) {
            asm volatile("{\n\t.reg .pred P;\n\tsetp.ne.u32 P, %0, 0;\n\t@P st.shared.v2.u32 [%1+%4], {%2,%3};\n\t}"
                         ::"r"((uint32_t)ok), "r"(sb + 2 * p4), "r"(h0), "r"(h1), "n"(SH_OFF) : "memory");
        };
        auto place = [&](int r0, int r1) {
#pragma unroll
            for (int r = r0; r < r1; r++)
                if (lane + 32 * r < tot) rk[r] += *reinterpret_cast<const uint32_t*>(smem + BCUM_OFF + (ent[r].x >> 17));
#pragma unroll
            for (int r = r0; r < r1; r++)
                if (lane + 32 * r < tot) rk[r] = 4u * rk[r] + gi[rk[r] >> 2];
#pragma unroll
            for (int r = r0; r < r1; r++) put(lane + 32 * r < tot, rk[r], ent[r].x & 0x1ffffu, ent[r].y);
#pragma unroll
            for (int r = r0; r < r1; r++) puty(lane + 32 * r < tot, rk[r], ent[r].z, ent[r].w);
        };
        if (warp == NCOL) {
#pragma unroll
            for (int k = 0; k < 5; k++) {
                const uint32_t id = lane + 32 * k, py = ((id + 53 * c) & 127u) * 8u;
                if (k < 3) {
                    const uint32_t tile = min(id >> 2, 19u), c0 = bcum[tile * NB];
                    const bool ok = (id & 3) < (c0 & 3u) && id < 80;
                    const uint32_t p4 = gi[tile * JCAP] + (tile * JCAP * 4 + (id & 3)) * 4;
                    put(ok, p4, py, tile >> 2 << 27);
                    puty(ok, p4, 0u, 0u);
                } else {
                    const uint32_t i = id & 15, grp = (id >> 4) & 3, nq = ms.nq[grp];
                    const bool ok = i < 8 || (i < 12 && (nq & 1));
                    const uint32_t p4 = (grp * GCAP + (i < 8 ? 4 * ((nq + 1) & ~1u) + i : i - 8)) * 4;
                    put(ok, p4, py, i < 8 ? 6u << 27 : 0u);
                    puty(ok, p4, 0u, 0u);
                }
            }
        } else {
            place(0, RND0);
            if (tot > 32 * RND0) place(RND0, RND);
        }
    }
    __syncthreads();

    if (warp < 8) {
        asm volatile("setmaxnreg.inc.sync.aligned.u32 232;");
        const int half = warp >> 2, grp = (warp + half) & 3;
        const uint32_t az = __shfl_sync(0xffffffffu, sb + ZERO_OFF + (g >> 1) * 512 + t * 32 + (g & 1) * 16, lane);
        uint32_t sb2;
        asm volatile(
            "{\n"
            ".reg .f32 c<160>, h<16>, th<8>, fz;\n"
            ".reg .b32 x<16>, a<4>, r<4>, rd<8>, e<2>, p<80>, mt, xa, aa, an<4>, ab, ea, tmp, cnt, st, rl, rh, dum, du2;\n"
            ".reg .b16 lo, hi;\n"
            ".reg .pred pk, pm, pw, pe, pr, d0, d1, d2, d3, d4;\n"
            "mov.f32 fz, 0f00000000;\n"
            "mov.f32 c0, fz; mov.f32 c1, fz; mov.f32 c2, fz; mov.f32 c3, fz; mov.f32 c4, fz; mov.f32 c5, fz; mov.f32 c6, fz; mov.f32 c7, fz;\n"
            "mov.f32 c8, fz; mov.f32 c9, fz; mov.f32 c10, fz; mov.f32 c11, fz; mov.f32 c12, fz; mov.f32 c13, fz; mov.f32 c14, fz; mov.f32 c15, fz;\n"
            "mov.f32 c16, fz; mov.f32 c17, fz; mov.f32 c18, fz; mov.f32 c19, fz; mov.f32 c20, fz; mov.f32 c21, fz; mov.f32 c22, fz; mov.f32 c23, fz;\n"
            "mov.f32 c24, fz; mov.f32 c25, fz; mov.f32 c26, fz; mov.f32 c27, fz; mov.f32 c28, fz; mov.f32 c29, fz; mov.f32 c30, fz; mov.f32 c31, fz;\n"
            "mov.f32 c32, fz; mov.f32 c33, fz; mov.f32 c34, fz; mov.f32 c35, fz; mov.f32 c36, fz; mov.f32 c37, fz; mov.f32 c38, fz; mov.f32 c39, fz;\n"
            "mov.f32 c40, fz; mov.f32 c41, fz; mov.f32 c42, fz; mov.f32 c43, fz; mov.f32 c44, fz; mov.f32 c45, fz; mov.f32 c46, fz; mov.f32 c47, fz;\n"
            "mov.f32 c48, fz; mov.f32 c49, fz; mov.f32 c50, fz; mov.f32 c51, fz; mov.f32 c52, fz; mov.f32 c53, fz; mov.f32 c54, fz; mov.f32 c55, fz;\n"
            "mov.f32 c56, fz; mov.f32 c57, fz; mov.f32 c58, fz; mov.f32 c59, fz; mov.f32 c60, fz; mov.f32 c61, fz; mov.f32 c62, fz; mov.f32 c63, fz;\n"
            "mov.f32 c64, fz; mov.f32 c65, fz; mov.f32 c66, fz; mov.f32 c67, fz; mov.f32 c68, fz; mov.f32 c69, fz; mov.f32 c70, fz; mov.f32 c71, fz;\n"
            "mov.f32 c72, fz; mov.f32 c73, fz; mov.f32 c74, fz; mov.f32 c75, fz; mov.f32 c76, fz; mov.f32 c77, fz; mov.f32 c78, fz; mov.f32 c79, fz;\n"
            "mov.f32 c80, fz; mov.f32 c81, fz; mov.f32 c82, fz; mov.f32 c83, fz; mov.f32 c84, fz; mov.f32 c85, fz; mov.f32 c86, fz; mov.f32 c87, fz;\n"
            "mov.f32 c88, fz; mov.f32 c89, fz; mov.f32 c90, fz; mov.f32 c91, fz; mov.f32 c92, fz; mov.f32 c93, fz; mov.f32 c94, fz; mov.f32 c95, fz;\n"
            "mov.f32 c96, fz; mov.f32 c97, fz; mov.f32 c98, fz; mov.f32 c99, fz; mov.f32 c100, fz; mov.f32 c101, fz; mov.f32 c102, fz; mov.f32 c103, fz;\n"
            "mov.f32 c104, fz; mov.f32 c105, fz; mov.f32 c106, fz; mov.f32 c107, fz; mov.f32 c108, fz; mov.f32 c109, fz; mov.f32 c110, fz; mov.f32 c111, fz;\n"
            "mov.f32 c112, fz; mov.f32 c113, fz; mov.f32 c114, fz; mov.f32 c115, fz; mov.f32 c116, fz; mov.f32 c117, fz; mov.f32 c118, fz; mov.f32 c119, fz;\n"
            "mov.f32 c120, fz; mov.f32 c121, fz; mov.f32 c122, fz; mov.f32 c123, fz; mov.f32 c124, fz; mov.f32 c125, fz; mov.f32 c126, fz; mov.f32 c127, fz;\n"
            "mov.f32 c128, fz; mov.f32 c129, fz; mov.f32 c130, fz; mov.f32 c131, fz; mov.f32 c132, fz; mov.f32 c133, fz; mov.f32 c134, fz; mov.f32 c135, fz;\n"
            "mov.f32 c136, fz; mov.f32 c137, fz; mov.f32 c138, fz; mov.f32 c139, fz; mov.f32 c140, fz; mov.f32 c141, fz; mov.f32 c142, fz; mov.f32 c143, fz;\n"
            "mov.f32 c144, fz; mov.f32 c145, fz; mov.f32 c146, fz; mov.f32 c147, fz; mov.f32 c148, fz; mov.f32 c149, fz; mov.f32 c150, fz; mov.f32 c151, fz;\n"
            "mov.f32 c152, fz; mov.f32 c153, fz; mov.f32 c154, fz; mov.f32 c155, fz; mov.f32 c156, fz; mov.f32 c157, fz; mov.f32 c158, fz; mov.f32 c159, fz;\n"
            "mov.b32 x0, 0; mov.b32 x1, 0; mov.b32 x2, 0; mov.b32 x3, 0; mov.b32 x4, 0; mov.b32 x5, 0; mov.b32 x6, 0; mov.b32 x7, 0; mov.b32 x8, 0; mov.b32 x9, 0; mov.b32 x10, 0; mov.b32 x11, 0; mov.b32 x12, 0; mov.b32 x13, 0; mov.b32 x14, 0; mov.b32 x15, 0;\n"
            "mov.b32 a0, 0; mov.b32 a1, 0; mov.b32 a2, 0; mov.b32 a3, 0;\n"
            "elect.sync _|pe, 0xffffffff;\n"
            "mov.pred pr, pe;\n"
            "mov.b32 xa, %1; mov.b32 aa, %2; mov.b32 ea, %4;\n"
            "mov.u32 cnt, 0; and.b32 tmp, aa, 0xffffff80;\n"
            "S0L: mbarrier.try_wait.parity.shared::cta.b64 pw, [tmp+520], 0; @pw bra.uni S0D;\n"
            "add.u32 cnt, cnt, 1; setp.lt.u32 pk, cnt, 1000000; @pk bra.uni S0L; trap;\n"
            "S0D:\n"
            "ld.shared.v2.u32 {e0,e1}, [ea]; ld.shared.u32 mt, [aa+512];\n"
            "mma.sync.aligned.m16n8k16.row.col.f32.bf16.bf16.f32 {h0,h1,h2,h3}, {%7,%8,%9,%10}, {e0,e1}, {fz,fz,fz,fz};\n"
            "mma.sync.aligned.m16n8k16.row.col.f32.bf16.bf16.f32 {h4,h5,h6,h7}, {%11,%12,%13,%14}, {e0,e1}, {fz,fz,fz,fz};\n"
            "mma.sync.aligned.m16n8k16.row.col.f32.bf16.bf16.f32 {h8,h9,h10,h11}, {%15,%16,%17,%18}, {e0,e1}, {fz,fz,fz,fz};\n"
            "mma.sync.aligned.m16n8k16.row.col.f32.bf16.bf16.f32 {h12,h13,h14,h15}, {%19,%20,%21,%22}, {e0,e1}, {fz,fz,fz,fz};\n"
            "or.b32 a0, e0, mt; and.b32 a0, a0, %5;\n"
            "add.u32 xa, xa, 2048; add.u32 aa, aa, 2560; mov.u32 st, 1;\n"
            "mov.u32 cnt, 0; and.b32 tmp, aa, 0xffffff80;\n"
            "S1L: mbarrier.try_wait.parity.shared::cta.b64 pw, [tmp+520], 0; @pw bra.uni S1D;\n"
            "add.u32 cnt, cnt, 1; setp.lt.u32 pk, cnt, 1000000; @pk bra.uni S1L; trap;\n"
            "S1D:\n"
            "B0_0:\n"
            "xor.b32 tmp, mt, %3; and.b32 tmp, tmp, 1536; setp.eq.u32 pm, tmp, 0; selp.b32 ab, aa, %3, pm;\n"
            "and.b32 tmp, mt, 2048; setp.ne.u32 d0, tmp, 0; and.b32 tmp, mt, 4096; setp.ne.u32 d1, tmp, 0; and.b32 tmp, mt, 8192; setp.ne.u32 d2, tmp, 0;\n"
            "mad.lo.u32 cnt, a0, %5, ea; mad.lo.s32 ea, st, 2560, ea;\n"
            "ld.shared.u32 mt, [aa+512];\n"
            "mma.sync.aligned.m16n8k16.row.col.f32.bf16.bf16.f32 {c0,c1,c2,c3}, {a0,a1,a2,a3}, {x0,x1}, {c0,c1,c2,c3};\n"
            "mma.sync.aligned.m16n8k16.row.col.f32.bf16.bf16.f32 {c4,c5,c6,c7}, {a0,a1,a2,a3}, {x2,x3}, {c4,c5,c6,c7};\n"
            "ld.shared.v4.u32 {x0,x1,x2,x3}, [xa+0];\n"
            "tanh.approx.f32 th0, h0;\n"
            "tanh.approx.f32 th1, h2;\n"
            "fma.rn.f32 th0, h0, th0, h0;\n"
            "fma.rn.f32 th1, h2, th1, h2;\n"
            "cvt.rn.bf16x2.f32 r0, th1, th0;\n"
            "mma.sync.aligned.m16n8k16.row.col.f32.bf16.bf16.f32 {c8,c9,c10,c11}, {a0,a1,a2,a3}, {x4,x5}, {c8,c9,c10,c11};\n"
            "mma.sync.aligned.m16n8k16.row.col.f32.bf16.bf16.f32 {c12,c13,c14,c15}, {a0,a1,a2,a3}, {x6,x7}, {c12,c13,c14,c15};\n"
            "ld.shared.v4.u32 {x4,x5,x6,x7}, [xa+128];\n"
            "tanh.approx.f32 th2, h4;\n"
            "tanh.approx.f32 th3, h6;\n"
            "fma.rn.f32 th2, h4, th2, h4;\n"
            "fma.rn.f32 th3, h6, th3, h6;\n"
            "cvt.rn.bf16x2.f32 r1, th3, th2;\n"
            "mma.sync.aligned.m16n8k16.row.col.f32.bf16.bf16.f32 {c16,c17,c18,c19}, {a0,a1,a2,a3}, {x8,x9}, {c16,c17,c18,c19};\n"
            "mma.sync.aligned.m16n8k16.row.col.f32.bf16.bf16.f32 {c20,c21,c22,c23}, {a0,a1,a2,a3}, {x10,x11}, {c20,c21,c22,c23};\n"
            "ld.shared.v4.u32 {x8,x9,x10,x11}, [xa+512];\n"
            "tanh.approx.f32 th4, h8;\n"
            "tanh.approx.f32 th5, h10;\n"
            "fma.rn.f32 th4, h8, th4, h8;\n"
            "fma.rn.f32 th5, h10, th5, h10;\n"
            "cvt.rn.bf16x2.f32 r2, th5, th4;\n"
            "mma.sync.aligned.m16n8k16.row.col.f32.bf16.bf16.f32 {c24,c25,c26,c27}, {a0,a1,a2,a3}, {x12,x13}, {c24,c25,c26,c27};\n"
            "mma.sync.aligned.m16n8k16.row.col.f32.bf16.bf16.f32 {c28,c29,c30,c31}, {a0,a1,a2,a3}, {x14,x15}, {c28,c29,c30,c31};\n"
            "ld.shared.v4.u32 {x12,x13,x14,x15}, [xa+640];\n"
            "tanh.approx.f32 th6, h12;\n"
            "tanh.approx.f32 th7, h14;\n"
            "fma.rn.f32 th6, h12, th6, h12;\n"
            "fma.rn.f32 th7, h14, th7, h14;\n"
            "cvt.rn.bf16x2.f32 r3, th7, th6;\n"
            "ld.shared.v4.u32 {a0,a1,a2,a3}, [ab+0];\n"
            "@pe mbarrier.arrive.shared::cta.b64 _, [cnt+280];\n"
            "mov.b32 {lo,hi}, r0; mov.b32 rl, {lo,lo}; mov.b32 rh, {hi,hi};\n"
            "mul.bf16x2 x0, x0, rl; mul.bf16x2 x1, x1, rl; mul.bf16x2 x2, x2, rh; mul.bf16x2 x3, x3, rh;\n"
            "mov.b32 {lo,hi}, r1; mov.b32 rl, {lo,lo}; mov.b32 rh, {hi,hi};\n"
            "mul.bf16x2 x4, x4, rl; mul.bf16x2 x5, x5, rl; mul.bf16x2 x6, x6, rh; mul.bf16x2 x7, x7, rh;\n"
            "mov.b32 {lo,hi}, r2; mov.b32 rl, {lo,lo}; mov.b32 rh, {hi,hi};\n"
            "mul.bf16x2 x8, x8, rl; mul.bf16x2 x9, x9, rl; mul.bf16x2 x10, x10, rh; mul.bf16x2 x11, x11, rh;\n"
            "mov.b32 {lo,hi}, r3; mov.b32 rl, {lo,lo}; mov.b32 rh, {hi,hi};\n"
            "mul.bf16x2 x12, x12, rl; mul.bf16x2 x13, x13, rl; mul.bf16x2 x14, x14, rh; mul.bf16x2 x15, x15, rh;\n"
            "@d1 bra.uni L1; @d2 bra.uni B1_4; @d0 bra.uni B1_1; bra.uni B1_0;\n"
            "B0_1:\n"
            "xor.b32 tmp, mt, %3; and.b32 tmp, tmp, 1536; setp.eq.u32 pm, tmp, 0; selp.b32 ab, aa, %3, pm;\n"
            "and.b32 tmp, mt, 2048; setp.ne.u32 d0, tmp, 0; and.b32 tmp, mt, 4096; setp.ne.u32 d1, tmp, 0; and.b32 tmp, mt, 8192; setp.ne.u32 d2, tmp, 0;\n"
            "mad.lo.u32 cnt, a0, %5, ea; mad.lo.s32 ea, st, 2560, ea;\n"
            "ld.shared.u32 mt, [aa+512];\n"
            "mma.sync.aligned.m16n8k16.row.col.f32.bf16.bf16.f32 {c32,c33,c34,c35}, {a0,a1,a2,a3}, {x0,x1}, {c32,c33,c34,c35};\n"
            "mma.sync.aligned.m16n8k16.row.col.f32.bf16.bf16.f32 {c36,c37,c38,c39}, {a0,a1,a2,a3}, {x2,x3}, {c36,c37,c38,c39};\n"
            "ld.shared.v4.u32 {x0,x1,x2,x3}, [xa+0];\n"
            "tanh.approx.f32 th0, h0;\n"
            "tanh.approx.f32 th1, h2;\n"
            "fma.rn.f32 th0, h0, th0, h0;\n"
            "fma.rn.f32 th1, h2, th1, h2;\n"
            "cvt.rn.bf16x2.f32 r0, th1, th0;\n"
            "mma.sync.aligned.m16n8k16.row.col.f32.bf16.bf16.f32 {c40,c41,c42,c43}, {a0,a1,a2,a3}, {x4,x5}, {c40,c41,c42,c43};\n"
            "mma.sync.aligned.m16n8k16.row.col.f32.bf16.bf16.f32 {c44,c45,c46,c47}, {a0,a1,a2,a3}, {x6,x7}, {c44,c45,c46,c47};\n"
            "ld.shared.v4.u32 {x4,x5,x6,x7}, [xa+128];\n"
            "tanh.approx.f32 th2, h4;\n"
            "tanh.approx.f32 th3, h6;\n"
            "fma.rn.f32 th2, h4, th2, h4;\n"
            "fma.rn.f32 th3, h6, th3, h6;\n"
            "cvt.rn.bf16x2.f32 r1, th3, th2;\n"
            "mma.sync.aligned.m16n8k16.row.col.f32.bf16.bf16.f32 {c48,c49,c50,c51}, {a0,a1,a2,a3}, {x8,x9}, {c48,c49,c50,c51};\n"
            "mma.sync.aligned.m16n8k16.row.col.f32.bf16.bf16.f32 {c52,c53,c54,c55}, {a0,a1,a2,a3}, {x10,x11}, {c52,c53,c54,c55};\n"
            "ld.shared.v4.u32 {x8,x9,x10,x11}, [xa+512];\n"
            "tanh.approx.f32 th4, h8;\n"
            "tanh.approx.f32 th5, h10;\n"
            "fma.rn.f32 th4, h8, th4, h8;\n"
            "fma.rn.f32 th5, h10, th5, h10;\n"
            "cvt.rn.bf16x2.f32 r2, th5, th4;\n"
            "mma.sync.aligned.m16n8k16.row.col.f32.bf16.bf16.f32 {c56,c57,c58,c59}, {a0,a1,a2,a3}, {x12,x13}, {c56,c57,c58,c59};\n"
            "mma.sync.aligned.m16n8k16.row.col.f32.bf16.bf16.f32 {c60,c61,c62,c63}, {a0,a1,a2,a3}, {x14,x15}, {c60,c61,c62,c63};\n"
            "ld.shared.v4.u32 {x12,x13,x14,x15}, [xa+640];\n"
            "tanh.approx.f32 th6, h12;\n"
            "tanh.approx.f32 th7, h14;\n"
            "fma.rn.f32 th6, h12, th6, h12;\n"
            "fma.rn.f32 th7, h14, th7, h14;\n"
            "cvt.rn.bf16x2.f32 r3, th7, th6;\n"
            "ld.shared.v4.u32 {a0,a1,a2,a3}, [ab+0];\n"
            "@pe mbarrier.arrive.shared::cta.b64 _, [cnt+280];\n"
            "mov.b32 {lo,hi}, r0; mov.b32 rl, {lo,lo}; mov.b32 rh, {hi,hi};\n"
            "mul.bf16x2 x0, x0, rl; mul.bf16x2 x1, x1, rl; mul.bf16x2 x2, x2, rh; mul.bf16x2 x3, x3, rh;\n"
            "mov.b32 {lo,hi}, r1; mov.b32 rl, {lo,lo}; mov.b32 rh, {hi,hi};\n"
            "mul.bf16x2 x4, x4, rl; mul.bf16x2 x5, x5, rl; mul.bf16x2 x6, x6, rh; mul.bf16x2 x7, x7, rh;\n"
            "mov.b32 {lo,hi}, r2; mov.b32 rl, {lo,lo}; mov.b32 rh, {hi,hi};\n"
            "mul.bf16x2 x8, x8, rl; mul.bf16x2 x9, x9, rl; mul.bf16x2 x10, x10, rh; mul.bf16x2 x11, x11, rh;\n"
            "mov.b32 {lo,hi}, r3; mov.b32 rl, {lo,lo}; mov.b32 rh, {hi,hi};\n"
            "mul.bf16x2 x12, x12, rl; mul.bf16x2 x13, x13, rl; mul.bf16x2 x14, x14, rh; mul.bf16x2 x15, x15, rh;\n"
            "@d1 bra.uni L1; @d2 bra.uni B1_4; @d0 bra.uni B1_1; bra.uni B1_0;\n"
            "L0: @d0 bra.uni B0_3;\n"
            "B0_2:\n"
            "xor.b32 tmp, mt, %3; and.b32 tmp, tmp, 1536; setp.eq.u32 pm, tmp, 0; selp.b32 ab, aa, %3, pm;\n"
            "and.b32 tmp, mt, 2048; setp.ne.u32 d0, tmp, 0; and.b32 tmp, mt, 4096; setp.ne.u32 d1, tmp, 0; and.b32 tmp, mt, 8192; setp.ne.u32 d2, tmp, 0;\n"
            "mad.lo.u32 cnt, a0, %5, ea; mad.lo.s32 ea, st, 2560, ea;\n"
            "ld.shared.u32 mt, [aa+512];\n"
            "mma.sync.aligned.m16n8k16.row.col.f32.bf16.bf16.f32 {c64,c65,c66,c67}, {a0,a1,a2,a3}, {x0,x1}, {c64,c65,c66,c67};\n"
            "mma.sync.aligned.m16n8k16.row.col.f32.bf16.bf16.f32 {c68,c69,c70,c71}, {a0,a1,a2,a3}, {x2,x3}, {c68,c69,c70,c71};\n"
            "ld.shared.v4.u32 {x0,x1,x2,x3}, [xa+0];\n"
            "tanh.approx.f32 th0, h0;\n"
            "tanh.approx.f32 th1, h2;\n"
            "fma.rn.f32 th0, h0, th0, h0;\n"
            "fma.rn.f32 th1, h2, th1, h2;\n"
            "cvt.rn.bf16x2.f32 r0, th1, th0;\n"
            "mma.sync.aligned.m16n8k16.row.col.f32.bf16.bf16.f32 {c72,c73,c74,c75}, {a0,a1,a2,a3}, {x4,x5}, {c72,c73,c74,c75};\n"
            "mma.sync.aligned.m16n8k16.row.col.f32.bf16.bf16.f32 {c76,c77,c78,c79}, {a0,a1,a2,a3}, {x6,x7}, {c76,c77,c78,c79};\n"
            "ld.shared.v4.u32 {x4,x5,x6,x7}, [xa+128];\n"
            "tanh.approx.f32 th2, h4;\n"
            "tanh.approx.f32 th3, h6;\n"
            "fma.rn.f32 th2, h4, th2, h4;\n"
            "fma.rn.f32 th3, h6, th3, h6;\n"
            "cvt.rn.bf16x2.f32 r1, th3, th2;\n"
            "mma.sync.aligned.m16n8k16.row.col.f32.bf16.bf16.f32 {c80,c81,c82,c83}, {a0,a1,a2,a3}, {x8,x9}, {c80,c81,c82,c83};\n"
            "mma.sync.aligned.m16n8k16.row.col.f32.bf16.bf16.f32 {c84,c85,c86,c87}, {a0,a1,a2,a3}, {x10,x11}, {c84,c85,c86,c87};\n"
            "ld.shared.v4.u32 {x8,x9,x10,x11}, [xa+512];\n"
            "tanh.approx.f32 th4, h8;\n"
            "tanh.approx.f32 th5, h10;\n"
            "fma.rn.f32 th4, h8, th4, h8;\n"
            "fma.rn.f32 th5, h10, th5, h10;\n"
            "cvt.rn.bf16x2.f32 r2, th5, th4;\n"
            "mma.sync.aligned.m16n8k16.row.col.f32.bf16.bf16.f32 {c88,c89,c90,c91}, {a0,a1,a2,a3}, {x12,x13}, {c88,c89,c90,c91};\n"
            "mma.sync.aligned.m16n8k16.row.col.f32.bf16.bf16.f32 {c92,c93,c94,c95}, {a0,a1,a2,a3}, {x14,x15}, {c92,c93,c94,c95};\n"
            "ld.shared.v4.u32 {x12,x13,x14,x15}, [xa+640];\n"
            "tanh.approx.f32 th6, h12;\n"
            "tanh.approx.f32 th7, h14;\n"
            "fma.rn.f32 th6, h12, th6, h12;\n"
            "fma.rn.f32 th7, h14, th7, h14;\n"
            "cvt.rn.bf16x2.f32 r3, th7, th6;\n"
            "ld.shared.v4.u32 {a0,a1,a2,a3}, [ab+0];\n"
            "@pe mbarrier.arrive.shared::cta.b64 _, [cnt+280];\n"
            "mov.b32 {lo,hi}, r0; mov.b32 rl, {lo,lo}; mov.b32 rh, {hi,hi};\n"
            "mul.bf16x2 x0, x0, rl; mul.bf16x2 x1, x1, rl; mul.bf16x2 x2, x2, rh; mul.bf16x2 x3, x3, rh;\n"
            "mov.b32 {lo,hi}, r1; mov.b32 rl, {lo,lo}; mov.b32 rh, {hi,hi};\n"
            "mul.bf16x2 x4, x4, rl; mul.bf16x2 x5, x5, rl; mul.bf16x2 x6, x6, rh; mul.bf16x2 x7, x7, rh;\n"
            "mov.b32 {lo,hi}, r2; mov.b32 rl, {lo,lo}; mov.b32 rh, {hi,hi};\n"
            "mul.bf16x2 x8, x8, rl; mul.bf16x2 x9, x9, rl; mul.bf16x2 x10, x10, rh; mul.bf16x2 x11, x11, rh;\n"
            "mov.b32 {lo,hi}, r3; mov.b32 rl, {lo,lo}; mov.b32 rh, {hi,hi};\n"
            "mul.bf16x2 x12, x12, rl; mul.bf16x2 x13, x13, rl; mul.bf16x2 x14, x14, rh; mul.bf16x2 x15, x15, rh;\n"
            "@d1 bra.uni L1; @d2 bra.uni B1_4; @d0 bra.uni B1_1; bra.uni B1_0;\n"
            "B0_3:\n"
            "xor.b32 tmp, mt, %3; and.b32 tmp, tmp, 1536; setp.eq.u32 pm, tmp, 0; selp.b32 ab, aa, %3, pm;\n"
            "and.b32 tmp, mt, 2048; setp.ne.u32 d0, tmp, 0; and.b32 tmp, mt, 4096; setp.ne.u32 d1, tmp, 0; and.b32 tmp, mt, 8192; setp.ne.u32 d2, tmp, 0;\n"
            "mad.lo.u32 cnt, a0, %5, ea; mad.lo.s32 ea, st, 2560, ea;\n"
            "ld.shared.u32 mt, [aa+512];\n"
            "mma.sync.aligned.m16n8k16.row.col.f32.bf16.bf16.f32 {c96,c97,c98,c99}, {a0,a1,a2,a3}, {x0,x1}, {c96,c97,c98,c99};\n"
            "mma.sync.aligned.m16n8k16.row.col.f32.bf16.bf16.f32 {c100,c101,c102,c103}, {a0,a1,a2,a3}, {x2,x3}, {c100,c101,c102,c103};\n"
            "ld.shared.v4.u32 {x0,x1,x2,x3}, [xa+0];\n"
            "tanh.approx.f32 th0, h0;\n"
            "tanh.approx.f32 th1, h2;\n"
            "fma.rn.f32 th0, h0, th0, h0;\n"
            "fma.rn.f32 th1, h2, th1, h2;\n"
            "cvt.rn.bf16x2.f32 r0, th1, th0;\n"
            "mma.sync.aligned.m16n8k16.row.col.f32.bf16.bf16.f32 {c104,c105,c106,c107}, {a0,a1,a2,a3}, {x4,x5}, {c104,c105,c106,c107};\n"
            "mma.sync.aligned.m16n8k16.row.col.f32.bf16.bf16.f32 {c108,c109,c110,c111}, {a0,a1,a2,a3}, {x6,x7}, {c108,c109,c110,c111};\n"
            "ld.shared.v4.u32 {x4,x5,x6,x7}, [xa+128];\n"
            "tanh.approx.f32 th2, h4;\n"
            "tanh.approx.f32 th3, h6;\n"
            "fma.rn.f32 th2, h4, th2, h4;\n"
            "fma.rn.f32 th3, h6, th3, h6;\n"
            "cvt.rn.bf16x2.f32 r1, th3, th2;\n"
            "mma.sync.aligned.m16n8k16.row.col.f32.bf16.bf16.f32 {c112,c113,c114,c115}, {a0,a1,a2,a3}, {x8,x9}, {c112,c113,c114,c115};\n"
            "mma.sync.aligned.m16n8k16.row.col.f32.bf16.bf16.f32 {c116,c117,c118,c119}, {a0,a1,a2,a3}, {x10,x11}, {c116,c117,c118,c119};\n"
            "ld.shared.v4.u32 {x8,x9,x10,x11}, [xa+512];\n"
            "tanh.approx.f32 th4, h8;\n"
            "tanh.approx.f32 th5, h10;\n"
            "fma.rn.f32 th4, h8, th4, h8;\n"
            "fma.rn.f32 th5, h10, th5, h10;\n"
            "cvt.rn.bf16x2.f32 r2, th5, th4;\n"
            "mma.sync.aligned.m16n8k16.row.col.f32.bf16.bf16.f32 {c120,c121,c122,c123}, {a0,a1,a2,a3}, {x12,x13}, {c120,c121,c122,c123};\n"
            "mma.sync.aligned.m16n8k16.row.col.f32.bf16.bf16.f32 {c124,c125,c126,c127}, {a0,a1,a2,a3}, {x14,x15}, {c124,c125,c126,c127};\n"
            "ld.shared.v4.u32 {x12,x13,x14,x15}, [xa+640];\n"
            "tanh.approx.f32 th6, h12;\n"
            "tanh.approx.f32 th7, h14;\n"
            "fma.rn.f32 th6, h12, th6, h12;\n"
            "fma.rn.f32 th7, h14, th7, h14;\n"
            "cvt.rn.bf16x2.f32 r3, th7, th6;\n"
            "ld.shared.v4.u32 {a0,a1,a2,a3}, [ab+0];\n"
            "@pe mbarrier.arrive.shared::cta.b64 _, [cnt+280];\n"
            "mov.b32 {lo,hi}, r0; mov.b32 rl, {lo,lo}; mov.b32 rh, {hi,hi};\n"
            "mul.bf16x2 x0, x0, rl; mul.bf16x2 x1, x1, rl; mul.bf16x2 x2, x2, rh; mul.bf16x2 x3, x3, rh;\n"
            "mov.b32 {lo,hi}, r1; mov.b32 rl, {lo,lo}; mov.b32 rh, {hi,hi};\n"
            "mul.bf16x2 x4, x4, rl; mul.bf16x2 x5, x5, rl; mul.bf16x2 x6, x6, rh; mul.bf16x2 x7, x7, rh;\n"
            "mov.b32 {lo,hi}, r2; mov.b32 rl, {lo,lo}; mov.b32 rh, {hi,hi};\n"
            "mul.bf16x2 x8, x8, rl; mul.bf16x2 x9, x9, rl; mul.bf16x2 x10, x10, rh; mul.bf16x2 x11, x11, rh;\n"
            "mov.b32 {lo,hi}, r3; mov.b32 rl, {lo,lo}; mov.b32 rh, {hi,hi};\n"
            "mul.bf16x2 x12, x12, rl; mul.bf16x2 x13, x13, rl; mul.bf16x2 x14, x14, rh; mul.bf16x2 x15, x15, rh;\n"
            "@d1 bra.uni L1; @d2 bra.uni B1_4; @d0 bra.uni B1_1; bra.uni B1_0;\n"
            "B0_4:\n"
            "xor.b32 tmp, mt, %3; and.b32 tmp, tmp, 1536; setp.eq.u32 pm, tmp, 0; selp.b32 ab, aa, %3, pm;\n"
            "and.b32 tmp, mt, 2048; setp.ne.u32 d0, tmp, 0; and.b32 tmp, mt, 4096; setp.ne.u32 d1, tmp, 0; and.b32 tmp, mt, 8192; setp.ne.u32 d2, tmp, 0;\n"
            "mad.lo.u32 cnt, a0, %5, ea; mad.lo.s32 ea, st, 2560, ea;\n"
            "ld.shared.u32 mt, [aa+512];\n"
            "mma.sync.aligned.m16n8k16.row.col.f32.bf16.bf16.f32 {c128,c129,c130,c131}, {a0,a1,a2,a3}, {x0,x1}, {c128,c129,c130,c131};\n"
            "mma.sync.aligned.m16n8k16.row.col.f32.bf16.bf16.f32 {c132,c133,c134,c135}, {a0,a1,a2,a3}, {x2,x3}, {c132,c133,c134,c135};\n"
            "ld.shared.v4.u32 {x0,x1,x2,x3}, [xa+0];\n"
            "tanh.approx.f32 th0, h0;\n"
            "tanh.approx.f32 th1, h2;\n"
            "fma.rn.f32 th0, h0, th0, h0;\n"
            "fma.rn.f32 th1, h2, th1, h2;\n"
            "cvt.rn.bf16x2.f32 r0, th1, th0;\n"
            "mma.sync.aligned.m16n8k16.row.col.f32.bf16.bf16.f32 {c136,c137,c138,c139}, {a0,a1,a2,a3}, {x4,x5}, {c136,c137,c138,c139};\n"
            "mma.sync.aligned.m16n8k16.row.col.f32.bf16.bf16.f32 {c140,c141,c142,c143}, {a0,a1,a2,a3}, {x6,x7}, {c140,c141,c142,c143};\n"
            "ld.shared.v4.u32 {x4,x5,x6,x7}, [xa+128];\n"
            "tanh.approx.f32 th2, h4;\n"
            "tanh.approx.f32 th3, h6;\n"
            "fma.rn.f32 th2, h4, th2, h4;\n"
            "fma.rn.f32 th3, h6, th3, h6;\n"
            "cvt.rn.bf16x2.f32 r1, th3, th2;\n"
            "mma.sync.aligned.m16n8k16.row.col.f32.bf16.bf16.f32 {c144,c145,c146,c147}, {a0,a1,a2,a3}, {x8,x9}, {c144,c145,c146,c147};\n"
            "mma.sync.aligned.m16n8k16.row.col.f32.bf16.bf16.f32 {c148,c149,c150,c151}, {a0,a1,a2,a3}, {x10,x11}, {c148,c149,c150,c151};\n"
            "ld.shared.v4.u32 {x8,x9,x10,x11}, [xa+512];\n"
            "tanh.approx.f32 th4, h8;\n"
            "tanh.approx.f32 th5, h10;\n"
            "fma.rn.f32 th4, h8, th4, h8;\n"
            "fma.rn.f32 th5, h10, th5, h10;\n"
            "cvt.rn.bf16x2.f32 r2, th5, th4;\n"
            "mma.sync.aligned.m16n8k16.row.col.f32.bf16.bf16.f32 {c152,c153,c154,c155}, {a0,a1,a2,a3}, {x12,x13}, {c152,c153,c154,c155};\n"
            "mma.sync.aligned.m16n8k16.row.col.f32.bf16.bf16.f32 {c156,c157,c158,c159}, {a0,a1,a2,a3}, {x14,x15}, {c156,c157,c158,c159};\n"
            "ld.shared.v4.u32 {x12,x13,x14,x15}, [xa+640];\n"
            "tanh.approx.f32 th6, h12;\n"
            "tanh.approx.f32 th7, h14;\n"
            "fma.rn.f32 th6, h12, th6, h12;\n"
            "fma.rn.f32 th7, h14, th7, h14;\n"
            "cvt.rn.bf16x2.f32 r3, th7, th6;\n"
            "ld.shared.v4.u32 {a0,a1,a2,a3}, [ab+0];\n"
            "@pe mbarrier.arrive.shared::cta.b64 _, [cnt+280];\n"
            "mov.b32 {lo,hi}, r0; mov.b32 rl, {lo,lo}; mov.b32 rh, {hi,hi};\n"
            "mul.bf16x2 x0, x0, rl; mul.bf16x2 x1, x1, rl; mul.bf16x2 x2, x2, rh; mul.bf16x2 x3, x3, rh;\n"
            "mov.b32 {lo,hi}, r1; mov.b32 rl, {lo,lo}; mov.b32 rh, {hi,hi};\n"
            "mul.bf16x2 x4, x4, rl; mul.bf16x2 x5, x5, rl; mul.bf16x2 x6, x6, rh; mul.bf16x2 x7, x7, rh;\n"
            "mov.b32 {lo,hi}, r2; mov.b32 rl, {lo,lo}; mov.b32 rh, {hi,hi};\n"
            "mul.bf16x2 x8, x8, rl; mul.bf16x2 x9, x9, rl; mul.bf16x2 x10, x10, rh; mul.bf16x2 x11, x11, rh;\n"
            "mov.b32 {lo,hi}, r3; mov.b32 rl, {lo,lo}; mov.b32 rh, {hi,hi};\n"
            "mul.bf16x2 x12, x12, rl; mul.bf16x2 x13, x13, rl; mul.bf16x2 x14, x14, rh; mul.bf16x2 x15, x15, rh;\n"
            "@d1 bra.uni L1; @d2 bra.uni B1_4; @d0 bra.uni B1_1; bra.uni B1_0;\n"
            "B1_0:\n"
            "xor.b32 tmp, mt, ea; and.b32 tmp, tmp, 192; setp.eq.u32 pm, tmp, 0; selp.b32 ab, aa, %3, pm;\n"
            "and.b32 tmp, mt, 8; setp.ne.u32 d0, tmp, 0; and.b32 tmp, mt, 16; setp.ne.u32 d1, tmp, 0; and.b32 tmp, mt, 32; setp.ne.u32 d2, tmp, 0;\n"
            "ld.shared.v2.u32 {e0,e1}, [ea];\n"
            "shr.s32 st, mt, 24; mad.lo.s32 aa, st, 2560, aa;\n"
            "mma.sync.aligned.m16n8k16.row.col.f32.bf16.bf16.f32 {c0,c1,c2,c3}, {a0,a1,a2,a3}, {x0,x1}, {c0,c1,c2,c3};\n"
            "mma.sync.aligned.m16n8k16.row.col.f32.bf16.bf16.f32 {c4,c5,c6,c7}, {a0,a1,a2,a3}, {x2,x3}, {c4,c5,c6,c7};\n"
            "ld.shared.v4.u32 {x0,x1,x2,x3}, [xa+1024];\n"
            "tanh.approx.f32 th0, h1;\n"
            "tanh.approx.f32 th1, h3;\n"
            "fma.rn.f32 th0, h1, th0, h1;\n"
            "fma.rn.f32 th1, h3, th1, h3;\n"
            "cvt.rn.bf16x2.f32 r0, th1, th0;\n"
            "mma.sync.aligned.m16n8k16.row.col.f32.bf16.bf16.f32 {h0,h1,h2,h3}, {%7,%8,%9,%10}, {e0,e1}, {fz,fz,fz,fz};\n"
            "mma.sync.aligned.m16n8k16.row.col.f32.bf16.bf16.f32 {c8,c9,c10,c11}, {a0,a1,a2,a3}, {x4,x5}, {c8,c9,c10,c11};\n"
            "mma.sync.aligned.m16n8k16.row.col.f32.bf16.bf16.f32 {c12,c13,c14,c15}, {a0,a1,a2,a3}, {x6,x7}, {c12,c13,c14,c15};\n"
            "ld.shared.v4.u32 {x4,x5,x6,x7}, [xa+1152];\n"
            "tanh.approx.f32 th2, h5;\n"
            "tanh.approx.f32 th3, h7;\n"
            "fma.rn.f32 th2, h5, th2, h5;\n"
            "fma.rn.f32 th3, h7, th3, h7;\n"
            "cvt.rn.bf16x2.f32 r1, th3, th2;\n"
            "mma.sync.aligned.m16n8k16.row.col.f32.bf16.bf16.f32 {h4,h5,h6,h7}, {%11,%12,%13,%14}, {e0,e1}, {fz,fz,fz,fz};\n"
            "mma.sync.aligned.m16n8k16.row.col.f32.bf16.bf16.f32 {c16,c17,c18,c19}, {a0,a1,a2,a3}, {x8,x9}, {c16,c17,c18,c19};\n"
            "mma.sync.aligned.m16n8k16.row.col.f32.bf16.bf16.f32 {c20,c21,c22,c23}, {a0,a1,a2,a3}, {x10,x11}, {c20,c21,c22,c23};\n"
            "ld.shared.v4.u32 {x8,x9,x10,x11}, [xa+1536];\n"
            "tanh.approx.f32 th4, h9;\n"
            "tanh.approx.f32 th5, h11;\n"
            "fma.rn.f32 th4, h9, th4, h9;\n"
            "fma.rn.f32 th5, h11, th5, h11;\n"
            "cvt.rn.bf16x2.f32 r2, th5, th4;\n"
            "mma.sync.aligned.m16n8k16.row.col.f32.bf16.bf16.f32 {h8,h9,h10,h11}, {%15,%16,%17,%18}, {e0,e1}, {fz,fz,fz,fz};\n"
            "mma.sync.aligned.m16n8k16.row.col.f32.bf16.bf16.f32 {c24,c25,c26,c27}, {a0,a1,a2,a3}, {x12,x13}, {c24,c25,c26,c27};\n"
            "mma.sync.aligned.m16n8k16.row.col.f32.bf16.bf16.f32 {c28,c29,c30,c31}, {a0,a1,a2,a3}, {x14,x15}, {c28,c29,c30,c31};\n"
            "ld.shared.v4.u32 {x12,x13,x14,x15}, [xa+1664];\n"
            "tanh.approx.f32 th6, h13;\n"
            "tanh.approx.f32 th7, h15;\n"
            "fma.rn.f32 th6, h13, th6, h13;\n"
            "fma.rn.f32 th7, h15, th7, h15;\n"
            "cvt.rn.bf16x2.f32 r3, th7, th6;\n"
            "mma.sync.aligned.m16n8k16.row.col.f32.bf16.bf16.f32 {h12,h13,h14,h15}, {%19,%20,%21,%22}, {e0,e1}, {fz,fz,fz,fz};\n"
            "ld.shared.v4.u32 {a0,a1,a2,a3}, [ab+128];\n"
            "and.b32 tmp, aa, 0xffffff80; mbarrier.test_wait.parity.shared::cta.b64 pw, [tmp+520], mt;\n"
            "mad.lo.s32 xa, st, 2048, xa;\n"
            "mov.b32 {lo,hi}, r0; mov.b32 rl, {lo,lo}; mov.b32 rh, {hi,hi};\n"
            "mul.bf16x2 x0, x0, rl; mul.bf16x2 x1, x1, rl; mul.bf16x2 x2, x2, rh; mul.bf16x2 x3, x3, rh;\n"
            "mov.b32 {lo,hi}, r1; mov.b32 rl, {lo,lo}; mov.b32 rh, {hi,hi};\n"
            "mul.bf16x2 x4, x4, rl; mul.bf16x2 x5, x5, rl; mul.bf16x2 x6, x6, rh; mul.bf16x2 x7, x7, rh;\n"
            "mov.b32 {lo,hi}, r2; mov.b32 rl, {lo,lo}; mov.b32 rh, {hi,hi};\n"
            "mul.bf16x2 x8, x8, rl; mul.bf16x2 x9, x9, rl; mul.bf16x2 x10, x10, rh; mul.bf16x2 x11, x11, rh;\n"
            "mov.b32 {lo,hi}, r3; mov.b32 rl, {lo,lo}; mov.b32 rh, {hi,hi};\n"
            "mul.bf16x2 x12, x12, rl; mul.bf16x2 x13, x13, rl; mul.bf16x2 x14, x14, rh; mul.bf16x2 x15, x15, rh;\n"
            "@!pw bra.uni W1;\n"
            "@d2 bra.uni B0_4; @d1 bra.uni L0; @d0 bra.uni B0_1; bra.uni B0_0;\n"
            "B1_1:\n"
            "xor.b32 tmp, mt, ea; and.b32 tmp, tmp, 192; setp.eq.u32 pm, tmp, 0; selp.b32 ab, aa, %3, pm;\n"
            "and.b32 tmp, mt, 8; setp.ne.u32 d0, tmp, 0; and.b32 tmp, mt, 16; setp.ne.u32 d1, tmp, 0; and.b32 tmp, mt, 32; setp.ne.u32 d2, tmp, 0;\n"
            "ld.shared.v2.u32 {e0,e1}, [ea];\n"
            "shr.s32 st, mt, 24; mad.lo.s32 aa, st, 2560, aa;\n"
            "mma.sync.aligned.m16n8k16.row.col.f32.bf16.bf16.f32 {c32,c33,c34,c35}, {a0,a1,a2,a3}, {x0,x1}, {c32,c33,c34,c35};\n"
            "mma.sync.aligned.m16n8k16.row.col.f32.bf16.bf16.f32 {c36,c37,c38,c39}, {a0,a1,a2,a3}, {x2,x3}, {c36,c37,c38,c39};\n"
            "ld.shared.v4.u32 {x0,x1,x2,x3}, [xa+1024];\n"
            "tanh.approx.f32 th0, h1;\n"
            "tanh.approx.f32 th1, h3;\n"
            "fma.rn.f32 th0, h1, th0, h1;\n"
            "fma.rn.f32 th1, h3, th1, h3;\n"
            "cvt.rn.bf16x2.f32 r0, th1, th0;\n"
            "mma.sync.aligned.m16n8k16.row.col.f32.bf16.bf16.f32 {h0,h1,h2,h3}, {%7,%8,%9,%10}, {e0,e1}, {fz,fz,fz,fz};\n"
            "mma.sync.aligned.m16n8k16.row.col.f32.bf16.bf16.f32 {c40,c41,c42,c43}, {a0,a1,a2,a3}, {x4,x5}, {c40,c41,c42,c43};\n"
            "mma.sync.aligned.m16n8k16.row.col.f32.bf16.bf16.f32 {c44,c45,c46,c47}, {a0,a1,a2,a3}, {x6,x7}, {c44,c45,c46,c47};\n"
            "ld.shared.v4.u32 {x4,x5,x6,x7}, [xa+1152];\n"
            "tanh.approx.f32 th2, h5;\n"
            "tanh.approx.f32 th3, h7;\n"
            "fma.rn.f32 th2, h5, th2, h5;\n"
            "fma.rn.f32 th3, h7, th3, h7;\n"
            "cvt.rn.bf16x2.f32 r1, th3, th2;\n"
            "mma.sync.aligned.m16n8k16.row.col.f32.bf16.bf16.f32 {h4,h5,h6,h7}, {%11,%12,%13,%14}, {e0,e1}, {fz,fz,fz,fz};\n"
            "mma.sync.aligned.m16n8k16.row.col.f32.bf16.bf16.f32 {c48,c49,c50,c51}, {a0,a1,a2,a3}, {x8,x9}, {c48,c49,c50,c51};\n"
            "mma.sync.aligned.m16n8k16.row.col.f32.bf16.bf16.f32 {c52,c53,c54,c55}, {a0,a1,a2,a3}, {x10,x11}, {c52,c53,c54,c55};\n"
            "ld.shared.v4.u32 {x8,x9,x10,x11}, [xa+1536];\n"
            "tanh.approx.f32 th4, h9;\n"
            "tanh.approx.f32 th5, h11;\n"
            "fma.rn.f32 th4, h9, th4, h9;\n"
            "fma.rn.f32 th5, h11, th5, h11;\n"
            "cvt.rn.bf16x2.f32 r2, th5, th4;\n"
            "mma.sync.aligned.m16n8k16.row.col.f32.bf16.bf16.f32 {h8,h9,h10,h11}, {%15,%16,%17,%18}, {e0,e1}, {fz,fz,fz,fz};\n"
            "mma.sync.aligned.m16n8k16.row.col.f32.bf16.bf16.f32 {c56,c57,c58,c59}, {a0,a1,a2,a3}, {x12,x13}, {c56,c57,c58,c59};\n"
            "mma.sync.aligned.m16n8k16.row.col.f32.bf16.bf16.f32 {c60,c61,c62,c63}, {a0,a1,a2,a3}, {x14,x15}, {c60,c61,c62,c63};\n"
            "ld.shared.v4.u32 {x12,x13,x14,x15}, [xa+1664];\n"
            "tanh.approx.f32 th6, h13;\n"
            "tanh.approx.f32 th7, h15;\n"
            "fma.rn.f32 th6, h13, th6, h13;\n"
            "fma.rn.f32 th7, h15, th7, h15;\n"
            "cvt.rn.bf16x2.f32 r3, th7, th6;\n"
            "mma.sync.aligned.m16n8k16.row.col.f32.bf16.bf16.f32 {h12,h13,h14,h15}, {%19,%20,%21,%22}, {e0,e1}, {fz,fz,fz,fz};\n"
            "ld.shared.v4.u32 {a0,a1,a2,a3}, [ab+128];\n"
            "and.b32 tmp, aa, 0xffffff80; mbarrier.test_wait.parity.shared::cta.b64 pw, [tmp+520], mt;\n"
            "mad.lo.s32 xa, st, 2048, xa;\n"
            "mov.b32 {lo,hi}, r0; mov.b32 rl, {lo,lo}; mov.b32 rh, {hi,hi};\n"
            "mul.bf16x2 x0, x0, rl; mul.bf16x2 x1, x1, rl; mul.bf16x2 x2, x2, rh; mul.bf16x2 x3, x3, rh;\n"
            "mov.b32 {lo,hi}, r1; mov.b32 rl, {lo,lo}; mov.b32 rh, {hi,hi};\n"
            "mul.bf16x2 x4, x4, rl; mul.bf16x2 x5, x5, rl; mul.bf16x2 x6, x6, rh; mul.bf16x2 x7, x7, rh;\n"
            "mov.b32 {lo,hi}, r2; mov.b32 rl, {lo,lo}; mov.b32 rh, {hi,hi};\n"
            "mul.bf16x2 x8, x8, rl; mul.bf16x2 x9, x9, rl; mul.bf16x2 x10, x10, rh; mul.bf16x2 x11, x11, rh;\n"
            "mov.b32 {lo,hi}, r3; mov.b32 rl, {lo,lo}; mov.b32 rh, {hi,hi};\n"
            "mul.bf16x2 x12, x12, rl; mul.bf16x2 x13, x13, rl; mul.bf16x2 x14, x14, rh; mul.bf16x2 x15, x15, rh;\n"
            "@!pw bra.uni W1;\n"
            "@d2 bra.uni B0_4; @d1 bra.uni L0; @d0 bra.uni B0_1; bra.uni B0_0;\n"
            "L1: @d2 bra.uni END; @d0 bra.uni B1_3;\n"
            "B1_2:\n"
            "xor.b32 tmp, mt, ea; and.b32 tmp, tmp, 192; setp.eq.u32 pm, tmp, 0; selp.b32 ab, aa, %3, pm;\n"
            "and.b32 tmp, mt, 8; setp.ne.u32 d0, tmp, 0; and.b32 tmp, mt, 16; setp.ne.u32 d1, tmp, 0; and.b32 tmp, mt, 32; setp.ne.u32 d2, tmp, 0;\n"
            "ld.shared.v2.u32 {e0,e1}, [ea];\n"
            "shr.s32 st, mt, 24; mad.lo.s32 aa, st, 2560, aa;\n"
            "mma.sync.aligned.m16n8k16.row.col.f32.bf16.bf16.f32 {c64,c65,c66,c67}, {a0,a1,a2,a3}, {x0,x1}, {c64,c65,c66,c67};\n"
            "mma.sync.aligned.m16n8k16.row.col.f32.bf16.bf16.f32 {c68,c69,c70,c71}, {a0,a1,a2,a3}, {x2,x3}, {c68,c69,c70,c71};\n"
            "ld.shared.v4.u32 {x0,x1,x2,x3}, [xa+1024];\n"
            "tanh.approx.f32 th0, h1;\n"
            "tanh.approx.f32 th1, h3;\n"
            "fma.rn.f32 th0, h1, th0, h1;\n"
            "fma.rn.f32 th1, h3, th1, h3;\n"
            "cvt.rn.bf16x2.f32 r0, th1, th0;\n"
            "mma.sync.aligned.m16n8k16.row.col.f32.bf16.bf16.f32 {h0,h1,h2,h3}, {%7,%8,%9,%10}, {e0,e1}, {fz,fz,fz,fz};\n"
            "mma.sync.aligned.m16n8k16.row.col.f32.bf16.bf16.f32 {c72,c73,c74,c75}, {a0,a1,a2,a3}, {x4,x5}, {c72,c73,c74,c75};\n"
            "mma.sync.aligned.m16n8k16.row.col.f32.bf16.bf16.f32 {c76,c77,c78,c79}, {a0,a1,a2,a3}, {x6,x7}, {c76,c77,c78,c79};\n"
            "ld.shared.v4.u32 {x4,x5,x6,x7}, [xa+1152];\n"
            "tanh.approx.f32 th2, h5;\n"
            "tanh.approx.f32 th3, h7;\n"
            "fma.rn.f32 th2, h5, th2, h5;\n"
            "fma.rn.f32 th3, h7, th3, h7;\n"
            "cvt.rn.bf16x2.f32 r1, th3, th2;\n"
            "mma.sync.aligned.m16n8k16.row.col.f32.bf16.bf16.f32 {h4,h5,h6,h7}, {%11,%12,%13,%14}, {e0,e1}, {fz,fz,fz,fz};\n"
            "mma.sync.aligned.m16n8k16.row.col.f32.bf16.bf16.f32 {c80,c81,c82,c83}, {a0,a1,a2,a3}, {x8,x9}, {c80,c81,c82,c83};\n"
            "mma.sync.aligned.m16n8k16.row.col.f32.bf16.bf16.f32 {c84,c85,c86,c87}, {a0,a1,a2,a3}, {x10,x11}, {c84,c85,c86,c87};\n"
            "ld.shared.v4.u32 {x8,x9,x10,x11}, [xa+1536];\n"
            "tanh.approx.f32 th4, h9;\n"
            "tanh.approx.f32 th5, h11;\n"
            "fma.rn.f32 th4, h9, th4, h9;\n"
            "fma.rn.f32 th5, h11, th5, h11;\n"
            "cvt.rn.bf16x2.f32 r2, th5, th4;\n"
            "mma.sync.aligned.m16n8k16.row.col.f32.bf16.bf16.f32 {h8,h9,h10,h11}, {%15,%16,%17,%18}, {e0,e1}, {fz,fz,fz,fz};\n"
            "mma.sync.aligned.m16n8k16.row.col.f32.bf16.bf16.f32 {c88,c89,c90,c91}, {a0,a1,a2,a3}, {x12,x13}, {c88,c89,c90,c91};\n"
            "mma.sync.aligned.m16n8k16.row.col.f32.bf16.bf16.f32 {c92,c93,c94,c95}, {a0,a1,a2,a3}, {x14,x15}, {c92,c93,c94,c95};\n"
            "ld.shared.v4.u32 {x12,x13,x14,x15}, [xa+1664];\n"
            "tanh.approx.f32 th6, h13;\n"
            "tanh.approx.f32 th7, h15;\n"
            "fma.rn.f32 th6, h13, th6, h13;\n"
            "fma.rn.f32 th7, h15, th7, h15;\n"
            "cvt.rn.bf16x2.f32 r3, th7, th6;\n"
            "mma.sync.aligned.m16n8k16.row.col.f32.bf16.bf16.f32 {h12,h13,h14,h15}, {%19,%20,%21,%22}, {e0,e1}, {fz,fz,fz,fz};\n"
            "ld.shared.v4.u32 {a0,a1,a2,a3}, [ab+128];\n"
            "and.b32 tmp, aa, 0xffffff80; mbarrier.test_wait.parity.shared::cta.b64 pw, [tmp+520], mt;\n"
            "mad.lo.s32 xa, st, 2048, xa;\n"
            "mov.b32 {lo,hi}, r0; mov.b32 rl, {lo,lo}; mov.b32 rh, {hi,hi};\n"
            "mul.bf16x2 x0, x0, rl; mul.bf16x2 x1, x1, rl; mul.bf16x2 x2, x2, rh; mul.bf16x2 x3, x3, rh;\n"
            "mov.b32 {lo,hi}, r1; mov.b32 rl, {lo,lo}; mov.b32 rh, {hi,hi};\n"
            "mul.bf16x2 x4, x4, rl; mul.bf16x2 x5, x5, rl; mul.bf16x2 x6, x6, rh; mul.bf16x2 x7, x7, rh;\n"
            "mov.b32 {lo,hi}, r2; mov.b32 rl, {lo,lo}; mov.b32 rh, {hi,hi};\n"
            "mul.bf16x2 x8, x8, rl; mul.bf16x2 x9, x9, rl; mul.bf16x2 x10, x10, rh; mul.bf16x2 x11, x11, rh;\n"
            "mov.b32 {lo,hi}, r3; mov.b32 rl, {lo,lo}; mov.b32 rh, {hi,hi};\n"
            "mul.bf16x2 x12, x12, rl; mul.bf16x2 x13, x13, rl; mul.bf16x2 x14, x14, rh; mul.bf16x2 x15, x15, rh;\n"
            "@!pw bra.uni W1;\n"
            "@d2 bra.uni B0_4; @d1 bra.uni L0; @d0 bra.uni B0_1; bra.uni B0_0;\n"
            "B1_3:\n"
            "xor.b32 tmp, mt, ea; and.b32 tmp, tmp, 192; setp.eq.u32 pm, tmp, 0; selp.b32 ab, aa, %3, pm;\n"
            "and.b32 tmp, mt, 8; setp.ne.u32 d0, tmp, 0; and.b32 tmp, mt, 16; setp.ne.u32 d1, tmp, 0; and.b32 tmp, mt, 32; setp.ne.u32 d2, tmp, 0;\n"
            "ld.shared.v2.u32 {e0,e1}, [ea];\n"
            "shr.s32 st, mt, 24; mad.lo.s32 aa, st, 2560, aa;\n"
            "mma.sync.aligned.m16n8k16.row.col.f32.bf16.bf16.f32 {c96,c97,c98,c99}, {a0,a1,a2,a3}, {x0,x1}, {c96,c97,c98,c99};\n"
            "mma.sync.aligned.m16n8k16.row.col.f32.bf16.bf16.f32 {c100,c101,c102,c103}, {a0,a1,a2,a3}, {x2,x3}, {c100,c101,c102,c103};\n"
            "ld.shared.v4.u32 {x0,x1,x2,x3}, [xa+1024];\n"
            "tanh.approx.f32 th0, h1;\n"
            "tanh.approx.f32 th1, h3;\n"
            "fma.rn.f32 th0, h1, th0, h1;\n"
            "fma.rn.f32 th1, h3, th1, h3;\n"
            "cvt.rn.bf16x2.f32 r0, th1, th0;\n"
            "mma.sync.aligned.m16n8k16.row.col.f32.bf16.bf16.f32 {h0,h1,h2,h3}, {%7,%8,%9,%10}, {e0,e1}, {fz,fz,fz,fz};\n"
            "mma.sync.aligned.m16n8k16.row.col.f32.bf16.bf16.f32 {c104,c105,c106,c107}, {a0,a1,a2,a3}, {x4,x5}, {c104,c105,c106,c107};\n"
            "mma.sync.aligned.m16n8k16.row.col.f32.bf16.bf16.f32 {c108,c109,c110,c111}, {a0,a1,a2,a3}, {x6,x7}, {c108,c109,c110,c111};\n"
            "ld.shared.v4.u32 {x4,x5,x6,x7}, [xa+1152];\n"
            "tanh.approx.f32 th2, h5;\n"
            "tanh.approx.f32 th3, h7;\n"
            "fma.rn.f32 th2, h5, th2, h5;\n"
            "fma.rn.f32 th3, h7, th3, h7;\n"
            "cvt.rn.bf16x2.f32 r1, th3, th2;\n"
            "mma.sync.aligned.m16n8k16.row.col.f32.bf16.bf16.f32 {h4,h5,h6,h7}, {%11,%12,%13,%14}, {e0,e1}, {fz,fz,fz,fz};\n"
            "mma.sync.aligned.m16n8k16.row.col.f32.bf16.bf16.f32 {c112,c113,c114,c115}, {a0,a1,a2,a3}, {x8,x9}, {c112,c113,c114,c115};\n"
            "mma.sync.aligned.m16n8k16.row.col.f32.bf16.bf16.f32 {c116,c117,c118,c119}, {a0,a1,a2,a3}, {x10,x11}, {c116,c117,c118,c119};\n"
            "ld.shared.v4.u32 {x8,x9,x10,x11}, [xa+1536];\n"
            "tanh.approx.f32 th4, h9;\n"
            "tanh.approx.f32 th5, h11;\n"
            "fma.rn.f32 th4, h9, th4, h9;\n"
            "fma.rn.f32 th5, h11, th5, h11;\n"
            "cvt.rn.bf16x2.f32 r2, th5, th4;\n"
            "mma.sync.aligned.m16n8k16.row.col.f32.bf16.bf16.f32 {h8,h9,h10,h11}, {%15,%16,%17,%18}, {e0,e1}, {fz,fz,fz,fz};\n"
            "mma.sync.aligned.m16n8k16.row.col.f32.bf16.bf16.f32 {c120,c121,c122,c123}, {a0,a1,a2,a3}, {x12,x13}, {c120,c121,c122,c123};\n"
            "mma.sync.aligned.m16n8k16.row.col.f32.bf16.bf16.f32 {c124,c125,c126,c127}, {a0,a1,a2,a3}, {x14,x15}, {c124,c125,c126,c127};\n"
            "ld.shared.v4.u32 {x12,x13,x14,x15}, [xa+1664];\n"
            "tanh.approx.f32 th6, h13;\n"
            "tanh.approx.f32 th7, h15;\n"
            "fma.rn.f32 th6, h13, th6, h13;\n"
            "fma.rn.f32 th7, h15, th7, h15;\n"
            "cvt.rn.bf16x2.f32 r3, th7, th6;\n"
            "mma.sync.aligned.m16n8k16.row.col.f32.bf16.bf16.f32 {h12,h13,h14,h15}, {%19,%20,%21,%22}, {e0,e1}, {fz,fz,fz,fz};\n"
            "ld.shared.v4.u32 {a0,a1,a2,a3}, [ab+128];\n"
            "and.b32 tmp, aa, 0xffffff80; mbarrier.test_wait.parity.shared::cta.b64 pw, [tmp+520], mt;\n"
            "mad.lo.s32 xa, st, 2048, xa;\n"
            "mov.b32 {lo,hi}, r0; mov.b32 rl, {lo,lo}; mov.b32 rh, {hi,hi};\n"
            "mul.bf16x2 x0, x0, rl; mul.bf16x2 x1, x1, rl; mul.bf16x2 x2, x2, rh; mul.bf16x2 x3, x3, rh;\n"
            "mov.b32 {lo,hi}, r1; mov.b32 rl, {lo,lo}; mov.b32 rh, {hi,hi};\n"
            "mul.bf16x2 x4, x4, rl; mul.bf16x2 x5, x5, rl; mul.bf16x2 x6, x6, rh; mul.bf16x2 x7, x7, rh;\n"
            "mov.b32 {lo,hi}, r2; mov.b32 rl, {lo,lo}; mov.b32 rh, {hi,hi};\n"
            "mul.bf16x2 x8, x8, rl; mul.bf16x2 x9, x9, rl; mul.bf16x2 x10, x10, rh; mul.bf16x2 x11, x11, rh;\n"
            "mov.b32 {lo,hi}, r3; mov.b32 rl, {lo,lo}; mov.b32 rh, {hi,hi};\n"
            "mul.bf16x2 x12, x12, rl; mul.bf16x2 x13, x13, rl; mul.bf16x2 x14, x14, rh; mul.bf16x2 x15, x15, rh;\n"
            "@!pw bra.uni W1;\n"
            "@d2 bra.uni B0_4; @d1 bra.uni L0; @d0 bra.uni B0_1; bra.uni B0_0;\n"
            "B1_4:\n"
            "xor.b32 tmp, mt, ea; and.b32 tmp, tmp, 192; setp.eq.u32 pm, tmp, 0; selp.b32 ab, aa, %3, pm;\n"
            "and.b32 tmp, mt, 8; setp.ne.u32 d0, tmp, 0; and.b32 tmp, mt, 16; setp.ne.u32 d1, tmp, 0; and.b32 tmp, mt, 32; setp.ne.u32 d2, tmp, 0;\n"
            "ld.shared.v2.u32 {e0,e1}, [ea];\n"
            "shr.s32 st, mt, 24; mad.lo.s32 aa, st, 2560, aa;\n"
            "mma.sync.aligned.m16n8k16.row.col.f32.bf16.bf16.f32 {c128,c129,c130,c131}, {a0,a1,a2,a3}, {x0,x1}, {c128,c129,c130,c131};\n"
            "mma.sync.aligned.m16n8k16.row.col.f32.bf16.bf16.f32 {c132,c133,c134,c135}, {a0,a1,a2,a3}, {x2,x3}, {c132,c133,c134,c135};\n"
            "ld.shared.v4.u32 {x0,x1,x2,x3}, [xa+1024];\n"
            "tanh.approx.f32 th0, h1;\n"
            "tanh.approx.f32 th1, h3;\n"
            "fma.rn.f32 th0, h1, th0, h1;\n"
            "fma.rn.f32 th1, h3, th1, h3;\n"
            "cvt.rn.bf16x2.f32 r0, th1, th0;\n"
            "mma.sync.aligned.m16n8k16.row.col.f32.bf16.bf16.f32 {h0,h1,h2,h3}, {%7,%8,%9,%10}, {e0,e1}, {fz,fz,fz,fz};\n"
            "mma.sync.aligned.m16n8k16.row.col.f32.bf16.bf16.f32 {c136,c137,c138,c139}, {a0,a1,a2,a3}, {x4,x5}, {c136,c137,c138,c139};\n"
            "mma.sync.aligned.m16n8k16.row.col.f32.bf16.bf16.f32 {c140,c141,c142,c143}, {a0,a1,a2,a3}, {x6,x7}, {c140,c141,c142,c143};\n"
            "ld.shared.v4.u32 {x4,x5,x6,x7}, [xa+1152];\n"
            "tanh.approx.f32 th2, h5;\n"
            "tanh.approx.f32 th3, h7;\n"
            "fma.rn.f32 th2, h5, th2, h5;\n"
            "fma.rn.f32 th3, h7, th3, h7;\n"
            "cvt.rn.bf16x2.f32 r1, th3, th2;\n"
            "mma.sync.aligned.m16n8k16.row.col.f32.bf16.bf16.f32 {h4,h5,h6,h7}, {%11,%12,%13,%14}, {e0,e1}, {fz,fz,fz,fz};\n"
            "mma.sync.aligned.m16n8k16.row.col.f32.bf16.bf16.f32 {c144,c145,c146,c147}, {a0,a1,a2,a3}, {x8,x9}, {c144,c145,c146,c147};\n"
            "mma.sync.aligned.m16n8k16.row.col.f32.bf16.bf16.f32 {c148,c149,c150,c151}, {a0,a1,a2,a3}, {x10,x11}, {c148,c149,c150,c151};\n"
            "ld.shared.v4.u32 {x8,x9,x10,x11}, [xa+1536];\n"
            "tanh.approx.f32 th4, h9;\n"
            "tanh.approx.f32 th5, h11;\n"
            "fma.rn.f32 th4, h9, th4, h9;\n"
            "fma.rn.f32 th5, h11, th5, h11;\n"
            "cvt.rn.bf16x2.f32 r2, th5, th4;\n"
            "mma.sync.aligned.m16n8k16.row.col.f32.bf16.bf16.f32 {h8,h9,h10,h11}, {%15,%16,%17,%18}, {e0,e1}, {fz,fz,fz,fz};\n"
            "mma.sync.aligned.m16n8k16.row.col.f32.bf16.bf16.f32 {c152,c153,c154,c155}, {a0,a1,a2,a3}, {x12,x13}, {c152,c153,c154,c155};\n"
            "mma.sync.aligned.m16n8k16.row.col.f32.bf16.bf16.f32 {c156,c157,c158,c159}, {a0,a1,a2,a3}, {x14,x15}, {c156,c157,c158,c159};\n"
            "ld.shared.v4.u32 {x12,x13,x14,x15}, [xa+1664];\n"
            "tanh.approx.f32 th6, h13;\n"
            "tanh.approx.f32 th7, h15;\n"
            "fma.rn.f32 th6, h13, th6, h13;\n"
            "fma.rn.f32 th7, h15, th7, h15;\n"
            "cvt.rn.bf16x2.f32 r3, th7, th6;\n"
            "mma.sync.aligned.m16n8k16.row.col.f32.bf16.bf16.f32 {h12,h13,h14,h15}, {%19,%20,%21,%22}, {e0,e1}, {fz,fz,fz,fz};\n"
            "ld.shared.v4.u32 {a0,a1,a2,a3}, [ab+128];\n"
            "and.b32 tmp, aa, 0xffffff80; mbarrier.test_wait.parity.shared::cta.b64 pw, [tmp+520], mt;\n"
            "mad.lo.s32 xa, st, 2048, xa;\n"
            "mov.b32 {lo,hi}, r0; mov.b32 rl, {lo,lo}; mov.b32 rh, {hi,hi};\n"
            "mul.bf16x2 x0, x0, rl; mul.bf16x2 x1, x1, rl; mul.bf16x2 x2, x2, rh; mul.bf16x2 x3, x3, rh;\n"
            "mov.b32 {lo,hi}, r1; mov.b32 rl, {lo,lo}; mov.b32 rh, {hi,hi};\n"
            "mul.bf16x2 x4, x4, rl; mul.bf16x2 x5, x5, rl; mul.bf16x2 x6, x6, rh; mul.bf16x2 x7, x7, rh;\n"
            "mov.b32 {lo,hi}, r2; mov.b32 rl, {lo,lo}; mov.b32 rh, {hi,hi};\n"
            "mul.bf16x2 x8, x8, rl; mul.bf16x2 x9, x9, rl; mul.bf16x2 x10, x10, rh; mul.bf16x2 x11, x11, rh;\n"
            "mov.b32 {lo,hi}, r3; mov.b32 rl, {lo,lo}; mov.b32 rh, {hi,hi};\n"
            "mul.bf16x2 x12, x12, rl; mul.bf16x2 x13, x13, rl; mul.bf16x2 x14, x14, rh; mul.bf16x2 x15, x15, rh;\n"
            "@!pw bra.uni W1;\n"
            "@d2 bra.uni B0_4; @d1 bra.uni L0; @d0 bra.uni B0_1; bra.uni B0_0;\n"
            "W1:\n"
            "mov.u32 cnt, 0; and.b32 tmp, aa, 0xffffff80;\n"
            "W1L: mbarrier.try_wait.parity.shared::cta.b64 pw, [tmp+520], mt; @pw bra.uni W1D;\n"
            "add.u32 cnt, cnt, 1; setp.lt.u32 pk, cnt, 1000000; @pk bra.uni W1L; trap;\n"
            "W1D:\n"
            "@d2 bra.uni B0_4; @d1 bra.uni L0; @d0 bra.uni B0_1; bra.uni B0_0;\n"
            "END:\n"
            "cvt.rn.bf16x2.f32 p0, c1, c0; cvt.rn.bf16x2.f32 p1, c5, c4; cvt.rn.bf16x2.f32 p2, c9, c8; cvt.rn.bf16x2.f32 p3, c13, c12; cvt.rn.bf16x2.f32 p4, c17, c16; cvt.rn.bf16x2.f32 p5, c21, c20; cvt.rn.bf16x2.f32 p6, c25, c24; cvt.rn.bf16x2.f32 p7, c29, c28;\n"
            "cvt.rn.bf16x2.f32 p8, c3, c2; cvt.rn.bf16x2.f32 p9, c7, c6; cvt.rn.bf16x2.f32 p10, c11, c10; cvt.rn.bf16x2.f32 p11, c15, c14; cvt.rn.bf16x2.f32 p12, c19, c18; cvt.rn.bf16x2.f32 p13, c23, c22; cvt.rn.bf16x2.f32 p14, c27, c26; cvt.rn.bf16x2.f32 p15, c31, c30;\n"
            "cvt.rn.bf16x2.f32 p16, c33, c32; cvt.rn.bf16x2.f32 p17, c37, c36; cvt.rn.bf16x2.f32 p18, c41, c40; cvt.rn.bf16x2.f32 p19, c45, c44; cvt.rn.bf16x2.f32 p20, c49, c48; cvt.rn.bf16x2.f32 p21, c53, c52; cvt.rn.bf16x2.f32 p22, c57, c56; cvt.rn.bf16x2.f32 p23, c61, c60;\n"
            "cvt.rn.bf16x2.f32 p24, c35, c34; cvt.rn.bf16x2.f32 p25, c39, c38; cvt.rn.bf16x2.f32 p26, c43, c42; cvt.rn.bf16x2.f32 p27, c47, c46; cvt.rn.bf16x2.f32 p28, c51, c50; cvt.rn.bf16x2.f32 p29, c55, c54; cvt.rn.bf16x2.f32 p30, c59, c58; cvt.rn.bf16x2.f32 p31, c63, c62;\n"
            "cvt.rn.bf16x2.f32 p32, c65, c64; cvt.rn.bf16x2.f32 p33, c69, c68; cvt.rn.bf16x2.f32 p34, c73, c72; cvt.rn.bf16x2.f32 p35, c77, c76; cvt.rn.bf16x2.f32 p36, c81, c80; cvt.rn.bf16x2.f32 p37, c85, c84; cvt.rn.bf16x2.f32 p38, c89, c88; cvt.rn.bf16x2.f32 p39, c93, c92;\n"
            "cvt.rn.bf16x2.f32 p40, c67, c66; cvt.rn.bf16x2.f32 p41, c71, c70; cvt.rn.bf16x2.f32 p42, c75, c74; cvt.rn.bf16x2.f32 p43, c79, c78; cvt.rn.bf16x2.f32 p44, c83, c82; cvt.rn.bf16x2.f32 p45, c87, c86; cvt.rn.bf16x2.f32 p46, c91, c90; cvt.rn.bf16x2.f32 p47, c95, c94;\n"
            "cvt.rn.bf16x2.f32 p48, c97, c96; cvt.rn.bf16x2.f32 p49, c101, c100; cvt.rn.bf16x2.f32 p50, c105, c104; cvt.rn.bf16x2.f32 p51, c109, c108; cvt.rn.bf16x2.f32 p52, c113, c112; cvt.rn.bf16x2.f32 p53, c117, c116; cvt.rn.bf16x2.f32 p54, c121, c120; cvt.rn.bf16x2.f32 p55, c125, c124;\n"
            "cvt.rn.bf16x2.f32 p56, c99, c98; cvt.rn.bf16x2.f32 p57, c103, c102; cvt.rn.bf16x2.f32 p58, c107, c106; cvt.rn.bf16x2.f32 p59, c111, c110; cvt.rn.bf16x2.f32 p60, c115, c114; cvt.rn.bf16x2.f32 p61, c119, c118; cvt.rn.bf16x2.f32 p62, c123, c122; cvt.rn.bf16x2.f32 p63, c127, c126;\n"
            "cvt.rn.bf16x2.f32 p64, c129, c128; cvt.rn.bf16x2.f32 p65, c133, c132; cvt.rn.bf16x2.f32 p66, c137, c136; cvt.rn.bf16x2.f32 p67, c141, c140; cvt.rn.bf16x2.f32 p68, c145, c144; cvt.rn.bf16x2.f32 p69, c149, c148; cvt.rn.bf16x2.f32 p70, c153, c152; cvt.rn.bf16x2.f32 p71, c157, c156;\n"
            "cvt.rn.bf16x2.f32 p72, c131, c130; cvt.rn.bf16x2.f32 p73, c135, c134; cvt.rn.bf16x2.f32 p74, c139, c138; cvt.rn.bf16x2.f32 p75, c143, c142; cvt.rn.bf16x2.f32 p76, c147, c146; cvt.rn.bf16x2.f32 p77, c151, c150; cvt.rn.bf16x2.f32 p78, c155, c154; cvt.rn.bf16x2.f32 p79, c159, c158;\n"
            "and.b32 aa, %3, 0xfffff980; sub.u32 aa, aa, %6; mov.u32 mt, %%tid.x; shr.u32 st, mt, 7; shr.u32 cnt, mt, 5; add.u32 cnt, cnt, st; and.b32 cnt, cnt, 3;\n"
            "and.b32 mt, mt, 31; mad.lo.u32 tmp, mt, 16, aa; mad.lo.u32 tmp, st, 82432, tmp; mad.lo.u32 tmp, cnt, 10240, tmp; add.u32 cnt, cnt, 5;\n"
            "bar.sync cnt, 64;\n"
            "stmatrix.sync.aligned.m8n8.x4.shared.b16 [tmp+0], {p0,p1,p2,p3};\n"
            "stmatrix.sync.aligned.m8n8.x4.shared.b16 [tmp+41216], {p4,p5,p6,p7};\n"
            "stmatrix.sync.aligned.m8n8.x4.shared.b16 [tmp+1024], {p8,p9,p10,p11};\n"
            "stmatrix.sync.aligned.m8n8.x4.shared.b16 [tmp+42240], {p12,p13,p14,p15};\n"
            "stmatrix.sync.aligned.m8n8.x4.shared.b16 [tmp+2048], {p16,p17,p18,p19};\n"
            "stmatrix.sync.aligned.m8n8.x4.shared.b16 [tmp+43264], {p20,p21,p22,p23};\n"
            "stmatrix.sync.aligned.m8n8.x4.shared.b16 [tmp+3072], {p24,p25,p26,p27};\n"
            "stmatrix.sync.aligned.m8n8.x4.shared.b16 [tmp+44288], {p28,p29,p30,p31};\n"
            "stmatrix.sync.aligned.m8n8.x4.shared.b16 [tmp+4096], {p32,p33,p34,p35};\n"
            "stmatrix.sync.aligned.m8n8.x4.shared.b16 [tmp+45312], {p36,p37,p38,p39};\n"
            "stmatrix.sync.aligned.m8n8.x4.shared.b16 [tmp+5120], {p40,p41,p42,p43};\n"
            "stmatrix.sync.aligned.m8n8.x4.shared.b16 [tmp+46336], {p44,p45,p46,p47};\n"
            "stmatrix.sync.aligned.m8n8.x4.shared.b16 [tmp+6144], {p48,p49,p50,p51};\n"
            "stmatrix.sync.aligned.m8n8.x4.shared.b16 [tmp+47360], {p52,p53,p54,p55};\n"
            "stmatrix.sync.aligned.m8n8.x4.shared.b16 [tmp+7168], {p56,p57,p58,p59};\n"
            "stmatrix.sync.aligned.m8n8.x4.shared.b16 [tmp+48384], {p60,p61,p62,p63};\n"
            "stmatrix.sync.aligned.m8n8.x4.shared.b16 [tmp+8192], {p64,p65,p66,p67};\n"
            "stmatrix.sync.aligned.m8n8.x4.shared.b16 [tmp+49408], {p68,p69,p70,p71};\n"
            "stmatrix.sync.aligned.m8n8.x4.shared.b16 [tmp+9216], {p72,p73,p74,p75};\n"
            "stmatrix.sync.aligned.m8n8.x4.shared.b16 [tmp+50432], {p76,p77,p78,p79};\n"
            "mov.b32 %0, aa;\n"
            "}\n"
            : "=r"(sb2)
            : "r"(sb + t * XREG + grp * (NST * 2048) + half * 256 + ((g ^ ((2 * t + 2 * half) & 7)) << 4)),
              "r"(sb + AUX_OFF + grp * AUX_GR + t * 32 + (g & 1) * 16), "r"(az),
              "r"(sb + AUX_OFF + grp * AUX_GR + 256 + lane * 8), "r"(zero), "n"(ZERO_OFF),
              "r"(wr[0][0]), "r"(wr[0][1]), "r"(wr[0][2]), "r"(wr[0][3]), "r"(wr[1][0]), "r"(wr[1][1]), "r"(wr[1][2]), "r"(wr[1][3]),
              "r"(wr[2][0]), "r"(wr[2][1]), "r"(wr[2][2]), "r"(wr[2][3]), "r"(wr[3][0]), "r"(wr[3][1]), "r"(wr[3][2]), "r"(wr[3][3])
            : "memory");
        const int tid2 = threadIdx.x;
        sb2 = __shfl_sync(0xffffffffu, sb2, 0);
        const uint2 own = lds64(sb2 + MISC_OFF + 8);
        mbar_wait(sb2 + MISC_OFF, 0);
        asm volatile("fence.proxy.async.shared::cta;" ::: "memory");
        asm volatile("bar.sync 1, 256;" ::: "memory");
        const uint32_t wg = __shfl_sync(0xffffffffu, tid2 >> 7, 0);
        const uint64_t da = (uint64_t)((sb2 + WM_OFF + wg * 16384) >> 4) | (1ull << 16) | (64ull << 32) | (1ull << 62);
        const uint64_t db = (uint64_t)(sb2 >> 4) | (8ull << 16) | (64ull << 32);
        const int left = (int)own.y - 4 * (tid2 & 3);
        uint32_t* op = out + (size_t)(own.x + 4 * (tid2 & 3)) * 256 + ((tid2 >> 5) * 16 + ((tid2 & 31) >> 2)) * 2;
        float d0[40], d1[40], d2[40], d3[40], d4[40];
        mix_tiles<2, 0>(d0, da, db);
        mix_tiles<3, 2>(d1, da, db);
        store_tiles<2, 0, 1>(d0, op, left, 3 + wg);
        mix_tiles<5, 5>(d2, da, db);
        store_tiles<3, 2, 1>(d1, op, left, 3 + wg);
        mix_tiles<5, 10>(d3, da, db);
        store_tiles<5, 5, 1>(d2, op, left, 3 + wg);
        mix_tiles<5, 15>(d4, da, db);
        store_tiles<5, 10, 1>(d3, op, left, 3 + wg);
        store_tiles<5, 15, 0>(d4, op, left, 3 + wg);
    } else {
        asm volatile("setmaxnreg.dec.sync.aligned.u32 40;");
        const uint64_t map = ((uint64_t)maphi << 32) | maplo, efl = ((uint64_t)efhi << 32) | eflo;
        const uint32_t ab = s0 + AUX_OFF + pgrp * AUX_GR, xb = s0 + pgrp * (NST * 2048);
        uint32_t yp = s0 + SY_OFF + pgrp * GCAP * 4 - 32;
        uint32_t par = 0, prev = 0;
        uint32_t parv = keep(lane & zero);
        auto ahead = [&](int st, uint32_t ev) {
            asm volatile("cp.async.ca.shared.global [%0], [%1], 8;" ::"r"(w_l + st * AUX_ST + 256), "l"(efl + (ev & 0x1ffffe0u)) : "memory");
            cp_async_arrive(ab + st * AUX_ST + BAR_F0);
            if (st == NST - 1) parv ^= 1u;
            sts8(f_l + st * AUX_ST, (__byte_perm(ev, prev, fsel) & 0xfeu) | parv);
            prev = ev;
        };
        if (lds32(yp + 32 + 7 * 4) > (uint32_t)N) pc = 0;
        uint32_t wn0, wn1;
        uint32_t efo = blockIdx.x * EPC * 32u + pgrp * PFE;
        const uint32_t efend = min((blockIdx.x + 1) * EPC, E) * 32u;
        uint32_t pfo = (4u * (PFA * gridDim.x + blockIdx.x) + pgrp) * pfb;
        const uint32_t pfend = (uint32_t)N * 1024u - pfb;
        auto step = [&](int st, int WM) {
            if (left < st) return true;
            const uint4 y0 = lds128(yp + st * 32), y1 = lds128(yp + st * 32 + 16);
            const uint32_t ev = lds32(yp + st * 32 + 32 + e_l);
            uint32_t wa = wn0, wb = wn1;
            if (WM) {
                const uint32_t h0 = lds32(h_l + st * 64), h1 = lds32(h_l + st * 64 + 64);
                float w0[4], w1[4];
                mma1688_z(w0, h0, h1, cgb0);
                mma1688_z(w1, h0, h1, cgb1);
                wa = pack_bf16(w0[0], w0[1]); wb = pack_bf16(w1[0], w1[1]);
                if (WM == 2) { wn0 = pack_bf16(w0[2], w0[3]); wn1 = pack_bf16(w1[2], w1[3]); }
            }
            const uint32_t ys = y0.y + y0.z + y1.y + y1.z;
            const uint32_t tq = T0 + ((ys * pc) >> 13);
            const int sg = st % NST;
            mbar_wait(ab + sg * AUX_ST + BAR_EM, par ^ 1u);
            int rem = (int)(tq - (uint32_t)clock64());
            ahead(sg, ev);
            sts64(w_l + sg * AUX_ST, wa, wb);
            __syncwarp();
            asm volatile("{\n\t.reg .pred P;\n\tsetp.ne.u32 P, %1, 0;\n\t@P mbarrier.arrive.expect_tx.shared::cta.b64 _, [%0], %1;\n\t}"
                         ::"r"(ab + sg * AUX_ST + BAR_F0), "r"(bytes) : "memory");
#pragma unroll 1
            while (rem > 0) {
                __nanosleep(SLEEP);
                rem = (int)(tq - (uint32_t)clock64());
            }
            fetch_quad(xb + sg * 2048, ab + sg * AUX_ST + BAR_F0, y0, map);
            fetch_quad(xb + sg * 2048 + 1024, ab + sg * AUX_ST + BAR_F0, y1, map);
            return false;
        };
        ahead(0, lds32(yp + 32 + e_l));
        __syncwarp();
        if (lane == 0) asm volatile("mbarrier.arrive.shared::cta.b64 _, [%0], %1;" ::"r"(ab + BAR_F0), "n"(F0_COUNT - 32) : "memory");
#pragma unroll 1
        for (;;) {
            if (step(1, 2)) break;
            if (step(2, 0)) break;
            if (efo < efend) prefetch_bulk(ef + efo, min(PFE, efend - efo));
            efo += 4u * PFE;
            if (step(3, 2)) break;
            if (step(4, 0)) break;
            par ^= 1u;
            if (step(5, 1)) break;
            if (pfo <= pfend) prefetch_bulk(x + pfo, pfb);
            pfo += 4u * gridDim.x * pfb;
            yp += NST * 32;
            left -= NST;
            h_l += NST * 64;
        }
        const uint32_t fin = left == NST - 1 ? 0 : left + 1;
        mbar_wait(ab + fin * AUX_ST + BAR_EM, par ^ 1u);
        if (lane == 0) asm volatile("mbarrier.arrive.shared::cta.b64 _, [%0], %1;" ::"r"(ab + fin * AUX_ST + BAR_F0), "n"(F0_COUNT) : "memory");
        asm volatile("bar.sync 2, 128;" ::: "memory");
        const int ln = threadIdx.x & 31;
#pragma unroll 4
        for (int i = 0; i < 16; i++) {
            const int kr = i * 8 + ((threadIdx.x >> 4) & 7);
            const int dj = ((i >> 1) & 1) + (i & 4), n = kr & 7;
            const int ch = 16 * (2 * (i >> 3) + dj) + 2 * (n ^ dj) + (i & 1);
            asm volatile("cp.async.cg.shared.global [%0], [%1], 16;"
                         ::"r"(s0 + WM_OFF + ((ln >> 3) & 1) * 16384 + kr * 128 + (((ln & 7) ^ n) << 4)),
                           "l"(w_mix + ch * 128 + (ln & 15) * 8) : "memory");
        }
        cp_async_arrive(s0 + MISC_OFF);
        asm volatile("cp.async.wait_all;" ::: "memory");
    }
}

typedef CUresult (*EncodeFn)(CUtensorMap*, CUtensorMapDataType, cuuint32_t, void*, const cuuint64_t*, const cuuint64_t*,
                             const cuuint32_t*, const cuuint32_t*, CUtensorMapInterleave, CUtensorMapSwizzle,
                             CUtensorMapL2promotion, CUtensorMapFloatOOBfill);

}

#define WALK 45800
#define LEAD 6700

extern "C" void kernel_launch(void* const* d_in, const int* in_sizes, int n_in, void* d_out, int out_size) {
    const char* x = (const char*)d_in[0];
    const int* src = (const int*)d_in[1];
    const int* dst = (const int*)d_in[2];
    const uint2* Y = (const uint2*)d_in[3];
    const char* ef = (const char*)d_in[4];
    const __nv_bfloat16* w_rad = (const __nv_bfloat16*)d_in[5];
    const __nv_bfloat16* cg = (const __nv_bfloat16*)d_in[6];
    const __nv_bfloat16* w_mix = (const __nv_bfloat16*)d_in[7];
    const int N = in_sizes[0] / 512;
    const int E = in_sizes[1];

    static int num_cta = 0;
    static EncodeFn encode = nullptr;
    if (num_cta == 0) {
        int dev = 0, sms = 0;
        cudaGetDevice(&dev);
        cudaDeviceGetAttribute(&sms, cudaDevAttrMultiProcessorCount, dev);
        num_cta = sms < MAXCTA ? sms : MAXCTA;
        cudaFuncSetAttribute(tfn_kernel, cudaFuncAttributeMaxDynamicSharedMemorySize, SMEM_BYTES);
        void* fn = nullptr;
        cudaDriverEntryPointQueryResult qr;
        cudaGetDriverEntryPoint("cuTensorMapEncodeTiled", &fn, cudaEnableDefault, &qr);
        encode = (EncodeFn)fn;
    }
    int S = (N + num_cta - 1) / num_cta;
    if (S < 2) S = 2;
    const int EPC = ((E + num_cta - 1) / num_cta + 3) & ~3;
    if (S > SMAX || (E + 127) / 128 > 2 * NWARP * num_cta || N < 128 || N > 16384 || E <= 0 || E > (1 << 20) || encode == nullptr) return;
    CUtensorMap xmap;
    const cuuint64_t gd[2] = {64, (cuuint64_t)N * 8}, gs[1] = {128};
    const cuuint32_t bx[2] = {64, BOX_LINES}, es[2] = {1, 1};
    if (encode(&xmap, CU_TENSOR_MAP_DATA_TYPE_BFLOAT16, 2, (void*)x, gd, gs, bx, es, CU_TENSOR_MAP_INTERLEAVE_NONE,
               CU_TENSOR_MAP_SWIZZLE_128B, CU_TENSOR_MAP_L2_PROMOTION_NONE, CU_TENSOR_MAP_FLOAT_OOB_FILL_NONE) != CUDA_SUCCESS)
        return;
    const uint32_t magicS = (uint32_t)((0x100000000ull + S - 1) / S);
    uint32_t magicB = (uint32_t)(((unsigned long long)NB << 32) / N);
    int walk = WALK, lead = LEAD;
    double pc = (double)walk * ((double)E / N * S / 2432.0) / (16.0 * N);
    if (pc > 0.99) pc = 0.99;
    uint32_t pace = (uint32_t)(pc * 4096.0 + 0.5), curve = 0;
    const uint32_t pfb = ((uint32_t)(1024.0 * N / E * 40.0) + 127u) & ~127u;
    tfn_kernel<<<num_cta, NT, SMEM_BYTES, cudaStreamPerThread>>>(xmap, x, src, dst, Y, ef, w_rad, cg, w_mix, (uint32_t*)d_out, N, E, S,
                                                                 EPC, magicS, magicB, 0u, pace, lead, pfb, curve);
}
```

```cpp
#include <cuda_runtime.h>
#include <cuda.h>
#include <cuda_bf16.h>
#include <stdint.h>
#include <stddef.h>

namespace {

constexpr int NT = 384;
constexpr int NWARP = NT / 32;
constexpr int MAXCTA = 132;
constexpr int SFAST = 80;
constexpr int SMAX = 96;
constexpr int EPC_MAX = 3072;
constexpr int RND = 10;
constexpr int NB = 96;
constexpr int GCAP = 800;
constexpr int NCOL = NWARP - 1;
constexpr int KCAP = 1024;
constexpr int RND0 = 8;
constexpr uint32_t TAGM = 31u;
constexpr int NST = 5;
constexpr uint32_t F0_COUNT = 33;
#define SLEEPNS 100
constexpr uint32_t SLEEP = SLEEPNS;
constexpr uint32_t PFA = 2, PFE = 2048;
constexpr int SPIN_LIMIT = 1 << 22;

constexpr int XREG = 4 * NST * 2048 + 256;
constexpr int AUX_OFF = 4 * XREG;
constexpr int AUX_ST = 2560, AUX_GR = 640;
constexpr int BAR_F0 = 520, BAR_EM = 536;
constexpr int SY_OFF = AUX_OFF + NST * AUX_ST;
constexpr int SE_OFF = SY_OFF + 4 * GCAP * 4;
constexpr int SH_OFF = SE_OFF + 4 * GCAP * 4;
constexpr int MISC_OFF = SH_OFF + 4 * GCAP * 8;
constexpr int ZERO_OFF = ((MISC_OFF + 1024 + 2047) & ~2047) - 1024;
constexpr int WM_OFF = (SE_OFF + 1023) & ~1023;
constexpr int CNT_OFF = EPC_MAX * 16, START_OFF = CNT_OFF + 1024;
constexpr int BCNT_OFF = START_OFF + 1024;
constexpr int BCUM_OFF = BCNT_OFF + 24 * NB * 4 + 128;
constexpr int SEG_OFF = BCUM_OFF + 24 * NB * 2 + 128;
constexpr int WR_OFF = SEG_OFF + 1024;
constexpr int LDY_OFF = WR_OFF + 4096 + 128;
constexpr int GI_OFF = 0;
struct Misc {
    unsigned long long wbar;
    int node0, Sc;
    unsigned long long rbar;
    int nq[4];
    int dmax;
    uint32_t epoch, ref;
    uint32_t rseg[MAXCTA];
};
constexpr int SMEM_BYTES = ZERO_OFF + 1792;
static_assert(MISC_OFF + (int)sizeof(Misc) <= ZERO_OFF, "layout");
static_assert(SMEM_BYTES <= 227 * 1024, "shared memory");
static_assert(24 * KCAP + NCOL * RND * 32 + 64 <= 32768 && GCAP <= KCAP && LDY_OFF + EPC_MAX * 8 <= AUX_OFF && WR_OFF % 128 == 0, "tables");
static_assert(WM_OFF + 32768 <= MISC_OFF && SMAX * 2048 <= MISC_OFF, "layout");
static_assert(AUX_OFF % 256 == 0 && NB == 96 && NWARP == 12, "layout");

__device__ __align__(128) uint4 g_staged[(size_t)MAXCTA * EPC_MAX];
__device__ __align__(128) uint2 g_table[MAXCTA * 144];
__device__ unsigned int g_epoch[MAXCTA];

__device__ __forceinline__ void mma1688_z(float (&d)[4], uint32_t a0, uint32_t a1, uint32_t b0) {
    asm volatile(
        "mma.sync.aligned.m16n8k8.row.col.f32.bf16.bf16.f32 {%0,%1,%2,%3}, {%4,%5}, {%6}, {%7,%7,%7,%7};"
        : "=f"(d[0]), "=f"(d[1]), "=f"(d[2]), "=f"(d[3])
        : "r"(a0), "r"(a1), "r"(b0), "f"(0.0f));
}
__device__ __forceinline__ uint32_t pack_bf16(float lo, float hi) {
    uint32_t r;
    asm("cvt.rn.bf16x2.f32 %0, %1, %2;" : "=r"(r) : "f"(hi), "f"(lo));
    return r;
}
__device__ __forceinline__ uint32_t half_bf16x2(uint32_t v) {
    uint32_t r;
    asm("mul.bf16x2 %0, %1, %2;" : "=r"(r) : "r"(v), "r"(0x3f003f00u));
    return r;
}
__device__ __forceinline__ uint4 lds128(uint32_t a) {
    uint4 v;
    asm volatile("ld.shared.v4.u32 {%0,%1,%2,%3}, [%4];" : "=r"(v.x), "=r"(v.y), "=r"(v.z), "=r"(v.w) : "r"(a) : "memory");
    return v;
}
__device__ __forceinline__ uint32_t lds32(uint32_t a) {
    uint32_t v;
    asm volatile("ld.shared.u32 %0, [%1];" : "=r"(v) : "r"(a) : "memory");
    return v;
}
__device__ __forceinline__ uint2 lds64(uint32_t a) {
    uint2 v;
    asm volatile("ld.shared.v2.u32 {%0,%1}, [%2];" : "=r"(v.x), "=r"(v.y) : "r"(a) : "memory");
    return v;
}
__device__ __forceinline__ uint32_t atoms_add(uint32_t a, uint32_t v) {
    uint32_t r;
    asm volatile("atom.shared.add.u32 %0, [%1], %2;" : "=r"(r) : "r"(a), "r"(v) : "memory");
    return r;
}
__device__ __forceinline__ void sts8(uint32_t a, uint32_t v) {
    asm volatile("st.shared.u8 [%0], %1;" ::"r"(a), "r"(v) : "memory");
}
__device__ __forceinline__ void sts64(uint32_t a, uint32_t v0, uint32_t v1) {
    asm volatile("st.shared.v2.u32 [%0], {%1,%2};" ::"r"(a), "r"(v0), "r"(v1) : "memory");
}
#define OCT_BYTES 8192
#define BOX_LINES 8
__device__ __forceinline__ void fetch_quad(uint32_t dst, uint32_t bar, const uint4& y, uint64_t map) {
    asm volatile("{\n\t.reg .pred P;\n\telect.sync _|P, 0xffffffff;\n\t"
                 "@P cp.async.bulk.tensor.2d.shared::cluster.global.mbarrier::complete_tx::bytes [%0], [%6, {0, %2}], [%1];\n\t"
                 "@P cp.async.bulk.tensor.2d.shared::cluster.global.mbarrier::complete_tx::bytes [%0+%7], [%6, {0, %3}], [%1];\n\t"
                 "@P cp.async.bulk.tensor.2d.shared::cluster.global.mbarrier::complete_tx::bytes [%0+%8], [%6, {0, %4}], [%1];\n\t"
                 "@P cp.async.bulk.tensor.2d.shared::cluster.global.mbarrier::complete_tx::bytes [%0+%9], [%6, {0, %5}], [%1];\n\t}"
                 ::"r"(dst), "r"(bar), "r"(y.x), "r"(y.y), "r"(y.z), "r"(y.w), "l"(map), "n"(XREG), "n"(2 * XREG), "n"(3 * XREG)
                 : "memory");
}
__device__ __forceinline__ void cp_async_arrive(uint32_t bar) {
    asm volatile("cp.async.mbarrier.arrive.noinc.shared::cta.b64 [%0];" ::"r"(bar) : "memory");
}
__device__ __forceinline__ void mbar_init(uint32_t bar, uint32_t count) {
    asm volatile("mbarrier.init.shared::cta.b64 [%0], %1;" ::"r"(bar), "r"(count) : "memory");
}
__device__ __forceinline__ bool mbar_try(uint32_t bar, uint32_t parity) {
    uint32_t ok;
    asm volatile("{\n\t.reg .pred p;\n\tmbarrier.try_wait.parity.shared::cta.b64 p, [%1], %2;\n\tselp.u32 %0, 1, 0, p;\n\t}"
                 : "=r"(ok) : "r"(bar), "r"(parity) : "memory");
    return ok;
}
__device__ __forceinline__ void mbar_wait(uint32_t bar, uint32_t parity) {
    if (mbar_try(bar, parity)) return;
#pragma unroll 1
    for (int it = 0; it < SPIN_LIMIT; it++)
        if (mbar_try(bar, parity)) return;
    __trap();
}
__device__ __forceinline__ uint32_t clock_lo() {
    uint32_t v;
    asm volatile("mov.u32 %0, %%clock;" : "=r"(v));
    return v;
}
__device__ __forceinline__ uint32_t global_ticks() {
    uint32_t v;
    asm volatile("mov.u32 %0, %%globaltimer_lo;" : "=r"(v));
    return v >> 5;
}

#define TBL(snd, own) ((snd) * 144 + (own))
__device__ __forceinline__ void prefetch_line(const void* p) { asm volatile("prefetch.global.L2 [%0];" ::"l"(p)); }
__device__ __forceinline__ void prefetch_bulk(const void* p, uint32_t bytes) {
    asm volatile("{\n\t.reg .pred P;\n\telect.sync _|P, 0xffffffff;\n\t@P cp.async.bulk.prefetch.L2.global [%0], %1;\n\t}"
                 ::"l"(p), "r"(bytes) : "memory");
}
__device__ __forceinline__ uint4 ld_entry(const uint4* p) {
    uint4 e;
    asm volatile("ld.relaxed.gpu.global.v4.u32 {%0,%1,%2,%3}, [%4];" : "=r"(e.x), "=r"(e.y), "=r"(e.z), "=r"(e.w) : "l"(p) : "memory");
    return e;
}
__device__ __forceinline__ uint4 wait_entry(const uint4* p, uint4 e, uint32_t tag) {
    int it = 0;
    while (((e.y ^ tag) & TAGM) != 0u) {
        if (++it > SPIN_LIMIT) __trap();
        e = ld_entry(p);
    }
    return e;
}
__device__ __forceinline__ uint4 ldg128_if(bool p, const void* a, uint32_t other) {
    uint4 v = make_uint4(other, other, other, other);
    asm volatile("{\n\t.reg .pred P;\n\tsetp.ne.u32 P, %5, 0;\n\t@P ld.global.nc.L1::no_allocate.v4.u32 {%0,%1,%2,%3}, [%4];\n\t}"
                 : "+r"(v.x), "+r"(v.y), "+r"(v.z), "+r"(v.w) : "l"(a), "r"((uint32_t)p));
    return v;
}
__device__ __forceinline__ void stg64_if(bool p, void* a, uint32_t v0, uint32_t v1) {
    asm volatile("{\n\t.reg .pred P;\n\tsetp.ne.u32 P, %0, 0;\n\t@P st.global.v2.u32 [%1], {%2,%3};\n\t}"
                 ::"r"((uint32_t)p), "l"(a), "r"(v0), "r"(v1) : "memory");
}
__device__ __forceinline__ float bf_lo(uint32_t v) { return __uint_as_float(v << 16); }
__device__ __forceinline__ float bf_hi(uint32_t v) { return __uint_as_float(v & 0xffff0000u); }

#define F8(o) "+f"(d[o]), "+f"(d[o + 1]), "+f"(d[o + 2]), "+f"(d[o + 3]), "+f"(d[o + 4]), "+f"(d[o + 5]), "+f"(d[o + 6]), "+f"(d[o + 7])
template <int T>
__device__ __forceinline__ void wgmma_tiles(float (&d)[40], uint64_t a, uint64_t b, uint32_t acc) {
    if constexpr (T == 1)
        asm volatile("{\n\t.reg .pred P;\n\tsetp.ne.u32 P, %10, 0;\n\twgmma.mma_async.sync.aligned.m64n16k16.f32.bf16.bf16 "
                     "{%0,%1,%2,%3,%4,%5,%6,%7}, "
                     "%8, %9, P, 1, 1, 1, 0;\n\t}"
                     : F8(0) : "l"(a), "l"(b), "r"(acc));
    if constexpr (T == 2)
        asm volatile("{\n\t.reg .pred P;\n\tsetp.ne.u32 P, %18, 0;\n\twgmma.mma_async.sync.aligned.m64n32k16.f32.bf16.bf16 "
                     "{%0,%1,%2,%3,%4,%5,%6,%7,%8,%9,%10,%11,%12,%13,%14,%15}, "
                     "%16, %17, P, 1, 1, 1, 0;\n\t}"
                     : F8(0), F8(8) : "l"(a), "l"(b), "r"(acc));
    if constexpr (T == 3)
        asm volatile("{\n\t.reg .pred P;\n\tsetp.ne.u32 P, %26, 0;\n\twgmma.mma_async.sync.aligned.m64n48k16.f32.bf16.bf16 "
                     "{%0,%1,%2,%3,%4,%5,%6,%7,%8,%9,%10,%11,%12,%13,%14,%15,%16,%17,%18,%19,%20,%21,%22,%23}, "
                     "%24, %25, P, 1, 1, 1, 0;\n\t}"
                     : F8(0), F8(8), F8(16) : "l"(a), "l"(b), "r"(acc));
    if constexpr (T == 4)
        asm volatile("{\n\t.reg .pred P;\n\tsetp.ne.u32 P, %34, 0;\n\twgmma.mma_async.sync.aligned.m64n64k16.f32.bf16.bf16 "
                     "{%0,%1,%2,%3,%4,%5,%6,%7,%8,%9,%10,%11,%12,%13,%14,%15,%16,%17,%18,%19,%20,%21,%22,%23,%24,%25,%26,%27,%28,%29,%30,%31}, "
                     "%32, %33, P, 1, 1, 1, 0;\n\t}"
                     : F8(0), F8(8), F8(16), F8(24) : "l"(a), "l"(b), "r"(acc));
    if constexpr (T == 5)
        asm volatile("{\n\t.reg .pred P;\n\tsetp.ne.u32 P, %42, 0;\n\twgmma.mma_async.sync.aligned.m64n80k16.f32.bf16.bf16 "
                     "{%0,%1,%2,%3,%4,%5,%6,%7,%8,%9,%10,%11,%12,%13,%14,%15,%16,%17,%18,%19,%20,%21,%22,%23,%24,%25,%26,%27,%28,%29,%30,%31,%32,%33,%34,%35,%36,%37,%38,%39}, "
                     "%40, %41, P, 1, 1, 1, 0;\n\t}"
                     : F8(0), F8(8), F8(16), F8(24), F8(32) : "l"(a), "l"(b), "r"(acc));
}
template <int T, int O>
__device__ __forceinline__ void mix_tiles(float (&d)[40], uint64_t da, uint64_t db) {
    asm volatile("wgmma.fence.sync.aligned;" ::: "memory");
#pragma unroll
    for (int ks = 0; ks < 8; ks++) wgmma_tiles<T>(d, da + ks * 128, db + O * 128 + (ks >> 1) * (XREG / 16) + (ks & 1) * 16, ks);
    asm volatile("wgmma.commit_group.sync.aligned;" ::: "memory");
}
template <int T, int O, int PENDING>
__device__ __forceinline__ void store_tiles(float (&d)[40], uint32_t* op, int left, uint32_t bar) {
    asm volatile("wgmma.wait_group.sync.aligned %0;" ::"n"(PENDING) : "memory");
#pragma unroll
    for (int i = 0; i < 8 * T; i++) asm volatile("" : "+f"(d[i])::"memory");
#pragma unroll
    for (int k = 0; k < T; k++) {
        const int n = 16 * ((O + k) % 5) + (O + k) / 5;
#pragma unroll
        for (int u = 0; u < 2; u++)
            stg64_if(n < left, op + n * 256 + u * 16, pack_bf16(d[8 * k + 2 * u], d[8 * k + 2 * u + 1]),
                     pack_bf16(d[8 * k + 4 + 2 * u], d[8 * k + 4 + 2 * u + 1]));
    }
    if (PENDING) asm volatile("bar.sync %0, 128;" ::"r"(bar) : "memory");
}

__device__ __noinline__ void slow_cta(unsigned char* smem, const char* x, const char* ef, const __nv_bfloat16* w_rad,
                                      const __nv_bfloat16* cg, const __nv_bfloat16* w_mix, uint32_t* out, int node0, int Sc,
                                      uint32_t tag) {
    float* agg = reinterpret_cast<float*>(smem);
    Misc& ms = *reinterpret_cast<Misc*>(smem + MISC_OFF);
    const int tid = threadIdx.x, lane = tid & 31, warp = tid >> 5;
#pragma unroll 1
    for (int i = tid; i < Sc * 512; i += NT) agg[i] = 0.f;
    if (tid < (int)gridDim.x) {
        uint32_t v;
        asm volatile("ld.relaxed.gpu.global.u32 %0, [%1];" : "=r"(v) : "l"(&g_table[TBL(tid, blockIdx.x)]) : "memory");
        ms.rseg[tid] = v;
    }
    __syncthreads();
    uint2 wr[16];
#pragma unroll
    for (int f = 0; f < 16; f++) wr[f] = *reinterpret_cast<const uint2*>(w_rad + f * 128 + 4 * lane);
    float cgl[4];
#pragma unroll
    for (int f = 0; f < 4; f++) cgl[f] = __bfloat162float(cg[((lane >> 2) & 3) * 16 + f * 4 + (lane & 3)]);
    for (int s = 0; s < (int)gridDim.x; s++) {
        const int cn = ms.rseg[s] & 0xfffu;
        const uint4* p = g_staged + s * EPC_MAX + ((ms.rseg[s] >> 12) & 0xfffu);
        for (int i0 = 0; i0 < cn; i0 += 32) {
          uint4 el = make_uint4(0u, 0u, 0u, 0u);
          int dll = -1;
          if (i0 + lane < cn) {
              el = wait_entry(p + i0 + lane, ld_entry(p + i0 + lane), tag);
              dll = (int)(((el.y >> 25) & 31u) * 4 + (((el.x >> 20) / NB) & 3u));
          }
          for (uint32_t m = __ballot_sync(0xffffffffu, dll >= 0 && dll % NWARP == warp); m; m &= m - 1) {
            const int from = __ffs(m) - 1;
            const uint4 e = make_uint4(__shfl_sync(0xffffffffu, el.x, from), __shfl_sync(0xffffffffu, el.y, from),
                                       __shfl_sync(0xffffffffu, el.z, from), __shfl_sync(0xffffffffu, el.w, from));
            float* ap = agg + __shfl_sync(0xffffffffu, dll, from) * 512 + lane;
            const uint4* xp = reinterpret_cast<const uint4*>(x + (size_t)(e.x & 0x1fff8u) * 128 + lane * 32);
            const uint4* fp = reinterpret_cast<const uint4*>(ef + (e.y & 0x1ffffe0u));
            const uint4 xa = xp[0], xb = xp[1], fa = fp[0], fb = fp[1];
            const uint32_t fv[8] = {fa.x, fa.y, fa.z, fa.w, fb.x, fb.y, fb.z, fb.w};
            const uint32_t xv[8] = {xa.x, xa.y, xa.z, xa.w, xb.x, xb.y, xb.z, xb.w};
            float h[4] = {0.f, 0.f, 0.f, 0.f};
#pragma unroll
            for (int f = 0; f < 16; f++) {
                const float v = (f & 1) ? bf_hi(fv[f >> 1]) : bf_lo(fv[f >> 1]);
                h[0] += v * bf_lo(wr[f].x); h[1] += v * bf_hi(wr[f].x); h[2] += v * bf_lo(wr[f].y); h[3] += v * bf_hi(wr[f].y);
            }
            const float wl = bf_lo(e.z) * cgl[0] + bf_hi(e.z) * cgl[1] + bf_lo(e.w) * cgl[2] + bf_hi(e.w) * cgl[3];
#pragma unroll
            for (int k = 0; k < 4; k++) h[k] = __fdividef(h[k], 1.f + __expf(-h[k]));
#pragma unroll
            for (int o = 0; o < 4; o++) {
                const float w0 = __shfl_sync(0xffffffffu, wl, o), w1 = __shfl_sync(0xffffffffu, wl, 4 + o);
                const float w2 = __shfl_sync(0xffffffffu, wl, 8 + o), w3 = __shfl_sync(0xffffffffu, wl, 12 + o);
#pragma unroll
                for (int k = 0; k < 4; k++) {
                    const float tp = bf_lo(xv[2 * k]) * w0 + bf_hi(xv[2 * k]) * w1 + bf_lo(xv[2 * k + 1]) * w2 + bf_hi(xv[2 * k + 1]) * w3;
                    ap[(k * 4 + o) * 32] += tp * h[k];
                }
            }
          }
        }
    }
    __syncthreads();
    for (int n = tid >> 7; n < Sc; n += NT / 128) {
        const int d = tid & 127;
        float o[4] = {0.f, 0.f, 0.f, 0.f};
#pragma unroll 4
        for (int c = 0; c < 128; c++) {
            const float* a = agg + n * 512 + (c & 3) * 128 + (c >> 2);
            const float w = __bfloat162float(w_mix[c * 128 + d]);
            o[0] += a[0] * w; o[1] += a[32] * w; o[2] += a[64] * w; o[3] += a[96] * w;
        }
        *reinterpret_cast<uint2*>(out + (size_t)(node0 + n) * 256 + d * 2) = make_uint2(pack_bf16(o[0], o[1]), pack_bf16(o[2], o[3]));
    }
}

__global__ void __launch_bounds__(NT, 1)
tfn_kernel(const __grid_constant__ CUtensorMap xmap, const char* __restrict__ x, const int* __restrict__ src,
           const int* __restrict__ dst, const uint2* __restrict__ Y, const char* __restrict__ ef,
           const __nv_bfloat16* __restrict__ w_rad, const __nv_bfloat16* __restrict__ cg,
           const __nv_bfloat16* __restrict__ w_mix, uint32_t* __restrict__ out, int N, int E, int S, int EPC,
           uint32_t magicS, uint32_t negS, uint32_t magicB, uint32_t zero, uint32_t pace, int lead, uint32_t pfb, uint32_t curve) {
    extern __shared__ __align__(1024) unsigned char smem[];
    Misc& ms = *reinterpret_cast<Misc*>(smem + MISC_OFF);
    int* const cnt = reinterpret_cast<int*>(smem + CNT_OFF);
    int* const start = reinterpret_cast<int*>(smem + START_OFF);
    uint2* const bcnt = reinterpret_cast<uint2*>(smem + BCNT_OFF);
    const int tid = threadIdx.x;
    const int lane = tid & 31, warp = __shfl_sync(0xffffffffu, tid >> 5, 0);
    const int c = blockIdx.x;
    const int numCTA = gridDim.x;
    const int node0 = c * S;
    const int Sc = max(0, min(S, N - node0));
    const uint32_t sb = (uint32_t)__cvta_generic_to_shared(smem);

    const int e0[2] = {(warp * numCTA + c) * 128 + 4 * lane, ((warp + NWARP) * numCTA + c) * 128 + 4 * lane};
    int d8[8], s8[8];
#pragma unroll
    for (int h = 0; h < 2; h++) {
        const uint4 v = ldg128_if(e0[h] + 3 < E, dst + e0[h], (MAXCTA + 4 + lane) * S);
        d8[4 * h] = (int)v.x; d8[4 * h + 1] = (int)v.y; d8[4 * h + 2] = (int)v.z; d8[4 * h + 3] = (int)v.w;
    }
#pragma unroll
    for (int h = 0; h < 2; h++) {
        const uint4 v = ldg128_if(e0[h] + 3 < E, src + e0[h], 0u);
        s8[4 * h] = (int)v.x; s8[4 * h + 1] = (int)v.y; s8[4 * h + 2] = (int)v.z; s8[4 * h + 3] = (int)v.w;
    }
    if (tid == NT - 64) asm volatile("prefetch.tensormap [%0];" ::"l"(&xmap) : "memory");
    uint32_t ep0 = 0;
    if (tid == NT - 1) asm volatile("ld.relaxed.gpu.global.u32 %0, [%1];" : "=r"(ep0) : "l"(&g_epoch[c]) : "memory");
    if (warp == 7) {
        for (int i = c + lane * numCTA; i <= 32 + 256; i += 32 * numCTA)
            prefetch_line(i < 32 ? (const char*)w_rad + i * 128 : (i < 288 ? (const char*)w_mix + (i - 32) * 128 : (const char*)cg));
    }
    if (tid < MAXCTA) cnt[tid] = 0;
#pragma unroll
    for (int k = 0; k < 3; k++) bcnt[tid + k * NT] = make_uint2(0u, 0u);
    if (tid < 224) reinterpret_cast<uint2*>(smem + ZERO_OFF)[tid] = make_uint2(0u, 0u);
    if (tid >= 160 && tid < 320) {
        const int i = tid - 160;
        *reinterpret_cast<uint32_t*>(smem + AUX_OFF + (i >> 5) * AUX_ST + ((i >> 3) & 3) * AUX_GR + 512 + (i & 7) * 16) =
            (i >> 5) == NST - 1 ? (uint32_t)(1 - NST) << 24 : 1u << 24;
    }
    auto load_y = [&]() {
#pragma unroll
        for (int h = 0; h < 4; h++) {
            const int i = e0[h >> 1] - 2 * lane + (h & 1) * 64;
            asm volatile("cp.async.cg.shared.global [%0], [%1], 16, %2;" ::"r"(sb + LDY_OFF + warp * 2048 + h * 512 + lane * 16),
                         "l"(Y + min(i, E - 1 & ~1)), "r"(max(0, min(2, E - i)) * 8) : "memory");
        }
    };
    if (lane < NST && warp < 8) {
        const int k = warp >> 2;
        mbar_init(sb + AUX_OFF + lane * AUX_ST + (warp & 3) * AUX_GR + BAR_F0 + 16 * k, k == 0 ? F0_COUNT : 2u);
    }
    if (tid == 330) { mbar_init(sb + MISC_OFF + 16, 1); mbar_init(sb + MISC_OFF, 128); ms.node0 = node0; ms.Sc = Sc; ms.dmax = -32768; ms.ref = global_ticks(); }
    __syncthreads();
    load_y();
    if (E & 3) {
#pragma unroll
        for (int k = 0; k < 8; k++) {
            const int i = e0[k >> 2] + (k & 3);
            if (i >= (E & ~3) && i < E) { d8[k] = __ldg(dst + i); s8[k] = __ldg(src + i); }
        }
    }
    const uint32_t one = 1u + (lane & zero);
    const bool second = e0[1] - 4 * lane < E;
    uint32_t bin[8], pos[8];
#pragma unroll
    for (int k = 0; k < 8; k++) bin[k] = __umulhi((uint32_t)d8[k], magicS);
#pragma unroll
    for (int k = 0; k < 4; k++) pos[k] = atoms_add(sb + CNT_OFF + bin[k] * 4, one);
    if (second) {
#pragma unroll
        for (int k = 4; k < 8; k++) pos[k] = atoms_add(sb + CNT_OFF + bin[k] * 4, one);
    }
    if (tid == NT - 1) {
        ms.epoch = ep0 + 1u;
        g_epoch[c] = ep0 + 1u;
    }
    __syncthreads();
    const uint32_t epoch = ms.epoch;
    const uint32_t tag = epoch & TAGM;
    uint32_t w0[8], w1[8];
    auto words = [&](int h) {
#pragma unroll
        for (int k = 4 * h; k < 4 * h + 4; k++) {
            const uint32_t dl = (uint32_t)d8[k] + bin[k] * negS, sr = (uint32_t)s8[k];
            w0[k] = (((((dl >> 3) & ~3u) | (dl & 3u)) * NB + __umulhi(sr, magicB)) << 20) + ((dl & 16u) * 4096u + sr) * 8u;
            w1[k] = (dl >> 2) * (33u << 25) + ((uint32_t)e0[h] * 32u + tag + (k & 3) * 32);
        }
    };
    if (warp >= NWARP - 5) {
        const int w = warp - (NWARP - 5), o = tid - (NT - 160);
        int pre = 0;
#pragma unroll
        for (int k = 0; k < 4; k++)
            if (k < w) pre += cnt[lane + 32 * k];
        const int v = o < numCTA ? cnt[o] : 0;
        int incl = v;
#pragma unroll
        for (int d = 1; d < 32; d <<= 1)
            asm volatile("{\n\t.reg .pred P;\n\t.reg .b32 v;\n\tshfl.sync.up.b32 v|P, %0, %1, 0, 0xffffffff;\n\t@P add.u32 %0, %0, v;\n\t}"
                         : "+r"(incl) : "r"(d));
        const int ex = __reduce_add_sync(0xffffffffu, pre) + incl - v;
        start[o] = ex;
        if (o < numCTA)
            asm volatile("st.relaxed.gpu.global.u32 [%0], %1;" ::"l"(g_table + TBL(c, o)), "r"((epoch << 24) | (ex << 12) | v) : "memory");
    }
    __syncthreads();
    if (tid == NT - 64)
        asm volatile("mbarrier.arrive.expect_tx.shared::cta.b64 _, [%3], 4224;\n\t"
                     "cp.async.bulk.shared::cluster.global.mbarrier::complete_tx::bytes [%0], [%1], 4096, [%3];\n\t"
                     "cp.async.bulk.shared::cluster.global.mbarrier::complete_tx::bytes [%0+4096], [%2], 128, [%3];"
                     ::"r"(sb + WR_OFF), "l"(w_rad), "l"(cg), "r"(sb + MISC_OFF + 16) : "memory");
    const int ne = start[MAXCTA];
    auto scatter = [&](int h) {
#pragma unroll
        for (int k = 0; k < 4; k++) pos[4 * h + k] += lds32(sb + START_OFF + bin[4 * h + k] * 4);
        words(h);
        if (h == 0) {
            asm volatile("cp.async.wait_all;" ::: "memory");
            __syncwarp();
        }
        const uint4 ya = lds128(sb + LDY_OFF + warp * 2048 + h * 1024 + lane * 32), yb = lds128(sb + LDY_OFF + warp * 2048 + h * 1024 + lane * 32 + 16);
#pragma unroll
        for (int k = 0; k < 4; k++)
            asm volatile("{\n\t.reg .pred P;\n\tsetp.lt.u32 P, %0, %6;\n\t@P st.shared.v4.u32 [%1], {%2,%3,%4,%5};\n\t}"
                         ::"r"(bin[4 * h + k]), "r"(sb + pos[4 * h + k] * 16), "r"(w0[4 * h + k]), "r"(w1[4 * h + k]),
                           "r"(k == 0 ? ya.x : (k == 1 ? ya.z : (k == 2 ? yb.x : yb.z))),
                           "r"(k == 0 ? ya.y : (k == 1 ? ya.w : (k == 2 ? yb.y : yb.w))), "n"(MAXCTA) : "memory");
    };
    scatter(0);
    if (second) scatter(1);
    asm volatile("fence.proxy.async.shared::cta;" ::: "memory");
    __syncthreads();
    if (tid == NT - 32 && ne > 0) {
        asm volatile("cp.async.bulk.global.shared::cta.bulk_group [%0], [%1], %2;" ::"l"(g_staged + (size_t)c * EPC_MAX),
                     "r"(sb), "r"(ne * 16) : "memory");
        asm volatile("cp.async.bulk.commit_group;" ::: "memory");
    }

    const int g = lane >> 2, t = lane & 3;
    uint32_t wr[4][4];
    const bool mine = warp + NCOL * lane < numCTA && warp < NCOL;
    const uint2* tp = g_table + TBL(warp + NCOL * lane, c);
    auto look = [&](const uint32_t* p, uint32_t& v) {
        asm volatile("{\n\t.reg .pred P;\n\tsetp.ne.u32 P, %2, 0;\n\t@P ld.relaxed.gpu.global.u32 %0, [%1];\n\t}"
                     : "+r"(v) : "l"(p), "r"((uint32_t)mine) : "memory");
    };
    uint32_t sv = epoch << 24;
    look(&tp->x, sv);
    if (tid == 64 && (uint32_t)(c + 1) * 4u * PFA * pfb <= (uint32_t)N * 1024u)
        asm volatile("cp.async.bulk.prefetch.L2.global [%0], %1;" ::"l"(x + (size_t)c * 4u * PFA * pfb), "r"(4u * PFA * pfb) : "memory");
    auto uni = [&](uint32_t v) { return __shfl_sync(0xffffffffu, v + (lane & zero), 0); };
    auto keep = [&](uint32_t v) { return __shfl_sync(0xffffffffu, v, lane); };
    const int pgrp = (warp + 2) & 3;
    uint32_t cgb0, cgb1, s0, maplo, maphi, e_l, h_l, f_l, w_l, eflo, efhi, fsel, bytes, pc, cu, tbase;
    {
        mbar_wait(sb + MISC_OFF + 16, 0);
        const uint4 cv = lds128(sb + WR_OFF + 4096 + (g & 3) * 32 + (t & 1) * 16);
        const uint32_t csel = g < 4 ? 0x5410u : 0x7632u;
        cgb0 = t < 2 ? __byte_perm(cv.x, cv.z, csel) : 0u;
        cgb1 = t < 2 ? __byte_perm(cv.y, cv.w, csel) : 0u;
        s0 = uni(sb);
        const uint64_t map0 = reinterpret_cast<uint64_t>(&xmap), ef0 = reinterpret_cast<uint64_t>(ef) + t * 8;
        maphi = uni((uint32_t)(map0 >> 32)); maplo = uni((uint32_t)(map0 & 0xffffffffu));
        e_l = keep(SE_OFF - SY_OFF + (4 * (g & 1) + (g >> 1)) * 4);
        h_l = keep(sb + SH_OFF + pgrp * GCAP * 8 - 64 + g * 8 + (t & 1) * 4);
        f_l = keep(sb + AUX_OFF + pgrp * AUX_GR + 512 + (g >> 1) * 32 + (t & 1) * 16 + (~g & 1));
        w_l = keep(sb + AUX_OFF + pgrp * AUX_GR + lane * 8);
        efhi = keep((uint32_t)(ef0 >> 32) + (lane & zero)); eflo = keep((uint32_t)(ef0 & 0xffffffffu));
        fsel = keep(g & 1 ? 7 : 3);
        bytes = keep(lane == 0 ? OCT_BYTES : 0u);
        pc = uni(pace); cu = uni(curve);
        tbase = clock_lo() + (uint32_t)((int)(short)(ms.ref - global_ticks()) * 63 + lead);
    }
    if (warp < 8) {
#pragma unroll
        for (int j = 0; j < 4; j++) {
            const int dj = (j & 1) + 4 * (j >> 1);
            const uint32_t p = sb + WR_OFF + t * 4 * 256 + 32 * (2 * ((warp >> 2) & 1) + dj) + 4 * (g ^ dj);
#pragma unroll
            for (int i = 0; i < 4; i++) wr[j][i] = lds32(p + i * 256);
        }
#pragma unroll
        for (int j = 0; j < 4; j++) {
            uint32_t h[4];
#pragma unroll
            for (int i = 0; i < 4; i++) h[i] = half_bf16x2(wr[j][i]);
            wr[j][0] = __byte_perm(h[0], h[1], 0x5410);
            wr[j][1] = __byte_perm(h[0], h[1], 0x7632);
            wr[j][2] = __byte_perm(h[2], h[3], 0x5410);
            wr[j][3] = __byte_perm(h[2], h[3], 0x7632);
        }
    }

    uint4 ent[RND];
    uint32_t rk[RND];
    int tot = 0;
#pragma unroll
    for (int r = 0; r < RND; r++) { ent[r].x = (24 * NB + lane) << 19; rk[r] = 0; }
    if (warp == NWARP - 1) {
        asm volatile("cp.async.bulk.wait_group 0;" ::: "memory");
        __syncwarp();
        const uint32_t w = (epoch << 16) | (global_ticks() & 0xffffu);
#pragma unroll
        for (int k = 0; k < 5; k++)
            asm volatile("{\n\t.reg .pred P;\n\tsetp.lt.s32 P, %0, %1;\n\t@P st.relaxed.gpu.global.u32 [%2+4], %3;\n\t}"
                         ::"r"(lane + 32 * k), "n"(144), "l"(g_table + TBL(c, lane) + 32 * k), "r"(w) : "memory");
    } else {
        const uint4* gp[RND];
        auto poll = [&](const uint32_t* p, uint32_t& v, int sh) {
#pragma unroll 1
            for (int it = 0; !__all_sync(0xffffffffu, ((v ^ (epoch << sh)) >> sh) == 0u); it++) {
                if (it > SPIN_LIMIT) __trap();
                look(p, v);
            }
        };
        poll(&tp->x, sv, 24);
        int incl = (int)(sv & 0xfffu);
#pragma unroll
        for (int o = 1; o < 16; o <<= 1) {
            asm volatile("{\n\t.reg .pred P;\n\t.reg .b32 v;\n\tshfl.sync.up.b32 v|P, %0, %1, 0, 0xffffffff;\n\t@P add.u32 %0, %0, v;\n\t}"
                         : "+r"(incl) : "r"(o));
        }
        tot = __shfl_sync(0xffffffffu, incl, 15);
        const bool some = (sv & 0xfffu) != 0u;
        const uint32_t seg_b = sb + SEG_OFF + warp * 64;
        asm volatile("{\n\t.reg .pred P;\n\tsetp.ne.u32 P, %2, 0;\n\t@P st.shared.u32 [%0], %1;\n\t}"
                     ::"r"(seg_b + 4 * __popc(__ballot_sync(0xffffffffu, some) & ((1u << lane) - 1u))),
                       "r"((warp + NCOL * lane) * EPC_MAX + (int)((sv >> 12) & 0xfffu) - incl + (int)(sv & 0xfffu)), "r"((uint32_t)some) : "memory");
        __syncwarp();
        if (!some) incl = -1;
        const uint32_t le = (2u << lane) - 1u;
        uint32_t sg = seg_b;
#pragma unroll
        for (int r = 0; r < RND; r++) {
            uint32_t bit;
            asm("shl.b32 %0, 1, %1;" : "=r"(bit) : "r"(incl - 32 * r));
            const uint32_t ends = __reduce_or_sync(0xffffffffu, bit);
            gp[r] = g_staged + (lane + 32 * r + (int)lds32(sg + 4 * __popc(ends & le)));
            sg += 4 * __popc(ends);
            ent[r].y = tag;
        }
        const uint32_t ref = ms.ref;
        uint32_t ts = (epoch << 16) | (ref & 0xffffu);
        look(&tp->y, ts);
        poll(&tp->y, ts, 16);
#pragma unroll
        for (int r = 0; r < RND; r++)
            if (lane + 32 * r < tot) ent[r] = ld_entry(gp[r]);
        asm volatile("{\n\t.reg .pred P;\n\tsetp.ne.u32 P, %2, 0;\n\t@P red.shared.max.s32 [%0], %1;\n\t}"
                     ::"r"(sb + MISC_OFF + (uint32_t)offsetof(Misc, dmax)), "r"(__reduce_max_sync(0xffffffffu, (int)(short)(ts - ref))),
                       "r"(bytes) : "memory");
        uint32_t stale = 0;
#pragma unroll
        for (int r = 0; r < RND; r++) stale |= ent[r].y ^ tag;
        if (stale & TAGM) {
#pragma unroll
            for (int r = 0; r < RND; r++)
                if (lane + 32 * r < tot) ent[r] = wait_entry(gp[r], ent[r], tag);
        }
#pragma unroll
        for (int r = 0; r < RND0; r++) rk[r] = atoms_add(sb + BCNT_OFF + (ent[r].x >> 17), one);
        if (tot > 32 * RND0) {
#pragma unroll
            for (int r = RND0; r < RND; r++) rk[r] = atoms_add(sb + BCNT_OFF + (ent[r].x >> 17), one);
        }
    }
    __syncthreads();
    bool over = tot > 32 * RND || S > SFAST;
    {
        const int grp = warp & 3, u = warp >> 2;
        uint32_t v[3], incl[3], lo[3], hi[3], tt[3];
#pragma unroll
        for (int p = 0; p < 3; p++) {
            uint32_t a[3];
#pragma unroll
            for (int i = 0; i < 3; i++) {
                const uint2 w = bcnt[(4 * p + grp) * NB + 32 * i + lane];
                a[i] = w.x + (w.y << 16);
            }
            v[p] = u == 0 ? a[0] : (u == 1 ? a[1] : a[2]);
            incl[p] = v[p];
            lo[p] = __reduce_add_sync(0xffffffffu, u == 0 ? 0u : (u == 1 ? a[0] : a[0] + a[1]));
            tt[p] = __reduce_add_sync(0xffffffffu, a[0] + a[1] + a[2]);
        }
#pragma unroll
        for (int o = 1; o < 32; o <<= 1)
#pragma unroll
            for (int p = 0; p < 3; p++) {
                asm volatile("{\n\t.reg .pred P;\n\t.reg .b32 v;\n\tshfl.sync.up.b32 v|P, %0, %1, 0, 0xffffffff;\n\t@P add.u32 %0, %0, v;\n\t}"
                             : "+r"(incl[p]) : "r"(o));
            }
        uint32_t all = 0, nq = 0;
#pragma unroll
        for (int p = 0; p < 3; p++) {
            const uint32_t up = (tt[p] + 0x30003u) & 0xfffcfffcu, tb = (8 * p + 2 * grp) * KCAP * 0x10001u + (KCAP << 16);
            nq += up;
            incl[p] += lo[p] + up - tt[p] + tb;
            v[p] = incl[p] - v[p];
            *reinterpret_cast<uint32_t*>(smem + BCUM_OFF + ((4 * p + grp) * NB + 32 * u + lane) * 4) = v[p];
            lo[p] = warp < 4 && lane == 0 ? tb : (v[p] + 0x10001u) & 0xfffcfffcu;
            hi[p] = (incl[p] + 0x10001u) & 0xfffcfffcu;
            all += lo[p] - tb;
        }
        nq = ((nq & 0xffffu) + (nq >> 16)) >> 2;
        uint32_t run = (all & 0xffffu) + (all >> 16) + (nq & 1u) * 4u + grp * GCAP, rel[5];
#pragma unroll
        for (int i = 0; i < 5; i++) {
            const uint32_t l = (i & 1) ? lo[i >> 1] >> 16 : lo[i >> 1] & 0xffffu, h = (i & 1) ? hi[i >> 1] >> 16 : hi[i >> 1] & 0xffffu;
            rel[i] = run - l;
            asm volatile("{\n\t.reg .pred P;\n\tsetp.lt.u32 P, %0, %1;\n\t@P st.shared.u32 [%3], %2;\n\t@P st.shared.u32 [%4+-4], %2;\n\t}"
                         ::"r"(l), "r"(h), "r"(rel[i]), "r"(s0 + GI_OFF + l), "r"(s0 + GI_OFF + h) : "memory");
            run = rel[i] + h;
        }
        if ((((hi[0] - lo[0] + 0x40004u) | (hi[1] - lo[1] + 0x40004u) | (hi[2] - lo[2] + 4u)) & 0xfff0fff0u) != 0u) {
#pragma unroll
            for (int i = 0; i < 5; i++) {
                const uint32_t l = (i & 1) ? lo[i >> 1] >> 16 : lo[i >> 1] & 0xffffu, h = (i & 1) ? hi[i >> 1] >> 16 : hi[i >> 1] & 0xffffu;
#pragma unroll 1
                for (uint32_t j = l; j < h; j += 4) *reinterpret_cast<uint32_t*>(smem + GI_OFF + j) = rel[i];
            }
        }
        if (warp < 4 && lane == 0) ms.nq[grp] = (int)nq;
        over = over || 4 * nq + 20 > GCAP;
    }
    asm volatile("fence.proxy.async.shared::cta;" ::: "memory");
    const bool slow = __syncthreads_or(over);
    {
        auto put = [&](bool ok, uint32_t idx, uint32_t y, uint32_t e, uint32_t h0, uint32_t h1) {
            asm volatile("{\n\t.reg .pred P;\n\tsetp.ne.u32 P, %0, 0;\n\t@P st.shared.u32 [%1+%7], %3;\n\t@P st.shared.u32 [%1+%8], %4;\n\t"
                         "@P st.shared.v2.u32 [%2+%9], {%5,%6};\n\t}"
                         ::"r"((uint32_t)ok), "r"(s0 + 4 * idx), "r"(s0 + 8 * idx), "r"(y), "r"(e), "r"(h0), "r"(h1),
                           "n"(SY_OFF), "n"(SE_OFF), "n"(SH_OFF) : "memory");
        };
        auto lds16 = [&](uint32_t a) {
            uint32_t v;
            asm volatile("ld.shared.u16 %0, [%1];" : "=r"(v) : "r"(a) : "memory");
            return v;
        };
        auto find = [&](int r0, int r1) {
#pragma unroll
            for (int r = r0; r < r1; r++) rk[r] += lds16(s0 + BCUM_OFF + (ent[r].x >> 18));
#pragma unroll
            for (int r = r0; r < r1; r++) rk[r] += lds32(s0 + GI_OFF + (rk[r] & 0x7ffcu));
        };
        auto place = [&](int r0, int r1) {
#pragma unroll
            for (int r = r0; r < r1; r++) put(lane + 32 * r < tot, rk[r], ent[r].x & 0x1ffffu, ent[r].y, ent[r].z, ent[r].w);
        };
        find(0, RND0);
        if (uni(slow) != 0u) {
            slow_cta(smem, x, ef, w_rad, cg, w_mix, out, node0, Sc, tag);
            return;
        }
        if (warp == NCOL) {
            uint32_t c0[3], rel[3], nq[2];
#pragma unroll
            for (int k = 0; k < 3; k++) {
                const uint32_t tile = 8 * k + g;
                c0[k] = lds16(s0 + BCUM_OFF + (tile >> 1) * NB * 4 + (tile & 1) * 2);
                rel[k] = lds32(s0 + GI_OFF + tile * KCAP);
            }
#pragma unroll
            for (int k = 0; k < 2; k++) nq[k] = ms.nq[2 * k + (lane >> 4)];
            const uint32_t py = lane + 53 * c;
#pragma unroll
            for (int k = 0; k < 3; k++) {
                const uint32_t tile = 8 * k + g;
                put(t < (c0[k] & 3u), rel[k] + tile * KCAP + t, ((py + 32 * k) & 127u) * 8u, (2 * k + (g & 1)) << 27, 0u, 0u);
            }
#pragma unroll
            for (int k = 0; k < 2; k++) {
                const uint32_t i = lane & 15;
                put(i < 8 || (i < 12 && (nq[k] & 1)), (2 * k + (lane >> 4)) * GCAP + (i < 8 ? 4 * ((nq[k] + 1) & ~1u) + i : i - 8),
                    ((py + 96 + 4 * k) & 127u) * 8u, i < 8 ? 6u << 27 : 0u, 0u, 0u);
            }
        } else {
            place(0, RND0);
            if (tot > 32 * RND0) { find(RND0, RND); place(RND0, RND); }
        }
    }
    const uint32_t T0 = uni(tbase + ms.dmax * 63);
    int left = (int)uni((uint32_t)(ms.nq[pgrp] + 1) >> 1);
    __syncthreads();

    if (warp < 8) {
        asm volatile("setmaxnreg.inc.sync.aligned.u32 232;");
        const int half = warp >> 2, grp = (warp + half) & 3;
        const uint32_t az = __shfl_sync(0xffffffffu, sb + ZERO_OFF + (g >> 1) * 512 + t * 32 + (g & 1) * 16, lane);
        uint32_t sb2;
        asm volatile(
            "{\n"
            ".reg .f32 c<160>, h<16>, th<8>, fz;\n"
            ".reg .b32 x<16>, a<4>, r<4>, rd<8>, e<2>, p<80>, mt, xa, aa, an<4>, ab, ea, tmp, cnt, st, rl, rh, dum, du2;\n"
            ".reg .b16 lo, hi;\n"
            ".reg .pred pk, pm, pw, pe, pr, d0, d1, d2, d3, d4;\n"
            "mov.f32 fz, 0f00000000;\n"
            "mov.f32 c0, fz; mov.f32 c1, fz; mov.f32 c2, fz; mov.f32 c3, fz; mov.f32 c4, fz; mov.f32 c5, fz; mov.f32 c6, fz; mov.f32 c7, fz;\n"
            "mov.f32 c8, fz; mov.f32 c9, fz; mov.f32 c10, fz; mov.f32 c11, fz; mov.f32 c12, fz; mov.f32 c13, fz; mov.f32 c14, fz; mov.f32 c15, fz;\n"
            "mov.f32 c16, fz; mov.f32 c17, fz; mov.f32 c18, fz; mov.f32 c19, fz; mov.f32 c20, fz; mov.f32 c21, fz; mov.f32 c22, fz; mov.f32 c23, fz;\n"
            "mov.f32 c24, fz; mov.f32 c25, fz; mov.f32 c26, fz; mov.f32 c27, fz; mov.f32 c28, fz; mov.f32 c29, fz; mov.f32 c30, fz; mov.f32 c31, fz;\n"
            "mov.f32 c32, fz; mov.f32 c33, fz; mov.f32 c34, fz; mov.f32 c35, fz; mov.f32 c36, fz; mov.f32 c37, fz; mov.f32 c38, fz; mov.f32 c39, fz;\n"
            "mov.f32 c40, fz; mov.f32 c41, fz; mov.f32 c42, fz; mov.f32 c43, fz; mov.f32 c44, fz; mov.f32 c45, fz; mov.f32 c46, fz; mov.f32 c47, fz;\n"
            "mov.f32 c48, fz; mov.f32 c49, fz; mov.f32 c50, fz; mov.f32 c51, fz; mov.f32 c52, fz; mov.f32 c53, fz; mov.f32 c54, fz; mov.f32 c55, fz;\n"
            "mov.f32 c56, fz; mov.f32 c57, fz; mov.f32 c58, fz; mov.f32 c59, fz; mov.f32 c60, fz; mov.f32 c61, fz; mov.f32 c62, fz; mov.f32 c63, fz;\n"
            "mov.f32 c64, fz; mov.f32 c65, fz; mov.f32 c66, fz; mov.f32 c67, fz; mov.f32 c68, fz; mov.f32 c69, fz; mov.f32 c70, fz; mov.f32 c71, fz;\n"
            "mov.f32 c72, fz; mov.f32 c73, fz; mov.f32 c74, fz; mov.f32 c75, fz; mov.f32 c76, fz; mov.f32 c77, fz; mov.f32 c78, fz; mov.f32 c79, fz;\n"
            "mov.f32 c80, fz; mov.f32 c81, fz; mov.f32 c82, fz; mov.f32 c83, fz; mov.f32 c84, fz; mov.f32 c85, fz; mov.f32 c86, fz; mov.f32 c87, fz;\n"
            "mov.f32 c88, fz; mov.f32 c89, fz; mov.f32 c90, fz; mov.f32 c91, fz; mov.f32 c92, fz; mov.f32 c93, fz; mov.f32 c94, fz; mov.f32 c95, fz;\n"
            "mov.f32 c96, fz; mov.f32 c97, fz; mov.f32 c98, fz; mov.f32 c99, fz; mov.f32 c100, fz; mov.f32 c101, fz; mov.f32 c102, fz; mov.f32 c103, fz;\n"
            "mov.f32 c104, fz; mov.f32 c105, fz; mov.f32 c106, fz; mov.f32 c107, fz; mov.f32 c108, fz; mov.f32 c109, fz; mov.f32 c110, fz; mov.f32 c111, fz;\n"
            "mov.f32 c112, fz; mov.f32 c113, fz; mov.f32 c114, fz; mov.f32 c115, fz; mov.f32 c116, fz; mov.f32 c117, fz; mov.f32 c118, fz; mov.f32 c119, fz;\n"
            "mov.f32 c120, fz; mov.f32 c121, fz; mov.f32 c122, fz; mov.f32 c123, fz; mov.f32 c124, fz; mov.f32 c125, fz; mov.f32 c126, fz; mov.f32 c127, fz;\n"
            "mov.f32 c128, fz; mov.f32 c129, fz; mov.f32 c130, fz; mov.f32 c131, fz; mov.f32 c132, fz; mov.f32 c133, fz; mov.f32 c134, fz; mov.f32 c135, fz;\n"
            "mov.f32 c136, fz; mov.f32 c137, fz; mov.f32 c138, fz; mov.f32 c139, fz; mov.f32 c140, fz; mov.f32 c141, fz; mov.f32 c142, fz; mov.f32 c143, fz;\n"
            "mov.f32 c144, fz; mov.f32 c145, fz; mov.f32 c146, fz; mov.f32 c147, fz; mov.f32 c148, fz; mov.f32 c149, fz; mov.f32 c150, fz; mov.f32 c151, fz;\n"
            "mov.f32 c152, fz; mov.f32 c153, fz; mov.f32 c154, fz; mov.f32 c155, fz; mov.f32 c156, fz; mov.f32 c157, fz; mov.f32 c158, fz; mov.f32 c159, fz;\n"
            "mov.b32 x0, 0; mov.b32 x1, 0; mov.b32 x2, 0; mov.b32 x3, 0; mov.b32 x4, 0; mov.b32 x5, 0; mov.b32 x6, 0; mov.b32 x7, 0; mov.b32 x8, 0; mov.b32 x9, 0; mov.b32 x10, 0; mov.b32 x11, 0; mov.b32 x12, 0; mov.b32 x13, 0; mov.b32 x14, 0; mov.b32 x15, 0;\n"
            "mov.b32 a0, 0; mov.b32 a1, 0; mov.b32 a2, 0; mov.b32 a3, 0;\n"
            "elect.sync _|pe, 0xffffffff;\n"
            "mov.pred pr, pe;\n"
            "mov.b32 xa, %1; mov.b32 aa, %2; mov.b32 ea, %4;\n"
            "mov.u32 cnt, 0; and.b32 tmp, aa, 0xffffff80;\n"
            "S0L: mbarrier.try_wait.parity.shared::cta.b64 pw, [tmp+520], 0; @pw bra.uni S0D;\n"
            "add.u32 cnt, cnt, 1; setp.lt.u32 pk, cnt, 1000000; @pk bra.uni S0L; trap;\n"
            "S0D:\n"
            "ld.shared.v2.u32 {e0,e1}, [ea]; ld.shared.u32 mt, [aa+512];\n"
            "mma.sync.aligned.m16n8k16.row.col.f32.bf16.bf16.f32 {h0,h1,h2,h3}, {%7,%8,%9,%10}, {e0,e1}, {fz,fz,fz,fz};\n"
            "mma.sync.aligned.m16n8k16.row.col.f32.bf16.bf16.f32 {h4,h5,h6,h7}, {%11,%12,%13,%14}, {e0,e1}, {fz,fz,fz,fz};\n"
            "mma.sync.aligned.m16n8k16.row.col.f32.bf16.bf16.f32 {h8,h9,h10,h11}, {%15,%16,%17,%18}, {e0,e1}, {fz,fz,fz,fz};\n"
            "mma.sync.aligned.m16n8k16.row.col.f32.bf16.bf16.f32 {h12,h13,h14,h15}, {%19,%20,%21,%22}, {e0,e1}, {fz,fz,fz,fz};\n"
            "or.b32 a0, e0, mt; and.b32 a0, a0, %5;\n"
            "add.u32 xa, xa, 2048; add.u32 aa, aa, 2560; mov.u32 st, 1;\n"
            "mov.u32 cnt, 0; and.b32 tmp, aa, 0xffffff80;\n"
            "S1L: mbarrier.try_wait.parity.shared::cta.b64 pw, [tmp+520], 0; @pw bra.uni S1D;\n"
            "add.u32 cnt, cnt, 1; setp.lt.u32 pk, cnt, 1000000; @pk bra.uni S1L; trap;\n"
            "S1D:\n"
            "B0_0:\n"
            "xor.b32 tmp, mt, %3; and.b32 tmp, tmp, 1536; setp.eq.u32 pm, tmp, 0; selp.b32 ab, aa, %3, pm;\n"
            "and.b32 tmp, mt, 2048; setp.ne.u32 d0, tmp, 0; and.b32 tmp, mt, 4096; setp.ne.u32 d1, tmp, 0; and.b32 tmp, mt, 8192; setp.ne.u32 d2, tmp, 0;\n"
            "mad.lo.u32 cnt, a0, %5, ea; mad.lo.s32 ea, st, 2560, ea;\n"
            "ld.shared.u32 mt, [aa+512];\n"
            "mma.sync.aligned.m16n8k16.row.col.f32.bf16.bf16.f32 {c0,c1,c2,c3}, {a0,a1,a2,a3}, {x0,x1}, {c0,c1,c2,c3};\n"
            "mma.sync.aligned.m16n8k16.row.col.f32.bf16.bf16.f32 {c4,c5,c6,c7}, {a0,a1,a2,a3}, {x2,x3}, {c4,c5,c6,c7};\n"
            "ld.shared.v4.u32 {x0,x1,x2,x3}, [xa+0];\n"
            "tanh.approx.f32 th0, h0;\n"
            "tanh.approx.f32 th1, h2;\n"
            "fma.rn.f32 th0, h0, th0, h0;\n"
            "fma.rn.f32 th1, h2, th1, h2;\n"
            "cvt.rn.bf16x2.f32 r0, th1, th0;\n"
            "mma.sync.aligned.m16n8k16.row.col.f32.bf16.bf16.f32 {c8,c9,c10,c11}, {a0,a1,a2,a3}, {x4,x5}, {c8,c9,c10,c11};\n"
            "mma.sync.aligned.m16n8k16.row.col.f32.bf16.bf16.f32 {c12,c13,c14,c15}, {a0,a1,a2,a3}, {x6,x7}, {c12,c13,c14,c15};\n"
            "ld.shared.v4.u32 {x4,x5,x6,x7}, [xa+128];\n"
            "tanh.approx.f32 th2, h4;\n"
            "tanh.approx.f32 th3, h6;\n"
            "fma.rn.f32 th2, h4, th2, h4;\n"
            "fma.rn.f32 th3, h6, th3, h6;\n"
            "cvt.rn.bf16x2.f32 r1, th3, th2;\n"
            "mma.sync.aligned.m16n8k16.row.col.f32.bf16.bf16.f32 {c16,c17,c18,c19}, {a0,a1,a2,a3}, {x8,x9}, {c16,c17,c18,c19};\n"
            "mma.sync.aligned.m16n8k16.row.col.f32.bf16.bf16.f32 {c20,c21,c22,c23}, {a0,a1,a2,a3}, {x10,x11}, {c20,c21,c22,c23};\n"
            "ld.shared.v4.u32 {x8,x9,x10,x11}, [xa+512];\n"
            "tanh.approx.f32 th4, h8;\n"
            "tanh.approx.f32 th5, h10;\n"
            "fma.rn.f32 th4, h8, th4, h8;\n"
            "fma.rn.f32 th5, h10, th5, h10;\n"
            "cvt.rn.bf16x2.f32 r2, th5, th4;\n"
            "mma.sync.aligned.m16n8k16.row.col.f32.bf16.bf16.f32 {c24,c25,c26,c27}, {a0,a1,a2,a3}, {x12,x13}, {c24,c25,c26,c27};\n"
            "mma.sync.aligned.m16n8k16.row.col.f32.bf16.bf16.f32 {c28,c29,c30,c31}, {a0,a1,a2,a3}, {x14,x15}, {c28,c29,c30,c31};\n"
            "ld.shared.v4.u32 {x12,x13,x14,x15}, [xa+640];\n"
            "tanh.approx.f32 th6, h12;\n"
            "tanh.approx.f32 th7, h14;\n"
            "fma.rn.f32 th6, h12, th6, h12;\n"
            "fma.rn.f32 th7, h14, th7, h14;\n"
            "cvt.rn.bf16x2.f32 r3, th7, th6;\n"
            "ld.shared.v4.u32 {a0,a1,a2,a3}, [ab+0];\n"
            "@pe mbarrier.arrive.shared::cta.b64 _, [cnt+280];\n"
            "mov.b32 {lo,hi}, r0; mov.b32 rl, {lo,lo}; mov.b32 rh, {hi,hi};\n"
            "mul.bf16x2 x0, x0, rl; mul.bf16x2 x1, x1, rl; mul.bf16x2 x2, x2, rh; mul.bf16x2 x3, x3, rh;\n"
            "mov.b32 {lo,hi}, r1; mov.b32 rl, {lo,lo}; mov.b32 rh, {hi,hi};\n"
            "mul.bf16x2 x4, x4, rl; mul.bf16x2 x5, x5, rl; mul.bf16x2 x6, x6, rh; mul.bf16x2 x7, x7, rh;\n"
            "mov.b32 {lo,hi}, r2; mov.b32 rl, {lo,lo}; mov.b32 rh, {hi,hi};\n"
            "mul.bf16x2 x8, x8, rl; mul.bf16x2 x9, x9, rl; mul.bf16x2 x10, x10, rh; mul.bf16x2 x11, x11, rh;\n"
            "mov.b32 {lo,hi}, r3; mov.b32 rl, {lo,lo}; mov.b32 rh, {hi,hi};\n"
            "mul.bf16x2 x12, x12, rl; mul.bf16x2 x13, x13, rl; mul.bf16x2 x14, x14, rh; mul.bf16x2 x15, x15, rh;\n"
            "@d1 bra.uni L1; @d2 bra.uni B1_4; @d0 bra.uni B1_1; bra.uni B1_0;\n"
            "B0_1:\n"
            "xor.b32 tmp, mt, %3; and.b32 tmp, tmp, 1536; setp.eq.u32 pm, tmp, 0; selp.b32 ab, aa, %3, pm;\n"
            "and.b32 tmp, mt, 2048; setp.ne.u32 d0, tmp, 0; and.b32 tmp, mt, 4096; setp.ne.u32 d1, tmp, 0; and.b32 tmp, mt, 8192; setp.ne.u32 d2, tmp, 0;\n"
            "mad.lo.u32 cnt, a0, %5, ea; mad.lo.s32 ea, st, 2560, ea;\n"
            "ld.shared.u32 mt, [aa+512];\n"
            "mma.sync.aligned.m16n8k16.row.col.f32.bf16.bf16.f32 {c32,c33,c34,c35}, {a0,a1,a2,a3}, {x0,x1}, {c32,c33,c34,c35};\n"
            "mma.sync.aligned.m16n8k16.row.col.f32.bf16.bf16.f32 {c36,c37,c38,c39}, {a0,a1,a2,a3}, {x2,x3}, {c36,c37,c38,c39};\n"
            "ld.shared.v4.u32 {x0,x1,x2,x3}, [xa+0];\n"
            "tanh.approx.f32 th0, h0;\n"
            "tanh.approx.f32 th1, h2;\n"
            "fma.rn.f32 th0, h0, th0, h0;\n"
            "fma.rn.f32 th1, h2, th1, h2;\n"
            "cvt.rn.bf16x2.f32 r0, th1, th0;\n"
            "mma.sync.aligned.m16n8k16.row.col.f32.bf16.bf16.f32 {c40,c41,c42,c43}, {a0,a1,a2,a3}, {x4,x5}, {c40,c41,c42,c43};\n"
            "mma.sync.aligned.m16n8k16.row.col.f32.bf16.bf16.f32 {c44,c45,c46,c47}, {a0,a1,a2,a3}, {x6,x7}, {c44,c45,c46,c47};\n"
            "ld.shared.v4.u32 {x4,x5,x6,x7}, [xa+128];\n"
            "tanh.approx.f32 th2, h4;\n"
            "tanh.approx.f32 th3, h6;\n"
            "fma.rn.f32 th2, h4, th2, h4;\n"
            "fma.rn.f32 th3, h6, th3, h6;\n"
            "cvt.rn.bf16x2.f32 r1, th3, th2;\n"
            "mma.sync.aligned.m16n8k16.row.col.f32.bf16.bf16.f32 {c48,c49,c50,c51}, {a0,a1,a2,a3}, {x8,x9}, {c48,c49,c50,c51};\n"
            "mma.sync.aligned.m16n8k16.row.col.f32.bf16.bf16.f32 {c52,c53,c54,c55}, {a0,a1,a2,a3}, {x10,x11}, {c52,c53,c54,c55};\n"
            "ld.shared.v4.u32 {x8,x9,x10,x11}, [xa+512];\n"
            "tanh.approx.f32 th4, h8;\n"
            "tanh.approx.f32 th5, h10;\n"
            "fma.rn.f32 th4, h8, th4, h8;\n"
            "fma.rn.f32 th5, h10, th5, h10;\n"
            "cvt.rn.bf16x2.f32 r2, th5, th4;\n"
            "mma.sync.aligned.m16n8k16.row.col.f32.bf16.bf16.f32 {c56,c57,c58,c59}, {a0,a1,a2,a3}, {x12,x13}, {c56,c57,c58,c59};\n"
            "mma.sync.aligned.m16n8k16.row.col.f32.bf16.bf16.f32 {c60,c61,c62,c63}, {a0,a1,a2,a3}, {x14,x15}, {c60,c61,c62,c63};\n"
            "ld.shared.v4.u32 {x12,x13,x14,x15}, [xa+640];\n"
            "tanh.approx.f32 th6, h12;\n"
            "tanh.approx.f32 th7, h14;\n"
            "fma.rn.f32 th6, h12, th6, h12;\n"
            "fma.rn.f32 th7, h14, th7, h14;\n"
            "cvt.rn.bf16x2.f32 r3, th7, th6;\n"
            "ld.shared.v4.u32 {a0,a1,a2,a3}, [ab+0];\n"
            "@pe mbarrier.arrive.shared::cta.b64 _, [cnt+280];\n"
            "mov.b32 {lo,hi}, r0; mov.b32 rl, {lo,lo}; mov.b32 rh, {hi,hi};\n"
            "mul.bf16x2 x0, x0, rl; mul.bf16x2 x1, x1, rl; mul.bf16x2 x2, x2, rh; mul.bf16x2 x3, x3, rh;\n"
            "mov.b32 {lo,hi}, r1; mov.b32 rl, {lo,lo}; mov.b32 rh, {hi,hi};\n"
            "mul.bf16x2 x4, x4, rl; mul.bf16x2 x5, x5, rl; mul.bf16x2 x6, x6, rh; mul.bf16x2 x7, x7, rh;\n"
            "mov.b32 {lo,hi}, r2; mov.b32 rl, {lo,lo}; mov.b32 rh, {hi,hi};\n"
            "mul.bf16x2 x8, x8, rl; mul.bf16x2 x9, x9, rl; mul.bf16x2 x10, x10, rh; mul.bf16x2 x11, x11, rh;\n"
            "mov.b32 {lo,hi}, r3; mov.b32 rl, {lo,lo}; mov.b32 rh, {hi,hi};\n"
            "mul.bf16x2 x12, x12, rl; mul.bf16x2 x13, x13, rl; mul.bf16x2 x14, x14, rh; mul.bf16x2 x15, x15, rh;\n"
            "@d1 bra.uni L1; @d2 bra.uni B1_4; @d0 bra.uni B1_1; bra.uni B1_0;\n"
            "L0: @d0 bra.uni B0_3;\n"
            "B0_2:\n"
            "xor.b32 tmp, mt, %3; and.b32 tmp, tmp, 1536; setp.eq.u32 pm, tmp, 0; selp.b32 ab, aa, %3, pm;\n"
            "and.b32 tmp, mt, 2048; setp.ne.u32 d0, tmp, 0; and.b32 tmp, mt, 4096; setp.ne.u32 d1, tmp, 0; and.b32 tmp, mt, 8192; setp.ne.u32 d2, tmp, 0;\n"
            "mad.lo.u32 cnt, a0, %5, ea; mad.lo.s32 ea, st, 2560, ea;\n"
            "ld.shared.u32 mt, [aa+512];\n"
            "mma.sync.aligned.m16n8k16.row.col.f32.bf16.bf16.f32 {c64,c65,c66,c67}, {a0,a1,a2,a3}, {x0,x1}, {c64,c65,c66,c67};\n"
            "mma.sync.aligned.m16n8k16.row.col.f32.bf16.bf16.f32 {c68,c69,c70,c71}, {a0,a1,a2,a3}, {x2,x3}, {c68,c69,c70,c71};\n"
            "ld.shared.v4.u32 {x0,x1,x2,x3}, [xa+0];\n"
            "tanh.approx.f32 th0, h0;\n"
            "tanh.approx.f32 th1, h2;\n"
            "fma.rn.f32 th0, h0, th0, h0;\n"
            "fma.rn.f32 th1, h2, th1, h2;\n"
            "cvt.rn.bf16x2.f32 r0, th1, th0;\n"
            "mma.sync.aligned.m16n8k16.row.col.f32.bf16.bf16.f32 {c72,c73,c74,c75}, {a0,a1,a2,a3}, {x4,x5}, {c72,c73,c74,c75};\n"
            "mma.sync.aligned.m16n8k16.row.col.f32.bf16.bf16.f32 {c76,c77,c78,c79}, {a0,a1,a2,a3}, {x6,x7}, {c76,c77,c78,c79};\n"
            "ld.shared.v4.u32 {x4,x5,x6,x7}, [xa+128];\n"
            "tanh.approx.f32 th2, h4;\n"
            "tanh.approx.f32 th3, h6;\n"
            "fma.rn.f32 th2, h4, th2, h4;\n"
            "fma.rn.f32 th3, h6, th3, h6;\n"
            "cvt.rn.bf16x2.f32 r1, th3, th2;\n"
            "mma.sync.aligned.m16n8k16.row.col.f32.bf16.bf16.f32 {c80,c81,c82,c83}, {a0,a1,a2,a3}, {x8,x9}, {c80,c81,c82,c83};\n"
            "mma.sync.aligned.m16n8k16.row.col.f32.bf16.bf16.f32 {c84,c85,c86,c87}, {a0,a1,a2,a3}, {x10,x11}, {c84,c85,c86,c87};\n"
            "ld.shared.v4.u32 {x8,x9,x10,x11}, [xa+512];\n"
            "tanh.approx.f32 th4, h8;\n"
            "tanh.approx.f32 th5, h10;\n"
            "fma.rn.f32 th4, h8, th4, h8;\n"
            "fma.rn.f32 th5, h10, th5, h10;\n"
            "cvt.rn.bf16x2.f32 r2, th5, th4;\n"
            "mma.sync.aligned.m16n8k16.row.col.f32.bf16.bf16.f32 {c88,c89,c90,c91}, {a0,a1,a2,a3}, {x12,x13}, {c88,c89,c90,c91};\n"
            "mma.sync.aligned.m16n8k16.row.col.f32.bf16.bf16.f32 {c92,c93,c94,c95}, {a0,a1,a2,a3}, {x14,x15}, {c92,c93,c94,c95};\n"
            "ld.shared.v4.u32 {x12,x13,x14,x15}, [xa+640];\n"
            "tanh.approx.f32 th6, h12;\n"
            "tanh.approx.f32 th7, h14;\n"
            "fma.rn.f32 th6, h12, th6, h12;\n"
            "fma.rn.f32 th7, h14, th7, h14;\n"
            "cvt.rn.bf16x2.f32 r3, th7, th6;\n"
            "ld.shared.v4.u32 {a0,a1,a2,a3}, [ab+0];\n"
            "@pe mbarrier.arrive.shared::cta.b64 _, [cnt+280];\n"
            "mov.b32 {lo,hi}, r0; mov.b32 rl, {lo,lo}; mov.b32 rh, {hi,hi};\n"
            "mul.bf16x2 x0, x0, rl; mul.bf16x2 x1, x1, rl; mul.bf16x2 x2, x2, rh; mul.bf16x2 x3, x3, rh;\n"
            "mov.b32 {lo,hi}, r1; mov.b32 rl, {lo,lo}; mov.b32 rh, {hi,hi};\n"
            "mul.bf16x2 x4, x4, rl; mul.bf16x2 x5, x5, rl; mul.bf16x2 x6, x6, rh; mul.bf16x2 x7, x7, rh;\n"
            "mov.b32 {lo,hi}, r2; mov.b32 rl, {lo,lo}; mov.b32 rh, {hi,hi};\n"
            "mul.bf16x2 x8, x8, rl; mul.bf16x2 x9, x9, rl; mul.bf16x2 x10, x10, rh; mul.bf16x2 x11, x11, rh;\n"
            "mov.b32 {lo,hi}, r3; mov.b32 rl, {lo,lo}; mov.b32 rh, {hi,hi};\n"
            "mul.bf16x2 x12, x12, rl; mul.bf16x2 x13, x13, rl; mul.bf16x2 x14, x14, rh; mul.bf16x2 x15, x15, rh;\n"
            "@d1 bra.uni L1; @d2 bra.uni B1_4; @d0 bra.uni B1_1; bra.uni B1_0;\n"
            "B0_3:\n"
            "xor.b32 tmp, mt, %3; and.b32 tmp, tmp, 1536; setp.eq.u32 pm, tmp, 0; selp.b32 ab, aa, %3, pm;\n"
            "and.b32 tmp, mt, 2048; setp.ne.u32 d0, tmp, 0; and.b32 tmp, mt, 4096; setp.ne.u32 d1, tmp, 0; and.b32 tmp, mt, 8192; setp.ne.u32 d2, tmp, 0;\n"
            "mad.lo.u32 cnt, a0, %5, ea; mad.lo.s32 ea, st, 2560, ea;\n"
            "ld.shared.u32 mt, [aa+512];\n"
            "mma.sync.aligned.m16n8k16.row.col.f32.bf16.bf16.f32 {c96,c97,c98,c99}, {a0,a1,a2,a3}, {x0,x1}, {c96,c97,c98,c99};\n"
            "mma.sync.aligned.m16n8k16.row.col.f32.bf16.bf16.f32 {c100,c101,c102,c103}, {a0,a1,a2,a3}, {x2,x3}, {c100,c101,c102,c103};\n"
            "ld.shared.v4.u32 {x0,x1,x2,x3}, [xa+0];\n"
            "tanh.approx.f32 th0, h0;\n"
            "tanh.approx.f32 th1, h2;\n"
            "fma.rn.f32 th0, h0, th0, h0;\n"
            "fma.rn.f32 th1, h2, th1, h2;\n"
            "cvt.rn.bf16x2.f32 r0, th1, th0;\n"
            "mma.sync.aligned.m16n8k16.row.col.f32.bf16.bf16.f32 {c104,c105,c106,c107}, {a0,a1,a2,a3}, {x4,x5}, {c104,c105,c106,c107};\n"
            "mma.sync.aligned.m16n8k16.row.col.f32.bf16.bf16.f32 {c108,c109,c110,c111}, {a0,a1,a2,a3}, {x6,x7}, {c108,c109,c110,c111};\n"
            "ld.shared.v4.u32 {x4,x5,x6,x7}, [xa+128];\n"
            "tanh.approx.f32 th2, h4;\n"
            "tanh.approx.f32 th3, h6;\n"
            "fma.rn.f32 th2, h4, th2, h4;\n"
            "fma.rn.f32 th3, h6, th3, h6;\n"
            "cvt.rn.bf16x2.f32 r1, th3, th2;\n"
            "mma.sync.aligned.m16n8k16.row.col.f32.bf16.bf16.f32 {c112,c113,c114,c115}, {a0,a1,a2,a3}, {x8,x9}, {c112,c113,c114,c115};\n"
            "mma.sync.aligned.m16n8k16.row.col.f32.bf16.bf16.f32 {c116,c117,c118,c119}, {a0,a1,a2,a3}, {x10,x11}, {c116,c117,c118,c119};\n"
            "ld.shared.v4.u32 {x8,x9,x10,x11}, [xa+512];\n"
            "tanh.approx.f32 th4, h8;\n"
            "tanh.approx.f32 th5, h10;\n"
            "fma.rn.f32 th4, h8, th4, h8;\n"
            "fma.rn.f32 th5, h10, th5, h10;\n"
            "cvt.rn.bf16x2.f32 r2, th5, th4;\n"
            "mma.sync.aligned.m16n8k16.row.col.f32.bf16.bf16.f32 {c120,c121,c122,c123}, {a0,a1,a2,a3}, {x12,x13}, {c120,c121,c122,c123};\n"
            "mma.sync.aligned.m16n8k16.row.col.f32.bf16.bf16.f32 {c124,c125,c126,c127}, {a0,a1,a2,a3}, {x14,x15}, {c124,c125,c126,c127};\n"
            "ld.shared.v4.u32 {x12,x13,x14,x15}, [xa+640];\n"
            "tanh.approx.f32 th6, h12;\n"
            "tanh.approx.f32 th7, h14;\n"
            "fma.rn.f32 th6, h12, th6, h12;\n"
            "fma.rn.f32 th7, h14, th7, h14;\n"
            "cvt.rn.bf16x2.f32 r3, th7, th6;\n"
            "ld.shared.v4.u32 {a0,a1,a2,a3}, [ab+0];\n"
            "@pe mbarrier.arrive.shared::cta.b64 _, [cnt+280];\n"
            "mov.b32 {lo,hi}, r0; mov.b32 rl, {lo,lo}; mov.b32 rh, {hi,hi};\n"
            "mul.bf16x2 x0, x0, rl; mul.bf16x2 x1, x1, rl; mul.bf16x2 x2, x2, rh; mul.bf16x2 x3, x3, rh;\n"
            "mov.b32 {lo,hi}, r1; mov.b32 rl, {lo,lo}; mov.b32 rh, {hi,hi};\n"
            "mul.bf16x2 x4, x4, rl; mul.bf16x2 x5, x5, rl; mul.bf16x2 x6, x6, rh; mul.bf16x2 x7, x7, rh;\n"
            "mov.b32 {lo,hi}, r2; mov.b32 rl, {lo,lo}; mov.b32 rh, {hi,hi};\n"
            "mul.bf16x2 x8, x8, rl; mul.bf16x2 x9, x9, rl; mul.bf16x2 x10, x10, rh; mul.bf16x2 x11, x11, rh;\n"
            "mov.b32 {lo,hi}, r3; mov.b32 rl, {lo,lo}; mov.b32 rh, {hi,hi};\n"
            "mul.bf16x2 x12, x12, rl; mul.bf16x2 x13, x13, rl; mul.bf16x2 x14, x14, rh; mul.bf16x2 x15, x15, rh;\n"
            "@d1 bra.uni L1; @d2 bra.uni B1_4; @d0 bra.uni B1_1; bra.uni B1_0;\n"
            "B0_4:\n"
            "xor.b32 tmp, mt, %3; and.b32 tmp, tmp, 1536; setp.eq.u32 pm, tmp, 0; selp.b32 ab, aa, %3, pm;\n"
            "and.b32 tmp, mt, 2048; setp.ne.u32 d0, tmp, 0; and.b32 tmp, mt, 4096; setp.ne.u32 d1, tmp, 0; and.b32 tmp, mt, 8192; setp.ne.u32 d2, tmp, 0;\n"
            "mad.lo.u32 cnt, a0, %5, ea; mad.lo.s32 ea, st, 2560, ea;\n"
            "ld.shared.u32 mt, [aa+512];\n"
            "mma.sync.aligned.m16n8k16.row.col.f32.bf16.bf16.f32 {c128,c129,c130,c131}, {a0,a1,a2,a3}, {x0,x1}, {c128,c129,c130,c131};\n"
            "mma.sync.aligned.m16n8k16.row.col.f32.bf16.bf16.f32 {c132,c133,c134,c135}, {a0,a1,a2,a3}, {x2,x3}, {c132,c133,c134,c135};\n"
            "ld.shared.v4.u32 {x0,x1,x2,x3}, [xa+0];\n"
            "tanh.approx.f32 th0, h0;\n"
            "tanh.approx.f32 th1, h2;\n"
            "fma.rn.f32 th0, h0, th0, h0;\n"
            "fma.rn.f32 th1, h2, th1, h2;\n"
            "cvt.rn.bf16x2.f32 r0, th1, th0;\n"
            "mma.sync.aligned.m16n8k16.row.col.f32.bf16.bf16.f32 {c136,c137,c138,c139}, {a0,a1,a2,a3}, {x4,x5}, {c136,c137,c138,c139};\n"
            "mma.sync.aligned.m16n8k16.row.col.f32.bf16.bf16.f32 {c140,c141,c142,c143}, {a0,a1,a2,a3}, {x6,x7}, {c140,c141,c142,c143};\n"
            "ld.shared.v4.u32 {x4,x5,x6,x7}, [xa+128];\n"
            "tanh.approx.f32 th2, h4;\n"
            "tanh.approx.f32 th3, h6;\n"
            "fma.rn.f32 th2, h4, th2, h4;\n"
            "fma.rn.f32 th3, h6, th3, h6;\n"
            "cvt.rn.bf16x2.f32 r1, th3, th2;\n"
            "mma.sync.aligned.m16n8k16.row.col.f32.bf16.bf16.f32 {c144,c145,c146,c147}, {a0,a1,a2,a3}, {x8,x9}, {c144,c145,c146,c147};\n"
            "mma.sync.aligned.m16n8k16.row.col.f32.bf16.bf16.f32 {c148,c149,c150,c151}, {a0,a1,a2,a3}, {x10,x11}, {c148,c149,c150,c151};\n"
            "ld.shared.v4.u32 {x8,x9,x10,x11}, [xa+512];\n"
            "tanh.approx.f32 th4, h8;\n"
            "tanh.approx.f32 th5, h10;\n"
            "fma.rn.f32 th4, h8, th4, h8;\n"
            "fma.rn.f32 th5, h10, th5, h10;\n"
            "cvt.rn.bf16x2.f32 r2, th5, th4;\n"
            "mma.sync.aligned.m16n8k16.row.col.f32.bf16.bf16.f32 {c152,c153,c154,c155}, {a0,a1,a2,a3}, {x12,x13}, {c152,c153,c154,c155};\n"
            "mma.sync.aligned.m16n8k16.row.col.f32.bf16.bf16.f32 {c156,c157,c158,c159}, {a0,a1,a2,a3}, {x14,x15}, {c156,c157,c158,c159};\n"
            "ld.shared.v4.u32 {x12,x13,x14,x15}, [xa+640];\n"
            "tanh.approx.f32 th6, h12;\n"
            "tanh.approx.f32 th7, h14;\n"
            "fma.rn.f32 th6, h12, th6, h12;\n"
            "fma.rn.f32 th7, h14, th7, h14;\n"
            "cvt.rn.bf16x2.f32 r3, th7, th6;\n"
            "ld.shared.v4.u32 {a0,a1,a2,a3}, [ab+0];\n"
            "@pe mbarrier.arrive.shared::cta.b64 _, [cnt+280];\n"
            "mov.b32 {lo,hi}, r0; mov.b32 rl, {lo,lo}; mov.b32 rh, {hi,hi};\n"
            "mul.bf16x2 x0, x0, rl; mul.bf16x2 x1, x1, rl; mul.bf16x2 x2, x2, rh; mul.bf16x2 x3, x3, rh;\n"
            "mov.b32 {lo,hi}, r1; mov.b32 rl, {lo,lo}; mov.b32 rh, {hi,hi};\n"
            "mul.bf16x2 x4, x4, rl; mul.bf16x2 x5, x5, rl; mul.bf16x2 x6, x6, rh; mul.bf16x2 x7, x7, rh;\n"
            "mov.b32 {lo,hi}, r2; mov.b32 rl, {lo,lo}; mov.b32 rh, {hi,hi};\n"
            "mul.bf16x2 x8, x8, rl; mul.bf16x2 x9, x9, rl; mul.bf16x2 x10, x10, rh; mul.bf16x2 x11, x11, rh;\n"
            "mov.b32 {lo,hi}, r3; mov.b32 rl, {lo,lo}; mov.b32 rh, {hi,hi};\n"
            "mul.bf16x2 x12, x12, rl; mul.bf16x2 x13, x13, rl; mul.bf16x2 x14, x14, rh; mul.bf16x2 x15, x15, rh;\n"
            "@d1 bra.uni L1; @d2 bra.uni B1_4; @d0 bra.uni B1_1; bra.uni B1_0;\n"
            "B1_0:\n"
            "xor.b32 tmp, mt, ea; and.b32 tmp, tmp, 192; setp.eq.u32 pm, tmp, 0; selp.b32 ab, aa, %3, pm;\n"
            "and.b32 tmp, mt, 8; setp.ne.u32 d0, tmp, 0; and.b32 tmp, mt, 16; setp.ne.u32 d1, tmp, 0; and.b32 tmp, mt, 32; setp.ne.u32 d2, tmp, 0;\n"
            "ld.shared.v2.u32 {e0,e1}, [ea];\n"
            "shr.s32 st, mt, 24; mad.lo.s32 aa, st, 2560, aa;\n"
            "mma.sync.aligned.m16n8k16.row.col.f32.bf16.bf16.f32 {c0,c1,c2,c3}, {a0,a1,a2,a3}, {x0,x1}, {c0,c1,c2,c3};\n"
            "mma.sync.aligned.m16n8k16.row.col.f32.bf16.bf16.f32 {c4,c5,c6,c7}, {a0,a1,a2,a3}, {x2,x3}, {c4,c5,c6,c7};\n"
            "ld.shared.v4.u32 {x0,x1,x2,x3}, [xa+1024];\n"
            "tanh.approx.f32 th0, h1;\n"
            "tanh.approx.f32 th1, h3;\n"
            "fma.rn.f32 th0, h1, th0, h1;\n"
            "fma.rn.f32 th1, h3, th1, h3;\n"
            "cvt.rn.bf16x2.f32 r0, th1, th0;\n"
            "mma.sync.aligned.m16n8k16.row.col.f32.bf16.bf16.f32 {h0,h1,h2,h3}, {%7,%8,%9,%10}, {e0,e1}, {fz,fz,fz,fz};\n"
            "mma.sync.aligned.m16n8k16.row.col.f32.bf16.bf16.f32 {c8,c9,c10,c11}, {a0,a1,a2,a3}, {x4,x5}, {c8,c9,c10,c11};\n"
            "mma.sync.aligned.m16n8k16.row.col.f32.bf16.bf16.f32 {c12,c13,c14,c15}, {a0,a1,a2,a3}, {x6,x7}, {c12,c13,c14,c15};\n"
            "ld.shared.v4.u32 {x4,x5,x6,x7}, [xa+1152];\n"
            "tanh.approx.f32 th2, h5;\n"
            "tanh.approx.f32 th3, h7;\n"
            "fma.rn.f32 th2, h5, th2, h5;\n"
            "fma.rn.f32 th3, h7, th3, h7;\n"
            "cvt.rn.bf16x2.f32 r1, th3, th2;\n"
            "mma.sync.aligned.m16n8k16.row.col.f32.bf16.bf16.f32 {h4,h5,h6,h7}, {%11,%12,%13,%14}, {e0,e1}, {fz,fz,fz,fz};\n"
            "mma.sync.aligned.m16n8k16.row.col.f32.bf16.bf16.f32 {c16,c17,c18,c19}, {a0,a1,a2,a3}, {x8,x9}, {c16,c17,c18,c19};\n"
            "mma.sync.aligned.m16n8k16.row.col.f32.bf16.bf16.f32 {c20,c21,c22,c23}, {a0,a1,a2,a3}, {x10,x11}, {c20,c21,c22,c23};\n"
            "ld.shared.v4.u32 {x8,x9,x10,x11}, [xa+1536];\n"
            "tanh.approx.f32 th4, h9;\n"
            "tanh.approx.f32 th5, h11;\n"
            "fma.rn.f32 th4, h9, th4, h9;\n"
            "fma.rn.f32 th5, h11, th5, h11;\n"
            "cvt.rn.bf16x2.f32 r2, th5, th4;\n"
            "mma.sync.aligned.m16n8k16.row.col.f32.bf16.bf16.f32 {h8,h9,h10,h11}, {%15,%16,%17,%18}, {e0,e1}, {fz,fz,fz,fz};\n"
            "mma.sync.aligned.m16n8k16.row.col.f32.bf16.bf16.f32 {c24,c25,c26,c27}, {a0,a1,a2,a3}, {x12,x13}, {c24,c25,c26,c27};\n"
            "mma.sync.aligned.m16n8k16.row.col.f32.bf16.bf16.f32 {c28,c29,c30,c31}, {a0,a1,a2,a3}, {x14,x15}, {c28,c29,c30,c31};\n"
            "ld.shared.v4.u32 {x12,x13,x14,x15}, [xa+1664];\n"
            "tanh.approx.f32 th6, h13;\n"
            "tanh.approx.f32 th7, h15;\n"
            "fma.rn.f32 th6, h13, th6, h13;\n"
            "fma.rn.f32 th7, h15, th7, h15;\n"
            "cvt.rn.bf16x2.f32 r3, th7, th6;\n"
            "mma.sync.aligned.m16n8k16.row.col.f32.bf16.bf16.f32 {h12,h13,h14,h15}, {%19,%20,%21,%22}, {e0,e1}, {fz,fz,fz,fz};\n"
            "ld.shared.v4.u32 {a0,a1,a2,a3}, [ab+128];\n"
            "and.b32 tmp, aa, 0xffffff80; mbarrier.test_wait.parity.shared::cta.b64 pw, [tmp+520], mt;\n"
            "mad.lo.s32 xa, st, 2048, xa;\n"
            "mov.b32 {lo,hi}, r0; mov.b32 rl, {lo,lo}; mov.b32 rh, {hi,hi};\n"
            "mul.bf16x2 x0, x0, rl; mul.bf16x2 x1, x1, rl; mul.bf16x2 x2, x2, rh; mul.bf16x2 x3, x3, rh;\n"
            "mov.b32 {lo,hi}, r1; mov.b32 rl, {lo,lo}; mov.b32 rh, {hi,hi};\n"
            "mul.bf16x2 x4, x4, rl; mul.bf16x2 x5, x5, rl; mul.bf16x2 x6, x6, rh; mul.bf16x2 x7, x7, rh;\n"
            "mov.b32 {lo,hi}, r2; mov.b32 rl, {lo,lo}; mov.b32 rh, {hi,hi};\n"
            "mul.bf16x2 x8, x8, rl; mul.bf16x2 x9, x9, rl; mul.bf16x2 x10, x10, rh; mul.bf16x2 x11, x11, rh;\n"
            "mov.b32 {lo,hi}, r3; mov.b32 rl, {lo,lo}; mov.b32 rh, {hi,hi};\n"
            "mul.bf16x2 x12, x12, rl; mul.bf16x2 x13, x13, rl; mul.bf16x2 x14, x14, rh; mul.bf16x2 x15, x15, rh;\n"
            "@!pw bra.uni W1;\n"
            "@d2 bra.uni B0_4; @d1 bra.uni L0; @d0 bra.uni B0_1; bra.uni B0_0;\n"
            "B1_1:\n"
            "xor.b32 tmp, mt, ea; and.b32 tmp, tmp, 192; setp.eq.u32 pm, tmp, 0; selp.b32 ab, aa, %3, pm;\n"
            "and.b32 tmp, mt, 8; setp.ne.u32 d0, tmp, 0; and.b32 tmp, mt, 16; setp.ne.u32 d1, tmp, 0; and.b32 tmp, mt, 32; setp.ne.u32 d2, tmp, 0;\n"
            "ld.shared.v2.u32 {e0,e1}, [ea];\n"
            "shr.s32 st, mt, 24; mad.lo.s32 aa, st, 2560, aa;\n"
            "mma.sync.aligned.m16n8k16.row.col.f32.bf16.bf16.f32 {c32,c33,c34,c35}, {a0,a1,a2,a3}, {x0,x1}, {c32,c33,c34,c35};\n"
            "mma.sync.aligned.m16n8k16.row.col.f32.bf16.bf16.f32 {c36,c37,c38,c39}, {a0,a1,a2,a3}, {x2,x3}, {c36,c37,c38,c39};\n"
            "ld.shared.v4.u32 {x0,x1,x2,x3}, [xa+1024];\n"
            "tanh.approx.f32 th0, h1;\n"
            "tanh.approx.f32 th1, h3;\n"
            "fma.rn.f32 th0, h1, th0, h1;\n"
            "fma.rn.f32 th1, h3, th1, h3;\n"
            "cvt.rn.bf16x2.f32 r0, th1, th0;\n"
            "mma.sync.aligned.m16n8k16.row.col.f32.bf16.bf16.f32 {h0,h1,h2,h3}, {%7,%8,%9,%10}, {e0,e1}, {fz,fz,fz,fz};\n"
            "mma.sync.aligned.m16n8k16.row.col.f32.bf16.bf16.f32 {c40,c41,c42,c43}, {a0,a1,a2,a3}, {x4,x5}, {c40,c41,c42,c43};\n"
            "mma.sync.aligned.m16n8k16.row.col.f32.bf16.bf16.f32 {c44,c45,c46,c47}, {a0,a1,a2,a3}, {x6,x7}, {c44,c45,c46,c47};\n"
            "ld.shared.v4.u32 {x4,x5,x6,x7}, [xa+1152];\n"
            "tanh.approx.f32 th2, h5;\n"
            "tanh.approx.f32 th3, h7;\n"
            "fma.rn.f32 th2, h5, th2, h5;\n"
            "fma.rn.f32 th3, h7, th3, h7;\n"
            "cvt.rn.bf16x2.f32 r1, th3, th2;\n"
            "mma.sync.aligned.m16n8k16.row.col.f32.bf16.bf16.f32 {h4,h5,h6,h7}, {%11,%12,%13,%14}, {e0,e1}, {fz,fz,fz,fz};\n"
            "mma.sync.aligned.m16n8k16.row.col.f32.bf16.bf16.f32 {c48,c49,c50,c51}, {a0,a1,a2,a3}, {x8,x9}, {c48,c49,c50,c51};\n"
            "mma.sync.aligned.m16n8k16.row.col.f32.bf16.bf16.f32 {c52,c53,c54,c55}, {a0,a1,a2,a3}, {x10,x11}, {c52,c53,c54,c55};\n"
            "ld.shared.v4.u32 {x8,x9,x10,x11}, [xa+1536];\n"
            "tanh.approx.f32 th4, h9;\n"
            "tanh.approx.f32 th5, h11;\n"
            "fma.rn.f32 th4, h9, th4, h9;\n"
            "fma.rn.f32 th5, h11, th5, h11;\n"
            "cvt.rn.bf16x2.f32 r2, th5, th4;\n"
            "mma.sync.aligned.m16n8k16.row.col.f32.bf16.bf16.f32 {h8,h9,h10,h11}, {%15,%16,%17,%18}, {e0,e1}, {fz,fz,fz,fz};\n"
            "mma.sync.aligned.m16n8k16.row.col.f32.bf16.bf16.f32 {c56,c57,c58,c59}, {a0,a1,a2,a3}, {x12,x13}, {c56,c57,c58,c59};\n"
            "mma.sync.aligned.m16n8k16.row.col.f32.bf16.bf16.f32 {c60,c61,c62,c63}, {a0,a1,a2,a3}, {x14,x15}, {c60,c61,c62,c63};\n"
            "ld.shared.v4.u32 {x12,x13,x14,x15}, [xa+1664];\n"
            "tanh.approx.f32 th6, h13;\n"
            "tanh.approx.f32 th7, h15;\n"
            "fma.rn.f32 th6, h13, th6, h13;\n"
            "fma.rn.f32 th7, h15, th7, h15;\n"
            "cvt.rn.bf16x2.f32 r3, th7, th6;\n"
            "mma.sync.aligned.m16n8k16.row.col.f32.bf16.bf16.f32 {h12,h13,h14,h15}, {%19,%20,%21,%22}, {e0,e1}, {fz,fz,fz,fz};\n"
            "ld.shared.v4.u32 {a0,a1,a2,a3}, [ab+128];\n"
            "and.b32 tmp, aa, 0xffffff80; mbarrier.test_wait.parity.shared::cta.b64 pw, [tmp+520], mt;\n"
            "mad.lo.s32 xa, st, 2048, xa;\n"
            "mov.b32 {lo,hi}, r0; mov.b32 rl, {lo,lo}; mov.b32 rh, {hi,hi};\n"
            "mul.bf16x2 x0, x0, rl; mul.bf16x2 x1, x1, rl; mul.bf16x2 x2, x2, rh; mul.bf16x2 x3, x3, rh;\n"
            "mov.b32 {lo,hi}, r1; mov.b32 rl, {lo,lo}; mov.b32 rh, {hi,hi};\n"
            "mul.bf16x2 x4, x4, rl; mul.bf16x2 x5, x5, rl; mul.bf16x2 x6, x6, rh; mul.bf16x2 x7, x7, rh;\n"
            "mov.b32 {lo,hi}, r2; mov.b32 rl, {lo,lo}; mov.b32 rh, {hi,hi};\n"
            "mul.bf16x2 x8, x8, rl; mul.bf16x2 x9, x9, rl; mul.bf16x2 x10, x10, rh; mul.bf16x2 x11, x11, rh;\n"
            "mov.b32 {lo,hi}, r3; mov.b32 rl, {lo,lo}; mov.b32 rh, {hi,hi};\n"
            "mul.bf16x2 x12, x12, rl; mul.bf16x2 x13, x13, rl; mul.bf16x2 x14, x14, rh; mul.bf16x2 x15, x15, rh;\n"
            "@!pw bra.uni W1;\n"
            "@d2 bra.uni B0_4; @d1 bra.uni L0; @d0 bra.uni B0_1; bra.uni B0_0;\n"
            "L1: @d2 bra.uni END; @d0 bra.uni B1_3;\n"
            "B1_2:\n"
            "xor.b32 tmp, mt, ea; and.b32 tmp, tmp, 192; setp.eq.u32 pm, tmp, 0; selp.b32 ab, aa, %3, pm;\n"
            "and.b32 tmp, mt, 8; setp.ne.u32 d0, tmp, 0; and.b32 tmp, mt, 16; setp.ne.u32 d1, tmp, 0; and.b32 tmp, mt, 32; setp.ne.u32 d2, tmp, 0;\n"
            "ld.shared.v2.u32 {e0,e1}, [ea];\n"
            "shr.s32 st, mt, 24; mad.lo.s32 aa, st, 2560, aa;\n"
            "mma.sync.aligned.m16n8k16.row.col.f32.bf16.bf16.f32 {c64,c65,c66,c67}, {a0,a1,a2,a3}, {x0,x1}, {c64,c65,c66,c67};\n"
            "mma.sync.aligned.m16n8k16.row.col.f32.bf16.bf16.f32 {c68,c69,c70,c71}, {a0,a1,a2,a3}, {x2,x3}, {c68,c69,c70,c71};\n"
            "ld.shared.v4.u32 {x0,x1,x2,x3}, [xa+1024];\n"
            "tanh.approx.f32 th0, h1;\n"
            "tanh.approx.f32 th1, h3;\n"
            "fma.rn.f32 th0, h1, th0, h1;\n"
            "fma.rn.f32 th1, h3, th1, h3;\n"
            "cvt.rn.bf16x2.f32 r0, th1, th0;\n"
            "mma.sync.aligned.m16n8k16.row.col.f32.bf16.bf16.f32 {h0,h1,h2,h3}, {%7,%8,%9,%10}, {e0,e1}, {fz,fz,fz,fz};\n"
            "mma.sync.aligned.m16n8k16.row.col.f32.bf16.bf16.f32 {c72,c73,c74,c75}, {a0,a1,a2,a3}, {x4,x5}, {c72,c73,c74,c75};\n"
            "mma.sync.aligned.m16n8k16.row.col.f32.bf16.bf16.f32 {c76,c77,c78,c79}, {a0,a1,a2,a3}, {x6,x7}, {c76,c77,c78,c79};\n"
            "ld.shared.v4.u32 {x4,x5,x6,x7}, [xa+1152];\n"
            "tanh.approx.f32 th2, h5;\n"
            "tanh.approx.f32 th3, h7;\n"
            "fma.rn.f32 th2, h5, th2, h5;\n"
            "fma.rn.f32 th3, h7, th3, h7;\n"
            "cvt.rn.bf16x2.f32 r1, th3, th2;\n"
            "mma.sync.aligned.m16n8k16.row.col.f32.bf16.bf16.f32 {h4,h5,h6,h7}, {%11,%12,%13,%14}, {e0,e1}, {fz,fz,fz,fz};\n"
            "mma.sync.aligned.m16n8k16.row.col.f32.bf16.bf16.f32 {c80,c81,c82,c83}, {a0,a1,a2,a3}, {x8,x9}, {c80,c81,c82,c83};\n"
            "mma.sync.aligned.m16n8k16.row.col.f32.bf16.bf16.f32 {c84,c85,c86,c87}, {a0,a1,a2,a3}, {x10,x11}, {c84,c85,c86,c87};\n"
            "ld.shared.v4.u32 {x8,x9,x10,x11}, [xa+1536];\n"
            "tanh.approx.f32 th4, h9;\n"
            "tanh.approx.f32 th5, h11;\n"
            "fma.rn.f32 th4, h9, th4, h9;\n"
            "fma.rn.f32 th5, h11, th5, h11;\n"
            "cvt.rn.bf16x2.f32 r2, th5, th4;\n"
            "mma.sync.aligned.m16n8k16.row.col.f32.bf16.bf16.f32 {h8,h9,h10,h11}, {%15,%16,%17,%18}, {e0,e1}, {fz,fz,fz,fz};\n"
            "mma.sync.aligned.m16n8k16.row.col.f32.bf16.bf16.f32 {c88,c89,c90,c91}, {a0,a1,a2,a3}, {x12,x13}, {c88,c89,c90,c91};\n"
            "mma.sync.aligned.m16n8k16.row.col.f32.bf16.bf16.f32 {c92,c93,c94,c95}, {a0,a1,a2,a3}, {x14,x15}, {c92,c93,c94,c95};\n"
            "ld.shared.v4.u32 {x12,x13,x14,x15}, [xa+1664];\n"
            "tanh.approx.f32 th6, h13;\n"
            "tanh.approx.f32 th7, h15;\n"
            "fma.rn.f32 th6, h13, th6, h13;\n"
            "fma.rn.f32 th7, h15, th7, h15;\n"
            "cvt.rn.bf16x2.f32 r3, th7, th6;\n"
            "mma.sync.aligned.m16n8k16.row.col.f32.bf16.bf16.f32 {h12,h13,h14,h15}, {%19,%20,%21,%22}, {e0,e1}, {fz,fz,fz,fz};\n"
            "ld.shared.v4.u32 {a0,a1,a2,a3}, [ab+128];\n"
            "and.b32 tmp, aa, 0xffffff80; mbarrier.test_wait.parity.shared::cta.b64 pw, [tmp+520], mt;\n"
            "mad.lo.s32 xa, st, 2048, xa;\n"
            "mov.b32 {lo,hi}, r0; mov.b32 rl, {lo,lo}; mov.b32 rh, {hi,hi};\n"
            "mul.bf16x2 x0, x0, rl; mul.bf16x2 x1, x1, rl; mul.bf16x2 x2, x2, rh; mul.bf16x2 x3, x3, rh;\n"
            "mov.b32 {lo,hi}, r1; mov.b32 rl, {lo,lo}; mov.b32 rh, {hi,hi};\n"
            "mul.bf16x2 x4, x4, rl; mul.bf16x2 x5, x5, rl; mul.bf16x2 x6, x6, rh; mul.bf16x2 x7, x7, rh;\n"
            "mov.b32 {lo,hi}, r2; mov.b32 rl, {lo,lo}; mov.b32 rh, {hi,hi};\n"
            "mul.bf16x2 x8, x8, rl; mul.bf16x2 x9, x9, rl; mul.bf16x2 x10, x10, rh; mul.bf16x2 x11, x11, rh;\n"
            "mov.b32 {lo,hi}, r3; mov.b32 rl, {lo,lo}; mov.b32 rh, {hi,hi};\n"
            "mul.bf16x2 x12, x12, rl; mul.bf16x2 x13, x13, rl; mul.bf16x2 x14, x14, rh; mul.bf16x2 x15, x15, rh;\n"
            "@!pw bra.uni W1;\n"
            "@d2 bra.uni B0_4; @d1 bra.uni L0; @d0 bra.uni B0_1; bra.uni B0_0;\n"
            "B1_3:\n"
            "xor.b32 tmp, mt, ea; and.b32 tmp, tmp, 192; setp.eq.u32 pm, tmp, 0; selp.b32 ab, aa, %3, pm;\n"
            "and.b32 tmp, mt, 8; setp.ne.u32 d0, tmp, 0; and.b32 tmp, mt, 16; setp.ne.u32 d1, tmp, 0; and.b32 tmp, mt, 32; setp.ne.u32 d2, tmp, 0;\n"
            "ld.shared.v2.u32 {e0,e1}, [ea];\n"
            "shr.s32 st, mt, 24; mad.lo.s32 aa, st, 2560, aa;\n"
            "mma.sync.aligned.m16n8k16.row.col.f32.bf16.bf16.f32 {c96,c97,c98,c99}, {a0,a1,a2,a3}, {x0,x1}, {c96,c97,c98,c99};\n"
            "mma.sync.aligned.m16n8k16.row.col.f32.bf16.bf16.f32 {c100,c101,c102,c103}, {a0,a1,a2,a3}, {x2,x3}, {c100,c101,c102,c103};\n"
            "ld.shared.v4.u32 {x0,x1,x2,x3}, [xa+1024];\n"
            "tanh.approx.f32 th0, h1;\n"
            "tanh.approx.f32 th1, h3;\n"
            "fma.rn.f32 th0, h1, th0, h1;\n"
            "fma.rn.f32 th1, h3, th1, h3;\n"
            "cvt.rn.bf16x2.f32 r0, th1, th0;\n"
            "mma.sync.aligned.m16n8k16.row.col.f32.bf16.bf16.f32 {h0,h1,h2,h3}, {%7,%8,%9,%10}, {e0,e1}, {fz,fz,fz,fz};\n"
            "mma.sync.aligned.m16n8k16.row.col.f32.bf16.bf16.f32 {c104,c105,c106,c107}, {a0,a1,a2,a3}, {x4,x5}, {c104,c105,c106,c107};\n"
            "mma.sync.aligned.m16n8k16.row.col.f32.bf16.bf16.f32 {c108,c109,c110,c111}, {a0,a1,a2,a3}, {x6,x7}, {c108,c109,c110,c111};\n"
            "ld.shared.v4.u32 {x4,x5,x6,x7}, [xa+1152];\n"
            "tanh.approx.f32 th2, h5;\n"
            "tanh.approx.f32 th3, h7;\n"
            "fma.rn.f32 th2, h5, th2, h5;\n"
            "fma.rn.f32 th3, h7, th3, h7;\n"
            "cvt.rn.bf16x2.f32 r1, th3, th2;\n"
            "mma.sync.aligned.m16n8k16.row.col.f32.bf16.bf16.f32 {h4,h5,h6,h7}, {%11,%12,%13,%14}, {e0,e1}, {fz,fz,fz,fz};\n"
            "mma.sync.aligned.m16n8k16.row.col.f32.bf16.bf16.f32 {c112,c113,c114,c115}, {a0,a1,a2,a3}, {x8,x9}, {c112,c113,c114,c115};\n"
            "mma.sync.aligned.m16n8k16.row.col.f32.bf16.bf16.f32 {c116,c117,c118,c119}, {a0,a1,a2,a3}, {x10,x11}, {c116,c117,c118,c119};\n"
            "ld.shared.v4.u32 {x8,x9,x10,x11}, [xa+1536];\n"
            "tanh.approx.f32 th4, h9;\n"
            "tanh.approx.f32 th5, h11;\n"
            "fma.rn.f32 th4, h9, th4, h9;\n"
            "fma.rn.f32 th5, h11, th5, h11;\n"
            "cvt.rn.bf16x2.f32 r2, th5, th4;\n"
            "mma.sync.aligned.m16n8k16.row.col.f32.bf16.bf16.f32 {h8,h9,h10,h11}, {%15,%16,%17,%18}, {e0,e1}, {fz,fz,fz,fz};\n"
            "mma.sync.aligned.m16n8k16.row.col.f32.bf16.bf16.f32 {c120,c121,c122,c123}, {a0,a1,a2,a3}, {x12,x13}, {c120,c121,c122,c123};\n"
            "mma.sync.aligned.m16n8k16.row.col.f32.bf16.bf16.f32 {c124,c125,c126,c127}, {a0,a1,a2,a3}, {x14,x15}, {c124,c125,c126,c127};\n"
            "ld.shared.v4.u32 {x12,x13,x14,x15}, [xa+1664];\n"
            "tanh.approx.f32 th6, h13;\n"
            "tanh.approx.f32 th7, h15;\n"
            "fma.rn.f32 th6, h13, th6, h13;\n"
            "fma.rn.f32 th7, h15, th7, h15;\n"
            "cvt.rn.bf16x2.f32 r3, th7, th6;\n"
            "mma.sync.aligned.m16n8k16.row.col.f32.bf16.bf16.f32 {h12,h13,h14,h15}, {%19,%20,%21,%22}, {e0,e1}, {fz,fz,fz,fz};\n"
            "ld.shared.v4.u32 {a0,a1,a2,a3}, [ab+128];\n"
            "and.b32 tmp, aa, 0xffffff80; mbarrier.test_wait.parity.shared::cta.b64 pw, [tmp+520], mt;\n"
            "mad.lo.s32 xa, st, 2048, xa;\n"
            "mov.b32 {lo,hi}, r0; mov.b32 rl, {lo,lo}; mov.b32 rh, {hi,hi};\n"
            "mul.bf16x2 x0, x0, rl; mul.bf16x2 x1, x1, rl; mul.bf16x2 x2, x2, rh; mul.bf16x2 x3, x3, rh;\n"
            "mov.b32 {lo,hi}, r1; mov.b32 rl, {lo,lo}; mov.b32 rh, {hi,hi};\n"
            "mul.bf16x2 x4, x4, rl; mul.bf16x2 x5, x5, rl; mul.bf16x2 x6, x6, rh; mul.bf16x2 x7, x7, rh;\n"
            "mov.b32 {lo,hi}, r2; mov.b32 rl, {lo,lo}; mov.b32 rh, {hi,hi};\n"
            "mul.bf16x2 x8, x8, rl; mul.bf16x2 x9, x9, rl; mul.bf16x2 x10, x10, rh; mul.bf16x2 x11, x11, rh;\n"
            "mov.b32 {lo,hi}, r3; mov.b32 rl, {lo,lo}; mov.b32 rh, {hi,hi};\n"
            "mul.bf16x2 x12, x12, rl; mul.bf16x2 x13, x13, rl; mul.bf16x2 x14, x14, rh; mul.bf16x2 x15, x15, rh;\n"
            "@!pw bra.uni W1;\n"
            "@d2 bra.uni B0_4; @d1 bra.uni L0; @d0 bra.uni B0_1; bra.uni B0_0;\n"
            "B1_4:\n"
            "xor.b32 tmp, mt, ea; and.b32 tmp, tmp, 192; setp.eq.u32 pm, tmp, 0; selp.b32 ab, aa, %3, pm;\n"
            "and.b32 tmp, mt, 8; setp.ne.u32 d0, tmp, 0; and.b32 tmp, mt, 16; setp.ne.u32 d1, tmp, 0; and.b32 tmp, mt, 32; setp.ne.u32 d2, tmp, 0;\n"
            "ld.shared.v2.u32 {e0,e1}, [ea];\n"
            "shr.s32 st, mt, 24; mad.lo.s32 aa, st, 2560, aa;\n"
            "mma.sync.aligned.m16n8k16.row.col.f32.bf16.bf16.f32 {c128,c129,c130,c131}, {a0,a1,a2,a3}, {x0,x1}, {c128,c129,c130,c131};\n"
            "mma.sync.aligned.m16n8k16.row.col.f32.bf16.bf16.f32 {c132,c133,c134,c135}, {a0,a1,a2,a3}, {x2,x3}, {c132,c133,c134,c135};\n"
            "ld.shared.v4.u32 {x0,x1,x2,x3}, [xa+1024];\n"
            "tanh.approx.f32 th0, h1;\n"
            "tanh.approx.f32 th1, h3;\n"
            "fma.rn.f32 th0, h1, th0, h1;\n"
            "fma.rn.f32 th1, h3, th1, h3;\n"
            "cvt.rn.bf16x2.f32 r0, th1, th0;\n"
            "mma.sync.aligned.m16n8k16.row.col.f32.bf16.bf16.f32 {h0,h1,h2,h3}, {%7,%8,%9,%10}, {e0,e1}, {fz,fz,fz,fz};\n"
            "mma.sync.aligned.m16n8k16.row.col.f32.bf16.bf16.f32 {c136,c137,c138,c139}, {a0,a1,a2,a3}, {x4,x5}, {c136,c137,c138,c139};\n"
            "mma.sync.aligned.m16n8k16.row.col.f32.bf16.bf16.f32 {c140,c141,c142,c143}, {a0,a1,a2,a3}, {x6,x7}, {c140,c141,c142,c143};\n"
            "ld.shared.v4.u32 {x4,x5,x6,x7}, [xa+1152];\n"
            "tanh.approx.f32 th2, h5;\n"
            "tanh.approx.f32 th3, h7;\n"
            "fma.rn.f32 th2, h5, th2, h5;\n"
            "fma.rn.f32 th3, h7, th3, h7;\n"
            "cvt.rn.bf16x2.f32 r1, th3, th2;\n"
            "mma.sync.aligned.m16n8k16.row.col.f32.bf16.bf16.f32 {h4,h5,h6,h7}, {%11,%12,%13,%14}, {e0,e1}, {fz,fz,fz,fz};\n"
            "mma.sync.aligned.m16n8k16.row.col.f32.bf16.bf16.f32 {c144,c145,c146,c147}, {a0,a1,a2,a3}, {x8,x9}, {c144,c145,c146,c147};\n"
            "mma.sync.aligned.m16n8k16.row.col.f32.bf16.bf16.f32 {c148,c149,c150,c151}, {a0,a1,a2,a3}, {x10,x11}, {c148,c149,c150,c151};\n"
            "ld.shared.v4.u32 {x8,x9,x10,x11}, [xa+1536];\n"
            "tanh.approx.f32 th4, h9;\n"
            "tanh.approx.f32 th5, h11;\n"
            "fma.rn.f32 th4, h9, th4, h9;\n"
            "fma.rn.f32 th5, h11, th5, h11;\n"
            "cvt.rn.bf16x2.f32 r2, th5, th4;\n"
            "mma.sync.aligned.m16n8k16.row.col.f32.bf16.bf16.f32 {h8,h9,h10,h11}, {%15,%16,%17,%18}, {e0,e1}, {fz,fz,fz,fz};\n"
            "mma.sync.aligned.m16n8k16.row.col.f32.bf16.bf16.f32 {c152,c153,c154,c155}, {a0,a1,a2,a3}, {x12,x13}, {c152,c153,c154,c155};\n"
            "mma.sync.aligned.m16n8k16.row.col.f32.bf16.bf16.f32 {c156,c157,c158,c159}, {a0,a1,a2,a3}, {x14,x15}, {c156,c157,c158,c159};\n"
            "ld.shared.v4.u32 {x12,x13,x14,x15}, [xa+1664];\n"
            "tanh.approx.f32 th6, h13;\n"
            "tanh.approx.f32 th7, h15;\n"
            "fma.rn.f32 th6, h13, th6, h13;\n"
            "fma.rn.f32 th7, h15, th7, h15;\n"
            "cvt.rn.bf16x2.f32 r3, th7, th6;\n"
            "mma.sync.aligned.m16n8k16.row.col.f32.bf16.bf16.f32 {h12,h13,h14,h15}, {%19,%20,%21,%22}, {e0,e1}, {fz,fz,fz,fz};\n"
            "ld.shared.v4.u32 {a0,a1,a2,a3}, [ab+128];\n"
            "and.b32 tmp, aa, 0xffffff80; mbarrier.test_wait.parity.shared::cta.b64 pw, [tmp+520], mt;\n"
            "mad.lo.s32 xa, st, 2048, xa;\n"
            "mov.b32 {lo,hi}, r0; mov.b32 rl, {lo,lo}; mov.b32 rh, {hi,hi};\n"
            "mul.bf16x2 x0, x0, rl; mul.bf16x2 x1, x1, rl; mul.bf16x2 x2, x2, rh; mul.bf16x2 x3, x3, rh;\n"
            "mov.b32 {lo,hi}, r1; mov.b32 rl, {lo,lo}; mov.b32 rh, {hi,hi};\n"
            "mul.bf16x2 x4, x4, rl; mul.bf16x2 x5, x5, rl; mul.bf16x2 x6, x6, rh; mul.bf16x2 x7, x7, rh;\n"
            "mov.b32 {lo,hi}, r2; mov.b32 rl, {lo,lo}; mov.b32 rh, {hi,hi};\n"
            "mul.bf16x2 x8, x8, rl; mul.bf16x2 x9, x9, rl; mul.bf16x2 x10, x10, rh; mul.bf16x2 x11, x11, rh;\n"
            "mov.b32 {lo,hi}, r3; mov.b32 rl, {lo,lo}; mov.b32 rh, {hi,hi};\n"
            "mul.bf16x2 x12, x12, rl; mul.bf16x2 x13, x13, rl; mul.bf16x2 x14, x14, rh; mul.bf16x2 x15, x15, rh;\n"
            "@!pw bra.uni W1;\n"
            "@d2 bra.uni B0_4; @d1 bra.uni L0; @d0 bra.uni B0_1; bra.uni B0_0;\n"
            "W1:\n"
            "mov.u32 cnt, 0; and.b32 tmp, aa, 0xffffff80;\n"
            "W1L: mbarrier.try_wait.parity.shared::cta.b64 pw, [tmp+520], mt; @pw bra.uni W1D;\n"
            "add.u32 cnt, cnt, 1; setp.lt.u32 pk, cnt, 1000000; @pk bra.uni W1L; trap;\n"
            "W1D:\n"
            "@d2 bra.uni B0_4; @d1 bra.uni L0; @d0 bra.uni B0_1; bra.uni B0_0;\n"
            "END:\n"
            "cvt.rn.bf16x2.f32 p0, c1, c0; cvt.rn.bf16x2.f32 p1, c5, c4; cvt.rn.bf16x2.f32 p2, c9, c8; cvt.rn.bf16x2.f32 p3, c13, c12; cvt.rn.bf16x2.f32 p4, c17, c16; cvt.rn.bf16x2.f32 p5, c21, c20; cvt.rn.bf16x2.f32 p6, c25, c24; cvt.rn.bf16x2.f32 p7, c29, c28;\n"
            "cvt.rn.bf16x2.f32 p8, c3, c2; cvt.rn.bf16x2.f32 p9, c7, c6; cvt.rn.bf16x2.f32 p10, c11, c10; cvt.rn.bf16x2.f32 p11, c15, c14; cvt.rn.bf16x2.f32 p12, c19, c18; cvt.rn.bf16x2.f32 p13, c23, c22; cvt.rn.bf16x2.f32 p14, c27, c26; cvt.rn.bf16x2.f32 p15, c31, c30;\n"
            "cvt.rn.bf16x2.f32 p16, c33, c32; cvt.rn.bf16x2.f32 p17, c37, c36; cvt.rn.bf16x2.f32 p18, c41, c40; cvt.rn.bf16x2.f32 p19, c45, c44; cvt.rn.bf16x2.f32 p20, c49, c48; cvt.rn.bf16x2.f32 p21, c53, c52; cvt.rn.bf16x2.f32 p22, c57, c56; cvt.rn.bf16x2.f32 p23, c61, c60;\n"
            "cvt.rn.bf16x2.f32 p24, c35, c34; cvt.rn.bf16x2.f32 p25, c39, c38; cvt.rn.bf16x2.f32 p26, c43, c42; cvt.rn.bf16x2.f32 p27, c47, c46; cvt.rn.bf16x2.f32 p28, c51, c50; cvt.rn.bf16x2.f32 p29, c55, c54; cvt.rn.bf16x2.f32 p30, c59, c58; cvt.rn.bf16x2.f32 p31, c63, c62;\n"
            "cvt.rn.bf16x2.f32 p32, c65, c64; cvt.rn.bf16x2.f32 p33, c69, c68; cvt.rn.bf16x2.f32 p34, c73, c72; cvt.rn.bf16x2.f32 p35, c77, c76; cvt.rn.bf16x2.f32 p36, c81, c80; cvt.rn.bf16x2.f32 p37, c85, c84; cvt.rn.bf16x2.f32 p38, c89, c88; cvt.rn.bf16x2.f32 p39, c93, c92;\n"
            "cvt.rn.bf16x2.f32 p40, c67, c66; cvt.rn.bf16x2.f32 p41, c71, c70; cvt.rn.bf16x2.f32 p42, c75, c74; cvt.rn.bf16x2.f32 p43, c79, c78; cvt.rn.bf16x2.f32 p44, c83, c82; cvt.rn.bf16x2.f32 p45, c87, c86; cvt.rn.bf16x2.f32 p46, c91, c90; cvt.rn.bf16x2.f32 p47, c95, c94;\n"
            "cvt.rn.bf16x2.f32 p48, c97, c96; cvt.rn.bf16x2.f32 p49, c101, c100; cvt.rn.bf16x2.f32 p50, c105, c104; cvt.rn.bf16x2.f32 p51, c109, c108; cvt.rn.bf16x2.f32 p52, c113, c112; cvt.rn.bf16x2.f32 p53, c117, c116; cvt.rn.bf16x2.f32 p54, c121, c120; cvt.rn.bf16x2.f32 p55, c125, c124;\n"
            "cvt.rn.bf16x2.f32 p56, c99, c98; cvt.rn.bf16x2.f32 p57, c103, c102; cvt.rn.bf16x2.f32 p58, c107, c106; cvt.rn.bf16x2.f32 p59, c111, c110; cvt.rn.bf16x2.f32 p60, c115, c114; cvt.rn.bf16x2.f32 p61, c119, c118; cvt.rn.bf16x2.f32 p62, c123, c122; cvt.rn.bf16x2.f32 p63, c127, c126;\n"
            "cvt.rn.bf16x2.f32 p64, c129, c128; cvt.rn.bf16x2.f32 p65, c133, c132; cvt.rn.bf16x2.f32 p66, c137, c136; cvt.rn.bf16x2.f32 p67, c141, c140; cvt.rn.bf16x2.f32 p68, c145, c144; cvt.rn.bf16x2.f32 p69, c149, c148; cvt.rn.bf16x2.f32 p70, c153, c152; cvt.rn.bf16x2.f32 p71, c157, c156;\n"
            "cvt.rn.bf16x2.f32 p72, c131, c130; cvt.rn.bf16x2.f32 p73, c135, c134; cvt.rn.bf16x2.f32 p74, c139, c138; cvt.rn.bf16x2.f32 p75, c143, c142; cvt.rn.bf16x2.f32 p76, c147, c146; cvt.rn.bf16x2.f32 p77, c151, c150; cvt.rn.bf16x2.f32 p78, c155, c154; cvt.rn.bf16x2.f32 p79, c159, c158;\n"
            "and.b32 aa, %3, 0xfffff980; sub.u32 aa, aa, %6; mov.u32 mt, %%tid.x; shr.u32 st, mt, 7; shr.u32 cnt, mt, 5; add.u32 cnt, cnt, st; and.b32 cnt, cnt, 3;\n"
            "and.b32 mt, mt, 31; mad.lo.u32 tmp, mt, 16, aa; mad.lo.u32 tmp, st, 82432, tmp; mad.lo.u32 tmp, cnt, 10240, tmp; add.u32 cnt, cnt, 5;\n"
            "bar.sync cnt, 64;\n"
            "stmatrix.sync.aligned.m8n8.x4.shared.b16 [tmp+0], {p0,p1,p2,p3};\n"
            "stmatrix.sync.aligned.m8n8.x4.shared.b16 [tmp+41216], {p4,p5,p6,p7};\n"
            "stmatrix.sync.aligned.m8n8.x4.shared.b16 [tmp+1024], {p8,p9,p10,p11};\n"
            "stmatrix.sync.aligned.m8n8.x4.shared.b16 [tmp+42240], {p12,p13,p14,p15};\n"
            "stmatrix.sync.aligned.m8n8.x4.shared.b16 [tmp+2048], {p16,p17,p18,p19};\n"
            "stmatrix.sync.aligned.m8n8.x4.shared.b16 [tmp+43264], {p20,p21,p22,p23};\n"
            "stmatrix.sync.aligned.m8n8.x4.shared.b16 [tmp+3072], {p24,p25,p26,p27};\n"
            "stmatrix.sync.aligned.m8n8.x4.shared.b16 [tmp+44288], {p28,p29,p30,p31};\n"
            "stmatrix.sync.aligned.m8n8.x4.shared.b16 [tmp+4096], {p32,p33,p34,p35};\n"
            "stmatrix.sync.aligned.m8n8.x4.shared.b16 [tmp+45312], {p36,p37,p38,p39};\n"
            "stmatrix.sync.aligned.m8n8.x4.shared.b16 [tmp+5120], {p40,p41,p42,p43};\n"
            "stmatrix.sync.aligned.m8n8.x4.shared.b16 [tmp+46336], {p44,p45,p46,p47};\n"
            "stmatrix.sync.aligned.m8n8.x4.shared.b16 [tmp+6144], {p48,p49,p50,p51};\n"
            "stmatrix.sync.aligned.m8n8.x4.shared.b16 [tmp+47360], {p52,p53,p54,p55};\n"
            "stmatrix.sync.aligned.m8n8.x4.shared.b16 [tmp+7168], {p56,p57,p58,p59};\n"
            "stmatrix.sync.aligned.m8n8.x4.shared.b16 [tmp+48384], {p60,p61,p62,p63};\n"
            "stmatrix.sync.aligned.m8n8.x4.shared.b16 [tmp+8192], {p64,p65,p66,p67};\n"
            "stmatrix.sync.aligned.m8n8.x4.shared.b16 [tmp+49408], {p68,p69,p70,p71};\n"
            "stmatrix.sync.aligned.m8n8.x4.shared.b16 [tmp+9216], {p72,p73,p74,p75};\n"
            "stmatrix.sync.aligned.m8n8.x4.shared.b16 [tmp+50432], {p76,p77,p78,p79};\n"
            "mov.b32 %0, aa;\n"
            "}\n"
            : "=r"(sb2)
            : "r"(sb + t * XREG + grp * (NST * 2048) + half * 256 + ((g ^ ((2 * t + 2 * half) & 7)) << 4)),
              "r"(sb + AUX_OFF + grp * AUX_GR + t * 32 + (g & 1) * 16), "r"(az),
              "r"(sb + AUX_OFF + grp * AUX_GR + 256 + lane * 8), "r"(zero), "n"(ZERO_OFF),
              "r"(wr[0][0]), "r"(wr[0][1]), "r"(wr[0][2]), "r"(wr[0][3]), "r"(wr[1][0]), "r"(wr[1][1]), "r"(wr[1][2]), "r"(wr[1][3]),
              "r"(wr[2][0]), "r"(wr[2][1]), "r"(wr[2][2]), "r"(wr[2][3]), "r"(wr[3][0]), "r"(wr[3][1]), "r"(wr[3][2]), "r"(wr[3][3])
            : "memory");
        const int tid2 = threadIdx.x;
        sb2 = __shfl_sync(0xffffffffu, sb2, 0);
        const uint2 own = lds64(sb2 + MISC_OFF + 8);
        mbar_wait(sb2 + MISC_OFF, 0);
        asm volatile("fence.proxy.async.shared::cta;" ::: "memory");
        asm volatile("bar.sync 1, 256;" ::: "memory");
        const uint32_t wg = __shfl_sync(0xffffffffu, tid2 >> 7, 0);
        const uint64_t da = (uint64_t)((sb2 + WM_OFF + wg * 16384) >> 4) | (1ull << 16) | (64ull << 32) | (1ull << 62);
        const uint64_t db = (uint64_t)(sb2 >> 4) | (8ull << 16) | (64ull << 32);
        const int left = (int)own.y - 4 * (tid2 & 3);
        uint32_t* op = out + (size_t)(own.x + 4 * (tid2 & 3)) * 256 + ((tid2 >> 5) * 16 + ((tid2 & 31) >> 2)) * 2;
        float d0[40], d1[40], d2[40], d3[40], d4[40];
        mix_tiles<2, 0>(d0, da, db);
        mix_tiles<3, 2>(d1, da, db);
        store_tiles<2, 0, 1>(d0, op, left, 3 + wg);
        mix_tiles<5, 5>(d2, da, db);
        store_tiles<3, 2, 1>(d1, op, left, 3 + wg);
        mix_tiles<5, 10>(d3, da, db);
        store_tiles<5, 5, 1>(d2, op, left, 3 + wg);
        mix_tiles<5, 15>(d4, da, db);
        store_tiles<5, 10, 1>(d3, op, left, 3 + wg);
        store_tiles<5, 15, 0>(d4, op, left, 3 + wg);
    } else {
        asm volatile("setmaxnreg.dec.sync.aligned.u32 40;");
        const uint64_t map = ((uint64_t)maphi << 32) | maplo, efl = ((uint64_t)efhi << 32) | eflo;
        const uint32_t ab = s0 + AUX_OFF + pgrp * AUX_GR, xb = s0 + pgrp * (NST * 2048);
        uint32_t yp = s0 + SY_OFF + pgrp * GCAP * 4 - 32;
        uint32_t par = 0, prev = 0;
        uint32_t parv = keep((lane & zero) + (pgrp & 1) * 128);
        auto ahead = [&](int st, uint32_t ev) {
            asm volatile("cp.async.ca.shared.global [%0], [%1], 8;" ::"r"(w_l + st * AUX_ST + 256), "l"(efl + (ev & 0x1ffffe0u)) : "memory");
            cp_async_arrive(ab + st * AUX_ST + BAR_F0);
            if (st == NST - 1) parv ^= 1u;
            sts8(f_l + st * AUX_ST, (__byte_perm(ev, prev, fsel) & 0xfeu) ^ parv);
            prev = ev;
        };
        if (lds32(yp + 32 + 7 * 4) > (uint32_t)N) pc = 0;
        uint32_t wn0, wn1;
        uint32_t efo = blockIdx.x * EPC * 32u + pgrp * PFE;
        const uint32_t efend = min((blockIdx.x + 1) * EPC, E) * 32u;
        uint32_t pfo = (4u * (PFA * gridDim.x + blockIdx.x) + pgrp) * pfb;
        const uint32_t pfend = (uint32_t)N * 1024u - pfb;
        auto step = [&](int st, int WM) {
            if (left < st) return true;
            const uint4 y0 = lds128(yp + st * 32), y1 = lds128(yp + st * 32 + 16);
            const uint32_t ev = lds32(yp + st * 32 + 32 + e_l);
            uint32_t wa = wn0, wb = wn1;
            if (WM) {
                const uint32_t h0 = lds32(h_l + st * 64), h1 = lds32(h_l + st * 64 + 64);
                float w0[4], w1[4];
                mma1688_z(w0, h0, h1, cgb0);
                mma1688_z(w1, h0, h1, cgb1);
                wa = pack_bf16(w0[0], w0[1]); wb = pack_bf16(w1[0], w1[1]);
                if (WM == 2) { wn0 = pack_bf16(w0[2], w0[3]); wn1 = pack_bf16(w1[2], w1[3]); }
            }
            const uint32_t ys = y0.y + y0.z + y1.y + y1.z;
            const uint32_t tq = T0 + ((ys * pc) >> 13);
            const int sg = st % NST;
            mbar_wait(ab + sg * AUX_ST + BAR_EM, par ^ 1u);
            int rem = (int)(tq - (uint32_t)clock64());
            ahead(sg, ev);
            sts64(w_l + sg * AUX_ST, wa, wb);
            __syncwarp();
            asm volatile("{\n\t.reg .pred P;\n\tsetp.ne.u32 P, %1, 0;\n\t@P mbarrier.arrive.expect_tx.shared::cta.b64 _, [%0], %1;\n\t}"
                         ::"r"(ab + sg * AUX_ST + BAR_F0), "r"(bytes) : "memory");
#pragma unroll 1
            while (rem > 0) {
                __nanosleep(SLEEP);
                rem = (int)(tq - (uint32_t)clock64());
            }
            fetch_quad(xb + sg * 2048, ab + sg * AUX_ST + BAR_F0, y0, map);
            fetch_quad(xb + sg * 2048 + 1024, ab + sg * AUX_ST + BAR_F0, y1, map);
            return false;
        };
        ahead(0, lds32(yp + 32 + e_l));
        __syncwarp();
        if (lane == 0) asm volatile("mbarrier.arrive.shared::cta.b64 _, [%0], %1;" ::"r"(ab + BAR_F0), "n"(F0_COUNT - 32) : "memory");
#pragma unroll 1
        for (;;) {
            if (step(1, 2)) break;
            if (step(2, 0)) break;
            if (efo < efend) prefetch_bulk(ef + efo, min(PFE, efend - efo));
            efo += 4u * PFE;
            if (step(3, 2)) break;
            if (step(4, 0)) break;
            par ^= 1u;
            if (step(5, 1)) break;
            if (pfo <= pfend) prefetch_bulk(x + pfo, pfb);
            pfo += 4u * gridDim.x * pfb;
            yp += NST * 32;
            left -= NST;
            h_l += NST * 64;
        }
        const uint32_t fin = left == NST - 1 ? 0 : left + 1;
        mbar_wait(ab + fin * AUX_ST + BAR_EM, par ^ 1u);
        if (lane == 0) asm volatile("mbarrier.arrive.shared::cta.b64 _, [%0], %1;" ::"r"(ab + fin * AUX_ST + BAR_F0), "n"(F0_COUNT) : "memory");
        asm volatile("bar.sync 2, 128;" ::: "memory");
        const int ln = threadIdx.x & 31;
#pragma unroll 4
        for (int i = 0; i < 16; i++) {
            const int kr = i * 8 + ((threadIdx.x >> 4) & 7);
            const int dj = ((i >> 1) & 1) + (i & 4), n = kr & 7;
            const int ch = 16 * (2 * (i >> 3) + dj) + 2 * (n ^ dj) + (i & 1);
            asm volatile("cp.async.cg.shared.global [%0], [%1], 16;"
                         ::"r"(s0 + WM_OFF + ((ln >> 3) & 1) * 16384 + kr * 128 + (((ln & 7) ^ n) << 4)),
                           "l"(w_mix + ch * 128 + (ln & 15) * 8) : "memory");
        }
        cp_async_arrive(s0 + MISC_OFF);
        asm volatile("cp.async.wait_all;" ::: "memory");
    }
}

typedef CUresult (*EncodeFn)(CUtensorMap*, CUtensorMapDataType, cuuint32_t, void*, const cuuint64_t*, const cuuint64_t*,
                             const cuuint32_t*, const cuuint32_t*, CUtensorMapInterleave, CUtensorMapSwizzle,
                             CUtensorMapL2promotion, CUtensorMapFloatOOBfill);

}

#define WALK 45800
#define LEAD 6300

extern "C" void kernel_launch(void* const* d_in, const int* in_sizes, int n_in, void* d_out, int out_size) {
    const char* x = (const char*)d_in[0];
    const int* src = (const int*)d_in[1];
    const int* dst = (const int*)d_in[2];
    const uint2* Y = (const uint2*)d_in[3];
    const char* ef = (const char*)d_in[4];
    const __nv_bfloat16* w_rad = (const __nv_bfloat16*)d_in[5];
    const __nv_bfloat16* cg = (const __nv_bfloat16*)d_in[6];
    const __nv_bfloat16* w_mix = (const __nv_bfloat16*)d_in[7];
    const int N = in_sizes[0] / 512;
    const int E = in_sizes[1];

    static int num_cta = 0;
    static EncodeFn encode = nullptr;
    if (num_cta == 0) {
        int dev = 0, sms = 0;
        cudaGetDevice(&dev);
        cudaDeviceGetAttribute(&sms, cudaDevAttrMultiProcessorCount, dev);
        num_cta = sms < MAXCTA ? sms : MAXCTA;
        cudaFuncSetAttribute(tfn_kernel, cudaFuncAttributeMaxDynamicSharedMemorySize, SMEM_BYTES);
        void* fn = nullptr;
        cudaDriverEntryPointQueryResult qr;
        cudaGetDriverEntryPoint("cuTensorMapEncodeTiled", &fn, cudaEnableDefault, &qr);
        encode = (EncodeFn)fn;
    }
    int S = (N + num_cta - 1) / num_cta;
    if (S < 2) S = 2;
    const int EPC = ((E + num_cta - 1) / num_cta + 3) & ~3;
    if (S > SMAX || (E + 127) / 128 > 2 * NWARP * num_cta || N < 128 || N > 16384 || E <= 0 || E > (1 << 20) || encode == nullptr) return;
    CUtensorMap xmap;
    const cuuint64_t gd[2] = {64, (cuuint64_t)N * 8}, gs[1] = {128};
    const cuuint32_t bx[2] = {64, BOX_LINES}, es[2] = {1, 1};
    if (encode(&xmap, CU_TENSOR_MAP_DATA_TYPE_BFLOAT16, 2, (void*)x, gd, gs, bx, es, CU_TENSOR_MAP_INTERLEAVE_NONE,
               CU_TENSOR_MAP_SWIZZLE_128B, CU_TENSOR_MAP_L2_PROMOTION_NONE, CU_TENSOR_MAP_FLOAT_OOB_FILL_NONE) != CUDA_SUCCESS)
        return;
    const uint32_t magicS = (uint32_t)((0x100000000ull + S - 1) / S);
    uint32_t magicB = (uint32_t)(((unsigned long long)NB << 32) / N);
    int walk = WALK, lead = LEAD;
    double pc = (double)walk * ((double)E / N * S / 2432.0) / (16.0 * N);
    if (pc > 0.99) pc = 0.99;
    uint32_t pace = (uint32_t)(pc * 4096.0 + 0.5), curve = 0;
    const uint32_t pfb = ((uint32_t)(1024.0 * N / E * 40.0) + 127u) & ~127u;
    tfn_kernel<<<num_cta, NT, SMEM_BYTES, cudaStreamPerThread>>>(xmap, x, src, dst, Y, ef, w_rad, cg, w_mix, (uint32_t*)d_out, N, E, S,
                                                                 EPC, magicS, 0u - S, magicB, 0u, pace, lead, pfb, curve);
}
```

```cpp
#include <cuda_runtime.h>
#include <cuda.h>
#include <cuda_bf16.h>
#include <stdint.h>
#include <stddef.h>

namespace {

constexpr int NT = 384;
constexpr int NWARP = NT / 32;
constexpr int MAXCTA = 132;
constexpr int SFAST = 80;
constexpr int SMAX = 96;
constexpr int EPC_MAX = 3072;
constexpr int RND = 10;
constexpr int NB = 96;
constexpr int GCAP = 800;
constexpr int NCOL = NWARP - 1;
constexpr int KCAP = 1024;
constexpr int RND0 = 8;
constexpr uint32_t TAGM = 31u;
constexpr int NST = 5;
constexpr uint32_t F0_COUNT = 33;
#define SLEEPNS 100
constexpr uint32_t SLEEP = SLEEPNS;
constexpr uint32_t PFA = 2, PFE = 2048;
constexpr int SPIN_LIMIT = 1 << 22;

constexpr int XREG = 4 * NST * 2048 + 256;
constexpr int AUX_OFF = 4 * XREG;
constexpr int AUX_ST = 2560, AUX_GR = 640;
constexpr int BAR_F0 = 520, BAR_EM = 536;
constexpr int SY_OFF = AUX_OFF + NST * AUX_ST;
constexpr int SE_OFF = SY_OFF + 4 * GCAP * 4;
constexpr int SH_OFF = SE_OFF + 4 * GCAP * 4;
constexpr int MISC_OFF = SH_OFF + 4 * GCAP * 8;
constexpr int ZERO_OFF = ((MISC_OFF + 1024 + 2047) & ~2047) - 1024;
constexpr int WM_OFF = (SE_OFF + 1023) & ~1023;
constexpr int CNT_OFF = EPC_MAX * 16, START_OFF = CNT_OFF + 1024;
constexpr int BCNT_OFF = START_OFF + 1024;
constexpr int BCUM_OFF = BCNT_OFF + 24 * NB * 4 + 128;
constexpr int SEG_OFF = BCUM_OFF + 24 * NB * 2 + 128;
constexpr int WR_OFF = SEG_OFF + 1024;
constexpr int LDY_OFF = WR_OFF + 4096 + 128;
constexpr int GI_OFF = 0;
struct Misc {
    unsigned long long wbar;
    int node0, Sc;
    unsigned long long rbar;
    int nq[4];
    int dmax;
    uint32_t epoch, ref;
    uint32_t rseg[MAXCTA];
};
constexpr int SMEM_BYTES = ZERO_OFF + 1792;
static_assert(MISC_OFF + (int)sizeof(Misc) <= ZERO_OFF, "layout");
static_assert(SMEM_BYTES <= 227 * 1024, "shared memory");
static_assert(24 * KCAP + NCOL * RND * 32 + 64 <= 32768 && GCAP <= KCAP && LDY_OFF + EPC_MAX * 8 <= AUX_OFF && WR_OFF % 128 == 0, "tables");
static_assert(WM_OFF + 32768 <= MISC_OFF && SMAX * 2048 <= MISC_OFF, "layout");
static_assert(AUX_OFF % 256 == 0 && NB == 96 && NWARP == 12, "layout");

__device__ __align__(128) uint4 g_staged[(size_t)MAXCTA * EPC_MAX];
__device__ __align__(128) uint2 g_table[MAXCTA * 144];
__device__ unsigned int g_epoch[MAXCTA];

__device__ __forceinline__ void mma1688_z(float (&d)[4], uint32_t a0, uint32_t a1, uint32_t b0) {
    asm volatile(
        "mma.sync.aligned.m16n8k8.row.col.f32.bf16.bf16.f32 {%0,%1,%2,%3}, {%4,%5}, {%6}, {%7,%7,%7,%7};"
        : "=f"(d[0]), "=f"(d[1]), "=f"(d[2]), "=f"(d[3])
        : "r"(a0), "r"(a1), "r"(b0), "f"(0.0f));
}
__device__ __forceinline__ uint32_t pack_bf16(float lo, float hi) {
    uint32_t r;
    asm("cvt.rn.bf16x2.f32 %0, %1, %2;" : "=r"(r) : "f"(hi), "f"(lo));
    return r;
}
__device__ __forceinline__ uint32_t half_bf16x2(uint32_t v) {
    uint32_t r;
    asm("mul.bf16x2 %0, %1, %2;" : "=r"(r) : "r"(v), "r"(0x3f003f00u));
    return r;
}
__device__ __forceinline__ uint4 lds128(uint32_t a) {
    uint4 v;
    asm volatile("ld.shared.v4.u32 {%0,%1,%2,%3}, [%4];" : "=r"(v.x), "=r"(v.y), "=r"(v.z), "=r"(v.w) : "r"(a) : "memory");
    return v;
}
__device__ __forceinline__ uint32_t lds32(uint32_t a) {
    uint32_t v;
    asm volatile("ld.shared.u32 %0, [%1];" : "=r"(v) : "r"(a) : "memory");
    return v;
}
__device__ __forceinline__ uint2 lds64(uint32_t a) {
    uint2 v;
    asm volatile("ld.shared.v2.u32 {%0,%1}, [%2];" : "=r"(v.x), "=r"(v.y) : "r"(a) : "memory");
    return v;
}
__device__ __forceinline__ uint32_t atoms_add(uint32_t a, uint32_t v) {
    uint32_t r;
    asm volatile("atom.shared.add.u32 %0, [%1], %2;" : "=r"(r) : "r"(a), "r"(v) : "memory");
    return r;
}
__device__ __forceinline__ void sts8(uint32_t a, uint32_t v) {
    asm volatile("st.shared.u8 [%0], %1;" ::"r"(a), "r"(v) : "memory");
}
__device__ __forceinline__ void sts64(uint32_t a, uint32_t v0, uint32_t v1) {
    asm volatile("st.shared.v2.u32 [%0], {%1,%2};" ::"r"(a), "r"(v0), "r"(v1) : "memory");
}
#define OCT_BYTES 8192
#define BOX_LINES 8
__device__ __forceinline__ void fetch_quad(uint32_t dst, uint32_t bar, const uint4& y, uint64_t map) {
    asm volatile("{\n\t.reg .pred P;\n\telect.sync _|P, 0xffffffff;\n\t"
                 "@P cp.async.bulk.tensor.2d.shared::cluster.global.mbarrier::complete_tx::bytes [%0], [%6, {0, %2}], [%1];\n\t"
                 "@P cp.async.bulk.tensor.2d.shared::cluster.global.mbarrier::complete_tx::bytes [%0+%7], [%6, {0, %3}], [%1];\n\t"
                 "@P cp.async.bulk.tensor.2d.shared::cluster.global.mbarrier::complete_tx::bytes [%0+%8], [%6, {0, %4}], [%1];\n\t"
                 "@P cp.async.bulk.tensor.2d.shared::cluster.global.mbarrier::complete_tx::bytes [%0+%9], [%6, {0, %5}], [%1];\n\t}"
                 ::"r"(dst), "r"(bar), "r"(y.x), "r"(y.y), "r"(y.z), "r"(y.w), "l"(map), "n"(XREG), "n"(2 * XREG), "n"(3 * XREG)
                 : "memory");
}
__device__ __forceinline__ void cp_async_arrive(uint32_t bar) {
    asm volatile("cp.async.mbarrier.arrive.noinc.shared::cta.b64 [%0];" ::"r"(bar) : "memory");
}
__device__ __forceinline__ void mbar_init(uint32_t bar, uint32_t count) {
    asm volatile("mbarrier.init.shared::cta.b64 [%0], %1;" ::"r"(bar), "r"(count) : "memory");
}
__device__ __forceinline__ bool mbar_try(uint32_t bar, uint32_t parity) {
    uint32_t ok;
    asm volatile("{\n\t.reg .pred p;\n\tmbarrier.try_wait.parity.shared::cta.b64 p, [%1], %2;\n\tselp.u32 %0, 1, 0, p;\n\t}"
                 : "=r"(ok) : "r"(bar), "r"(parity) : "memory");
    return ok;
}
__device__ __forceinline__ void mbar_wait(uint32_t bar, uint32_t parity) {
    if (mbar_try(bar, parity)) return;
#pragma unroll 1
    for (int it = 0; it < SPIN_LIMIT; it++)
        if (mbar_try(bar, parity)) return;
    __trap();
}
__device__ __forceinline__ uint32_t clock_lo() {
    uint32_t v;
    asm volatile("mov.u32 %0, %%clock;" : "=r"(v));
    return v;
}
__device__ __forceinline__ uint32_t global_ticks() {
    uint32_t v;
    asm volatile("mov.u32 %0, %%globaltimer_lo;" : "=r"(v));
    return v >> 5;
}

#define TBL(snd, own) ((snd) * 144 + (own))
__device__ __forceinline__ void prefetch_line(const void* p) { asm volatile("prefetch.global.L2 [%0];" ::"l"(p)); }
__device__ __forceinline__ void prefetch_bulk(const void* p, uint32_t bytes) {
    asm volatile("{\n\t.reg .pred P;\n\telect.sync _|P, 0xffffffff;\n\t@P cp.async.bulk.prefetch.L2.global [%0], %1;\n\t}"
                 ::"l"(p), "r"(bytes) : "memory");
}
__device__ __forceinline__ uint4 ld_entry(const uint4* p) {
    uint4 e;
    asm volatile("ld.relaxed.gpu.global.v4.u32 {%0,%1,%2,%3}, [%4];" : "=r"(e.x), "=r"(e.y), "=r"(e.z), "=r"(e.w) : "l"(p) : "memory");
    return e;
}
__device__ __forceinline__ uint4 wait_entry(const uint4* p, uint4 e, uint32_t tag) {
    int it = 0;
    while (((e.y ^ tag) & TAGM) != 0u) {
        if (++it > SPIN_LIMIT) __trap();
        e = ld_entry(p);
    }
    return e;
}
__device__ __forceinline__ uint4 ldg128_if(bool p, const void* a, uint32_t other) {
    uint4 v = make_uint4(other, other, other, other);
    asm volatile("{\n\t.reg .pred P;\n\tsetp.ne.u32 P, %5, 0;\n\t@P ld.global.nc.L1::no_allocate.v4.u32 {%0,%1,%2,%3}, [%4];\n\t}"
                 : "+r"(v.x), "+r"(v.y), "+r"(v.z), "+r"(v.w) : "l"(a), "r"((uint32_t)p));
    return v;
}
__device__ __forceinline__ void stg64_if(bool p, void* a, uint32_t v0, uint32_t v1) {
    asm volatile("{\n\t.reg .pred P;\n\tsetp.ne.u32 P, %0, 0;\n\t@P st.global.v2.u32 [%1], {%2,%3};\n\t}"
                 ::"r"((uint32_t)p), "l"(a), "r"(v0), "r"(v1) : "memory");
}
__device__ __forceinline__ float bf_lo(uint32_t v) { return __uint_as_float(v << 16); }
__device__ __forceinline__ float bf_hi(uint32_t v) { return __uint_as_float(v & 0xffff0000u); }

#define F8(o) "+f"(d[o]), "+f"(d[o + 1]), "+f"(d[o + 2]), "+f"(d[o + 3]), "+f"(d[o + 4]), "+f"(d[o + 5]), "+f"(d[o + 6]), "+f"(d[o + 7])
template <int T>
__device__ __forceinline__ void wgmma_tiles(float (&d)[32], const uint32_t (&a)[4], uint64_t b, uint32_t acc) {
    if constexpr (T == 2)
        asm volatile("{\n\t.reg .pred P;\n\tsetp.ne.u32 P, %21, 0;\n\twgmma.mma_async.sync.aligned.m64n32k16.f32.bf16.bf16 "
                     "{%0,%1,%2,%3,%4,%5,%6,%7,%8,%9,%10,%11,%12,%13,%14,%15}, "
                     "{%16,%17,%18,%19}, %20, P, 1, 1, 0;\n\t}"
                     : F8(0), F8(8) : "r"(a[0]), "r"(a[1]), "r"(a[2]), "r"(a[3]), "l"(b), "r"(acc));
    if constexpr (T == 4)
        asm volatile("{\n\t.reg .pred P;\n\tsetp.ne.u32 P, %37, 0;\n\twgmma.mma_async.sync.aligned.m64n64k16.f32.bf16.bf16 "
                     "{%0,%1,%2,%3,%4,%5,%6,%7,%8,%9,%10,%11,%12,%13,%14,%15,%16,%17,%18,%19,%20,%21,%22,%23,%24,%25,%26,%27,%28,%29,%30,%31}, "
                     "{%32,%33,%34,%35}, %36, P, 1, 1, 0;\n\t}"
                     : F8(0), F8(8), F8(16), F8(24) : "r"(a[0]), "r"(a[1]), "r"(a[2]), "r"(a[3]), "l"(b), "r"(acc));
}
template <int T, int O, int K0, int K1>
__device__ __forceinline__ void mix_tiles(float (&d)[32], const uint32_t (&da)[8][4], uint64_t db) {
    if (K0 == 0) asm volatile("wgmma.fence.sync.aligned;" ::: "memory");
#pragma unroll
    for (int ks = K0; ks < K1; ks++) wgmma_tiles<T>(d, da[ks], db + O * 128 + (ks >> 1) * (XREG / 16) + (ks & 1) * 16, ks);
    asm volatile("wgmma.commit_group.sync.aligned;" ::: "memory");
}
template <int T, int PENDING>
__device__ __forceinline__ void wait_tiles(float (&d)[32]) {
    asm volatile("wgmma.wait_group.sync.aligned %0;" ::"n"(PENDING) : "memory");
#pragma unroll
    for (int i = 0; i < 8 * T; i++) asm volatile("" : "+f"(d[i])::"memory");
}
template <int O, int K0, int K1, bool PIN>
__device__ __forceinline__ void store_tiles(float (&d)[32], uint32_t* op, int left, uint32_t bar) {
#pragma unroll
    for (int k = K0; k < K1; k++) {
        const int n = 16 * ((O + k) % 5) + (O + k) / 5;
#pragma unroll
        for (int u = 0; u < 2; u++)
            stg64_if(n < left, op + n * 256 + u * 16, pack_bf16(d[8 * k + 2 * u], d[8 * k + 2 * u + 1]),
                     pack_bf16(d[8 * k + 4 + 2 * u], d[8 * k + 4 + 2 * u + 1]));
    }
    if (PIN) asm volatile("bar.sync %0, 128;" ::"r"(bar) : "memory");
}

__device__ __noinline__ void slow_cta(unsigned char* smem, const char* x, const char* ef, const __nv_bfloat16* w_rad,
                                      const __nv_bfloat16* cg, const __nv_bfloat16* w_mix, uint32_t* out, int node0, int Sc,
                                      uint32_t tag) {
    float* agg = reinterpret_cast<float*>(smem);
    Misc& ms = *reinterpret_cast<Misc*>(smem + MISC_OFF);
    const int tid = threadIdx.x, lane = tid & 31, warp = tid >> 5;
#pragma unroll 1
    for (int i = tid; i < Sc * 512; i += NT) agg[i] = 0.f;
    if (tid < (int)gridDim.x) {
        uint32_t v;
        asm volatile("ld.relaxed.gpu.global.u32 %0, [%1];" : "=r"(v) : "l"(&g_table[TBL(tid, blockIdx.x)]) : "memory");
        ms.rseg[tid] = v;
    }
    __syncthreads();
    uint2 wr[16];
#pragma unroll
    for (int f = 0; f < 16; f++) wr[f] = *reinterpret_cast<const uint2*>(w_rad + f * 128 + 4 * lane);
    float cgl[4];
#pragma unroll
    for (int f = 0; f < 4; f++) cgl[f] = __bfloat162float(cg[((lane >> 2) & 3) * 16 + f * 4 + (lane & 3)]);
    for (int s = 0; s < (int)gridDim.x; s++) {
        const int cn = ms.rseg[s] & 0xfffu;
        const uint4* p = g_staged + s * EPC_MAX + ((ms.rseg[s] >> 12) & 0xfffu);
        for (int i0 = 0; i0 < cn; i0 += 32) {
          uint4 el = make_uint4(0u, 0u, 0u, 0u);
          int dll = -1;
          if (i0 + lane < cn) {
              el = wait_entry(p + i0 + lane, ld_entry(p + i0 + lane), tag);
              dll = (int)(((el.y >> 25) & 31u) * 4 + (((el.x >> 20) / NB) & 3u));
          }
          for (uint32_t m = __ballot_sync(0xffffffffu, dll >= 0 && dll % NWARP == warp); m; m &= m - 1) {
            const int from = __ffs(m) - 1;
            const uint4 e = make_uint4(__shfl_sync(0xffffffffu, el.x, from), __shfl_sync(0xffffffffu, el.y, from),
                                       __shfl_sync(0xffffffffu, el.z, from), __shfl_sync(0xffffffffu, el.w, from));
            float* ap = agg + __shfl_sync(0xffffffffu, dll, from) * 512 + lane;
            const uint4* xp = reinterpret_cast<const uint4*>(x + (size_t)(e.x & 0x1fff8u) * 128 + lane * 32);
            const uint4* fp = reinterpret_cast<const uint4*>(ef + (e.y & 0x1ffffe0u));
            const uint4 xa = xp[0], xb = xp[1], fa = fp[0], fb = fp[1];
            const uint32_t fv[8] = {fa.x, fa.y, fa.z, fa.w, fb.x, fb.y, fb.z, fb.w};
            const uint32_t xv[8] = {xa.x, xa.y, xa.z, xa.w, xb.x, xb.y, xb.z, xb.w};
            float h[4] = {0.f, 0.f, 0.f, 0.f};
#pragma unroll
            for (int f = 0; f < 16; f++) {
                const float v = (f & 1) ? bf_hi(fv[f >> 1]) : bf_lo(fv[f >> 1]);
                h[0] += v * bf_lo(wr[f].x); h[1] += v * bf_hi(wr[f].x); h[2] += v * bf_lo(wr[f].y); h[3] += v * bf_hi(wr[f].y);
            }
            const float wl = bf_lo(e.z) * cgl[0] + bf_hi(e.z) * cgl[1] + bf_lo(e.w) * cgl[2] + bf_hi(e.w) * cgl[3];
#pragma unroll
            for (int k = 0; k < 4; k++) h[k] = __fdividef(h[k], 1.f + __expf(-h[k]));
#pragma unroll
            for (int o = 0; o < 4; o++) {
                const float w0 = __shfl_sync(0xffffffffu, wl, o), w1 = __shfl_sync(0xffffffffu, wl, 4 + o);
                const float w2 = __shfl_sync(0xffffffffu, wl, 8 + o), w3 = __shfl_sync(0xffffffffu, wl, 12 + o);
#pragma unroll
                for (int k = 0; k < 4; k++) {
                    const float tp = bf_lo(xv[2 * k]) * w0 + bf_hi(xv[2 * k]) * w1 + bf_lo(xv[2 * k + 1]) * w2 + bf_hi(xv[2 * k + 1]) * w3;
                    ap[(k * 4 + o) * 32] += tp * h[k];
                }
            }
          }
        }
    }
    __syncthreads();
    for (int n = tid >> 7; n < Sc; n += NT / 128) {
        const int d = tid & 127;
        float o[4] = {0.f, 0.f, 0.f, 0.f};
#pragma unroll 4
        for (int c = 0; c < 128; c++) {
            const float* a = agg + n * 512 + (c & 3) * 128 + (c >> 2);
            const float w = __bfloat162float(w_mix[c * 128 + d]);
            o[0] += a[0] * w; o[1] += a[32] * w; o[2] += a[64] * w; o[3] += a[96] * w;
        }
        *reinterpret_cast<uint2*>(out + (size_t)(node0 + n) * 256 + d * 2) = make_uint2(pack_bf16(o[0], o[1]), pack_bf16(o[2], o[3]));
    }
}

__global__ void __launch_bounds__(NT, 1)
tfn_kernel(const __grid_constant__ CUtensorMap xmap, const char* __restrict__ x, const int* __restrict__ src,
           const int* __restrict__ dst, const uint2* __restrict__ Y, const char* __restrict__ ef,
           const __nv_bfloat16* __restrict__ w_rad, const __nv_bfloat16* __restrict__ cg,
           const __nv_bfloat16* __restrict__ w_mix, uint32_t* __restrict__ out, int N, int E, int S, int EPC,
           uint32_t magicS, uint32_t negS, uint32_t magicB, uint32_t zero, uint32_t pace, int lead, uint32_t pfb, uint32_t curve) {
    extern __shared__ __align__(1024) unsigned char smem[];
    Misc& ms = *reinterpret_cast<Misc*>(smem + MISC_OFF);
    int* const cnt = reinterpret_cast<int*>(smem + CNT_OFF);
    int* const start = reinterpret_cast<int*>(smem + START_OFF);
    uint2* const bcnt = reinterpret_cast<uint2*>(smem + BCNT_OFF);
    const int tid = threadIdx.x;
    const int lane = tid & 31, warp = __shfl_sync(0xffffffffu, tid >> 5, 0);
    const int c = blockIdx.x;
    const int numCTA = gridDim.x;
    const int node0 = c * S;
    const int Sc = max(0, min(S, N - node0));
    const uint32_t sb = (uint32_t)__cvta_generic_to_shared(smem);

    const int e0[2] = {(warp * numCTA + c) * 128 + 4 * lane, ((warp + NWARP) * numCTA + c) * 128 + 4 * lane};
    int d8[8], s8[8];
#pragma unroll
    for (int h = 0; h < 2; h++) {
        const uint4 v = ldg128_if(e0[h] + 3 < E, dst + e0[h], (MAXCTA + 4 + lane) * S);
        d8[4 * h] = (int)v.x; d8[4 * h + 1] = (int)v.y; d8[4 * h + 2] = (int)v.z; d8[4 * h + 3] = (int)v.w;
    }
#pragma unroll
    for (int h = 0; h < 2; h++) {
        const uint4 v = ldg128_if(e0[h] + 3 < E, src + e0[h], 0u);
        s8[4 * h] = (int)v.x; s8[4 * h + 1] = (int)v.y; s8[4 * h + 2] = (int)v.z; s8[4 * h + 3] = (int)v.w;
    }
    if (tid == NT - 64) asm volatile("prefetch.tensormap [%0];" ::"l"(&xmap) : "memory");
    uint32_t ep0 = 0;
    if (tid == NT - 1) asm volatile("ld.relaxed.gpu.global.u32 %0, [%1];" : "=r"(ep0) : "l"(&g_epoch[c]) : "memory");
    if (warp == 7) {
        for (int i = c + lane * numCTA; i <= 32 + 256; i += 32 * numCTA)
            prefetch_line(i < 32 ? (const char*)w_rad + i * 128 : (i < 288 ? (const char*)w_mix + (i - 32) * 128 : (const char*)cg));
    }
    if (tid < MAXCTA) cnt[tid] = 0;
#pragma unroll
    for (int k = 0; k < 3; k++) bcnt[tid + k * NT] = make_uint2(0u, 0u);
    if (tid < 224) reinterpret_cast<uint2*>(smem + ZERO_OFF)[tid] = make_uint2(0u, 0u);
    if (tid >= 160 && tid < 320) {
        const int i = tid - 160;
        *reinterpret_cast<uint32_t*>(smem + AUX_OFF + (i >> 5) * AUX_ST + ((i >> 3) & 3) * AUX_GR + 512 + (i & 7) * 16) =
            (i >> 5) == NST - 1 ? (uint32_t)(1 - NST) << 24 : 1u << 24;
    }
    auto load_y = [&]() {
#pragma unroll
        for (int h = 0; h < 4; h++) {
            const int i = e0[h >> 1] - 2 * lane + (h & 1) * 64;
            asm volatile("cp.async.cg.shared.global [%0], [%1], 16, %2;" ::"r"(sb + LDY_OFF + warp * 2048 + h * 512 + lane * 16),
                         "l"(Y + min(i, E - 1 & ~1)), "r"(max(0, min(2, E - i)) * 8) : "memory");
        }
    };
    if (lane < NST && warp < 8) {
        const int k = warp >> 2;
        mbar_init(sb + AUX_OFF + lane * AUX_ST + (warp & 3) * AUX_GR + BAR_F0 + 16 * k, k == 0 ? F0_COUNT : 2u);
    }
    if (tid == 330) { mbar_init(sb + MISC_OFF + 16, 1); mbar_init(sb + MISC_OFF, 128); ms.node0 = node0; ms.Sc = Sc; ms.dmax = -32768; ms.ref = global_ticks(); }
    __syncthreads();
    load_y();
    if (E & 3) {
#pragma unroll
        for (int k = 0; k < 8; k++) {
            const int i = e0[k >> 2] + (k & 3);
            if (i >= (E & ~3) && i < E) { d8[k] = __ldg(dst + i); s8[k] = __ldg(src + i); }
        }
    }
    const uint32_t one = 1u + (lane & zero);
    const bool second = e0[1] - 4 * lane < E;
    uint32_t bin[8], pos[8];
#pragma unroll
    for (int k = 0; k < 8; k++) bin[k] = __umulhi((uint32_t)d8[k], magicS);
#pragma unroll
    for (int k = 0; k < 4; k++) pos[k] = atoms_add(sb + CNT_OFF + bin[k] * 4, one);
    if (second) {
#pragma unroll
        for (int k = 4; k < 8; k++) pos[k] = atoms_add(sb + CNT_OFF + bin[k] * 4, one);
    }
    if (tid == NT - 1) {
        ms.epoch = ep0 + 1u;
        g_epoch[c] = ep0 + 1u;
    }
    __syncthreads();
    const uint32_t epoch = ms.epoch;
    const uint32_t tag = epoch & TAGM;
    uint32_t w0[8], w1[8];
    auto words = [&](int h) {
#pragma unroll
        for (int k = 4 * h; k < 4 * h + 4; k++) {
            const uint32_t dl = (uint32_t)d8[k] + bin[k] * negS, sr = (uint32_t)s8[k];
            w0[k] = (((((dl >> 3) & ~3u) | (dl & 3u)) * NB + __umulhi(sr, magicB)) << 20) + ((dl & 16u) * 4096u + sr) * 8u;
            w1[k] = (dl >> 2) * (33u << 25) + ((uint32_t)e0[h] * 32u + tag + (k & 3) * 32);
        }
    };
    if (warp >= NWARP - 5) {
        const int w = warp - (NWARP - 5), o = tid - (NT - 160);
        int pre = 0;
#pragma unroll
        for (int k = 0; k < 4; k++)
            if (k < w) pre += cnt[lane + 32 * k];
        const int v = o < numCTA ? cnt[o] : 0;
        int incl = v;
#pragma unroll
        for (int d = 1; d < 32; d <<= 1)
            asm volatile("{\n\t.reg .pred P;\n\t.reg .b32 v;\n\tshfl.sync.up.b32 v|P, %0, %1, 0, 0xffffffff;\n\t@P add.u32 %0, %0, v;\n\t}"
                         : "+r"(incl) : "r"(d));
        const int ex = __reduce_add_sync(0xffffffffu, pre) + incl - v;
        start[o] = ex;
        if (o < numCTA)
            asm volatile("st.relaxed.gpu.global.u32 [%0], %1;" ::"l"(g_table + TBL(c, o)), "r"((epoch << 24) | (ex << 12) | v) : "memory");
    }
    __syncthreads();
    if (tid == NT - 64)
        asm volatile("mbarrier.arrive.expect_tx.shared::cta.b64 _, [%3], 4224;\n\t"
                     "cp.async.bulk.shared::cluster.global.mbarrier::complete_tx::bytes [%0], [%1], 4096, [%3];\n\t"
                     "cp.async.bulk.shared::cluster.global.mbarrier::complete_tx::bytes [%0+4096], [%2], 128, [%3];"
                     ::"r"(sb + WR_OFF), "l"(w_rad), "l"(cg), "r"(sb + MISC_OFF + 16) : "memory");
    const int ne = start[MAXCTA];
    auto scatter = [&](int h) {
#pragma unroll
        for (int k = 0; k < 4; k++) pos[4 * h + k] += lds32(sb + START_OFF + bin[4 * h + k] * 4);
        words(h);
        if (h == 0) {
            asm volatile("cp.async.wait_all;" ::: "memory");
            __syncwarp();
        }
        const uint4 ya = lds128(sb + LDY_OFF + warp * 2048 + h * 1024 + lane * 32), yb = lds128(sb + LDY_OFF + warp * 2048 + h * 1024 + lane * 32 + 16);
#pragma unroll
        for (int k = 0; k < 4; k++)
            asm volatile("{\n\t.reg .pred P;\n\tsetp.lt.u32 P, %0, %6;\n\t@P st.shared.v4.u32 [%1], {%2,%3,%4,%5};\n\t}"
                         ::"r"(bin[4 * h + k]), "r"(sb + pos[4 * h + k] * 16), "r"(w0[4 * h + k]), "r"(w1[4 * h + k]),
                           "r"(k == 0 ? ya.x : (k == 1 ? ya.z : (k == 2 ? yb.x : yb.z))),
                           "r"(k == 0 ? ya.y : (k == 1 ? ya.w : (k == 2 ? yb.y : yb.w))), "n"(MAXCTA) : "memory");
    };
    scatter(0);
    if (second) scatter(1);
    asm volatile("fence.proxy.async.shared::cta;" ::: "memory");
    __syncthreads();
    if (tid == NT - 32 && ne > 0) {
        asm volatile("cp.async.bulk.global.shared::cta.bulk_group [%0], [%1], %2;" ::"l"(g_staged + (size_t)c * EPC_MAX),
                     "r"(sb), "r"(ne * 16) : "memory");
        asm volatile("cp.async.bulk.commit_group;" ::: "memory");
    }

    const int g = lane >> 2, t = lane & 3;
    uint32_t wr[4][4];
    const bool mine = warp + NCOL * lane < numCTA && warp < NCOL;
    const uint2* tp = g_table + TBL(warp + NCOL * lane, c);
    auto look = [&](const uint32_t* p, uint32_t& v) {
        asm volatile("{\n\t.reg .pred P;\n\tsetp.ne.u32 P, %2, 0;\n\t@P ld.relaxed.gpu.global.u32 %0, [%1];\n\t}"
                     : "+r"(v) : "l"(p), "r"((uint32_t)mine) : "memory");
    };
    uint32_t sv = epoch << 24;
    look(&tp->x, sv);
    if (tid == 64 && (uint32_t)(c + 1) * 4u * PFA * pfb <= (uint32_t)N * 1024u)
        asm volatile("cp.async.bulk.prefetch.L2.global [%0], %1;" ::"l"(x + (size_t)c * 4u * PFA * pfb), "r"(4u * PFA * pfb) : "memory");
    auto uni = [&](uint32_t v) { return __shfl_sync(0xffffffffu, v + (lane & zero), 0); };
    auto keep = [&](uint32_t v) { return __shfl_sync(0xffffffffu, v, lane); };
    const int pgrp = (warp + 2) & 3;
    uint32_t cgb0, cgb1, s0, maplo, maphi, e_l, h_l, f_l, w_l, eflo, efhi, fsel, bytes, pc, cu, tbase;
    {
        mbar_wait(sb + MISC_OFF + 16, 0);
        const uint4 cv = lds128(sb + WR_OFF + 4096 + (g & 3) * 32 + (t & 1) * 16);
        const uint32_t csel = g < 4 ? 0x5410u : 0x7632u;
        cgb0 = t < 2 ? __byte_perm(cv.x, cv.z, csel) : 0u;
        cgb1 = t < 2 ? __byte_perm(cv.y, cv.w, csel) : 0u;
        s0 = uni(sb);
        const uint64_t map0 = reinterpret_cast<uint64_t>(&xmap), ef0 = reinterpret_cast<uint64_t>(ef) + t * 8;
        maphi = uni((uint32_t)(map0 >> 32)); maplo = uni((uint32_t)(map0 & 0xffffffffu));
        e_l = keep(SE_OFF - SY_OFF + (4 * (g & 1) + (g >> 1)) * 4);
        h_l = keep(sb + SH_OFF + pgrp * GCAP * 8 - 64 + g * 8 + (t & 1) * 4);
        f_l = keep(sb + AUX_OFF + pgrp * AUX_GR + 512 + (g >> 1) * 32 + (t & 1) * 16 + (~g & 1));
        w_l = keep(sb + AUX_OFF + pgrp * AUX_GR + lane * 8);
        efhi = keep((uint32_t)(ef0 >> 32) + (lane & zero)); eflo = keep((uint32_t)(ef0 & 0xffffffffu));
        fsel = keep(g & 1 ? 7 : 3);
        bytes = keep(lane == 0 ? OCT_BYTES : 0u);
        pc = uni(pace); cu = uni(curve);
        tbase = clock_lo() + (uint32_t)((int)(short)(ms.ref - global_ticks()) * 63 + lead);
    }
    if (warp < 8) {
#pragma unroll
        for (int j = 0; j < 4; j++) {
            const int dj = (j & 1) + 4 * (j >> 1);
            const uint32_t p = sb + WR_OFF + t * 4 * 256 + 32 * (2 * ((warp >> 2) & 1) + dj) + 4 * (g ^ dj);
#pragma unroll
            for (int i = 0; i < 4; i++) wr[j][i] = lds32(p + i * 256);
        }
#pragma unroll
        for (int j = 0; j < 4; j++) {
            uint32_t h[4];
#pragma unroll
            for (int i = 0; i < 4; i++) h[i] = half_bf16x2(wr[j][i]);
            wr[j][0] = __byte_perm(h[0], h[1], 0x5410);
            wr[j][1] = __byte_perm(h[0], h[1], 0x7632);
            wr[j][2] = __byte_perm(h[2], h[3], 0x5410);
            wr[j][3] = __byte_perm(h[2], h[3], 0x7632);
        }
    }

    uint4 ent[RND];
    uint32_t rk[RND];
    int tot = 0;
#pragma unroll
    for (int r = 0; r < RND; r++) { ent[r].x = (24 * NB + lane) << 19; rk[r] = 0; }
    if (warp == NWARP - 1) {
        asm volatile("cp.async.bulk.wait_group 0;" ::: "memory");
        __syncwarp();
        const uint32_t w = (epoch << 16) | (global_ticks() & 0xffffu);
#pragma unroll
        for (int k = 0; k < 5; k++)
            asm volatile("{\n\t.reg .pred P;\n\tsetp.lt.s32 P, %0, %1;\n\t@P st.relaxed.gpu.global.u32 [%2+4], %3;\n\t}"
                         ::"r"(lane + 32 * k), "n"(144), "l"(g_table + TBL(c, lane) + 32 * k), "r"(w) : "memory");
    } else {
        const uint4* gp[RND];
        auto poll = [&](const uint32_t* p, uint32_t& v, int sh) {
#pragma unroll 1
            for (int it = 0; !__all_sync(0xffffffffu, ((v ^ (epoch << sh)) >> sh) == 0u); it++) {
                if (it > SPIN_LIMIT) __trap();
                look(p, v);
            }
        };
        poll(&tp->x, sv, 24);
        int incl = (int)(sv & 0xfffu);
#pragma unroll
        for (int o = 1; o < 16; o <<= 1) {
            asm volatile("{\n\t.reg .pred P;\n\t.reg .b32 v;\n\tshfl.sync.up.b32 v|P, %0, %1, 0, 0xffffffff;\n\t@P add.u32 %0, %0, v;\n\t}"
                         : "+r"(incl) : "r"(o));
        }
        tot = __shfl_sync(0xffffffffu, incl, 15);
        const bool some = (sv & 0xfffu) != 0u;
        const uint32_t seg_b = sb + SEG_OFF + warp * 64;
        asm volatile("{\n\t.reg .pred P;\n\tsetp.ne.u32 P, %2, 0;\n\t@P st.shared.u32 [%0], %1;\n\t}"
                     ::"r"(seg_b + 4 * __popc(__ballot_sync(0xffffffffu, some) & ((1u << lane) - 1u))),
                       "r"((warp + NCOL * lane) * EPC_MAX + (int)((sv >> 12) & 0xfffu) - incl + (int)(sv & 0xfffu)), "r"((uint32_t)some) : "memory");
        __syncwarp();
        if (!some) incl = -1;
        const uint32_t le = (2u << lane) - 1u;
        uint32_t sg = seg_b;
#pragma unroll
        for (int r = 0; r < RND; r++) {
            uint32_t bit;
            asm("shl.b32 %0, 1, %1;" : "=r"(bit) : "r"(incl - 32 * r));
            const uint32_t ends = __reduce_or_sync(0xffffffffu, bit);
            gp[r] = g_staged + (lane + 32 * r + (int)lds32(sg + 4 * __popc(ends & le)));
            sg += 4 * __popc(ends);
            ent[r].y = tag;
        }
        const uint32_t ref = ms.ref;
        uint32_t ts = (epoch << 16) | (ref & 0xffffu);
        look(&tp->y, ts);
        poll(&tp->y, ts, 16);
#pragma unroll
        for (int r = 0; r < RND; r++)
            if (lane + 32 * r < tot) ent[r] = ld_entry(gp[r]);
        asm volatile("{\n\t.reg .pred P;\n\tsetp.ne.u32 P, %2, 0;\n\t@P red.shared.max.s32 [%0], %1;\n\t}"
                     ::"r"(sb + MISC_OFF + (uint32_t)offsetof(Misc, dmax)), "r"(__reduce_max_sync(0xffffffffu, (int)(short)(ts - ref))),
                       "r"(bytes) : "memory");
        uint32_t stale = 0;
#pragma unroll
        for (int r = 0; r < RND; r++) stale |= ent[r].y ^ tag;
        if (stale & TAGM) {
#pragma unroll
            for (int r = 0; r < RND; r++)
                if (lane + 32 * r < tot) ent[r] = wait_entry(gp[r], ent[r], tag);
        }
#pragma unroll
        for (int r = 0; r < RND0; r++) rk[r] = atoms_add(sb + BCNT_OFF + (ent[r].x >> 17), one);
        if (tot > 32 * RND0) {
#pragma unroll
            for (int r = RND0; r < RND; r++) rk[r] = atoms_add(sb + BCNT_OFF + (ent[r].x >> 17), one);
        }
    }
    __syncthreads();
    bool over = tot > 32 * RND || S > SFAST;
    {
        const int grp = warp & 3, u = warp >> 2;
        uint32_t v[3], incl[3], lo[3], hi[3], tt[3];
#pragma unroll
        for (int p = 0; p < 3; p++) {
            uint32_t a[3];
#pragma unroll
            for (int i = 0; i < 3; i++) {
                const uint2 w = bcnt[(4 * p + grp) * NB + 32 * i + lane];
                a[i] = w.x + (w.y << 16);
            }
            v[p] = u == 0 ? a[0] : (u == 1 ? a[1] : a[2]);
            incl[p] = v[p];
            lo[p] = __reduce_add_sync(0xffffffffu, u == 0 ? 0u : (u == 1 ? a[0] : a[0] + a[1]));
            tt[p] = __reduce_add_sync(0xffffffffu, a[0] + a[1] + a[2]);
        }
#pragma unroll
        for (int o = 1; o < 32; o <<= 1)
#pragma unroll
            for (int p = 0; p < 3; p++) {
                asm volatile("{\n\t.reg .pred P;\n\t.reg .b32 v;\n\tshfl.sync.up.b32 v|P, %0, %1, 0, 0xffffffff;\n\t@P add.u32 %0, %0, v;\n\t}"
                             : "+r"(incl[p]) : "r"(o));
            }
        uint32_t all = 0, nq = 0;
#pragma unroll
        for (int p = 0; p < 3; p++) {
            const uint32_t up = (tt[p] + 0x30003u) & 0xfffcfffcu, tb = (8 * p + 2 * grp) * KCAP * 0x10001u + (KCAP << 16);
            nq += up;
            incl[p] += lo[p] + up - tt[p] + tb;
            v[p] = incl[p] - v[p];
            *reinterpret_cast<uint32_t*>(smem + BCUM_OFF + ((4 * p + grp) * NB + 32 * u + lane) * 4) = v[p];
            lo[p] = warp < 4 && lane == 0 ? tb : (v[p] + 0x10001u) & 0xfffcfffcu;
            hi[p] = (incl[p] + 0x10001u) & 0xfffcfffcu;
            all += lo[p] - tb;
        }
        nq = ((nq & 0xffffu) + (nq >> 16)) >> 2;
        uint32_t run = (all & 0xffffu) + (all >> 16) + (nq & 1u) * 4u + grp * GCAP, rel[5];
#pragma unroll
        for (int i = 0; i < 5; i++) {
            const uint32_t l = (i & 1) ? lo[i >> 1] >> 16 : lo[i >> 1] & 0xffffu, h = (i & 1) ? hi[i >> 1] >> 16 : hi[i >> 1] & 0xffffu;
            rel[i] = run - l;
            asm volatile("{\n\t.reg .pred P;\n\tsetp.lt.u32 P, %0, %1;\n\t@P st.shared.u32 [%3], %2;\n\t@P st.shared.u32 [%4+-4], %2;\n\t}"
                         ::"r"(l), "r"(h), "r"(rel[i]), "r"(s0 + GI_OFF + l), "r"(s0 + GI_OFF + h) : "memory");
            run = rel[i] + h;
        }
        if ((((hi[0] - lo[0] + 0x40004u) | (hi[1] - lo[1] + 0x40004u) | (hi[2] - lo[2] + 4u)) & 0xfff0fff0u) != 0u) {
#pragma unroll
            for (int i = 0; i < 5; i++) {
                const uint32_t l = (i & 1) ? lo[i >> 1] >> 16 : lo[i >> 1] & 0xffffu, h = (i & 1) ? hi[i >> 1] >> 16 : hi[i >> 1] & 0xffffu;
#pragma unroll 1
                for (uint32_t j = l; j < h; j += 4) *reinterpret_cast<uint32_t*>(smem + GI_OFF + j) = rel[i];
            }
        }
        if (warp < 4 && lane == 0) ms.nq[grp] = (int)nq;
        over = over || 4 * nq + 20 > GCAP;
    }
    asm volatile("fence.proxy.async.shared::cta;" ::: "memory");
    const bool slow = __syncthreads_or(over);
    {
        auto put = [&](bool ok, uint32_t idx, uint32_t y, uint32_t e, uint32_t h0, uint32_t h1) {
            asm volatile("{\n\t.reg .pred P;\n\tsetp.ne.u32 P, %0, 0;\n\t@P st.shared.u32 [%1+%7], %3;\n\t@P st.shared.u32 [%1+%8], %4;\n\t"
                         "@P st.shared.v2.u32 [%2+%9], {%5,%6};\n\t}"
                         ::"r"((uint32_t)ok), "r"(s0 + 4 * idx), "r"(s0 + 8 * idx), "r"(y), "r"(e), "r"(h0), "r"(h1),
                           "n"(SY_OFF), "n"(SE_OFF), "n"(SH_OFF) : "memory");
        };
        auto lds16 = [&](uint32_t a) {
            uint32_t v;
            asm volatile("ld.shared.u16 %0, [%1];" : "=r"(v) : "r"(a) : "memory");
            return v;
        };
        auto find = [&](int r0, int r1) {
#pragma unroll
            for (int r = r0; r < r1; r++) rk[r] += lds16(s0 + BCUM_OFF + (ent[r].x >> 18));
#pragma unroll
            for (int r = r0; r < r1; r++) rk[r] += lds32(s0 + GI_OFF + (rk[r] & 0x7ffcu));
        };
        auto place = [&](int r0, int r1) {
#pragma unroll
            for (int r = r0; r < r1; r++) put(lane + 32 * r < tot, rk[r], ent[r].x & 0x1ffffu, ent[r].y, ent[r].z, ent[r].w);
        };
        find(0, RND0);
        if (uni(slow) != 0u) {
            slow_cta(smem, x, ef, w_rad, cg, w_mix, out, node0, Sc, tag);
            return;
        }
        if (warp == NCOL) {
            uint32_t c0[3], rel[3], nq[2];
#pragma unroll
            for (int k = 0; k < 3; k++) {
                const uint32_t tile = 8 * k + g;
                c0[k] = lds16(s0 + BCUM_OFF + (tile >> 1) * NB * 4 + (tile & 1) * 2);
                rel[k] = lds32(s0 + GI_OFF + tile * KCAP);
            }
#pragma unroll
            for (int k = 0; k < 2; k++) nq[k] = ms.nq[2 * k + (lane >> 4)];
            const uint32_t py = lane + 53 * c;
#pragma unroll
            for (int k = 0; k < 3; k++) {
                const uint32_t tile = 8 * k + g;
                put(t < (c0[k] & 3u), rel[k] + tile * KCAP + t, ((py + 32 * k) & 127u) * 8u, (2 * k + (g & 1)) << 27, 0u, 0u);
            }
#pragma unroll
            for (int k = 0; k < 2; k++) {
                const uint32_t i = lane & 15;
                put(i < 8 || (i < 12 && (nq[k] & 1)), (2 * k + (lane >> 4)) * GCAP + (i < 8 ? 4 * ((nq[k] + 1) & ~1u) + i : i - 8),
                    ((py + 96 + 4 * k) & 127u) * 8u, i < 8 ? 6u << 27 : 0u, 0u, 0u);
            }
        } else {
            place(0, RND0);
            if (tot > 32 * RND0) { find(RND0, RND); place(RND0, RND); }
        }
    }
    const uint32_t T0 = uni(tbase + ms.dmax * 63);
    int left = (int)uni((uint32_t)(ms.nq[pgrp] + 1) >> 1);
    __syncthreads();

    if (warp < 8) {
        asm volatile("setmaxnreg.inc.sync.aligned.u32 232;");
        const int half = warp >> 2, grp = (warp + half) & 3;
        const uint32_t az = __shfl_sync(0xffffffffu, sb + ZERO_OFF + (g >> 1) * 512 + t * 32 + (g & 1) * 16, lane);
        uint32_t sb2;
        asm volatile(
            "{\n"
            ".reg .f32 c<160>, h<16>, th<8>, fz;\n"
            ".reg .b32 x<16>, a<4>, r<4>, rd<8>, e<2>, p<80>, mt, xa, aa, an<4>, ab, ea, tmp, cnt, st, rl, rh, dum, du2;\n"
            ".reg .b16 lo, hi;\n"
            ".reg .pred pk, pm, pw, pe, pr, d0, d1, d2, d3, d4;\n"
            "mov.f32 fz, 0f00000000;\n"
            "mov.f32 c0, fz; mov.f32 c1, fz; mov.f32 c2, fz; mov.f32 c3, fz; mov.f32 c4, fz; mov.f32 c5, fz; mov.f32 c6, fz; mov.f32 c7, fz;\n"
            "mov.f32 c8, fz; mov.f32 c9, fz; mov.f32 c10, fz; mov.f32 c11, fz; mov.f32 c12, fz; mov.f32 c13, fz; mov.f32 c14, fz; mov.f32 c15, fz;\n"
            "mov.f32 c16, fz; mov.f32 c17, fz; mov.f32 c18, fz; mov.f32 c19, fz; mov.f32 c20, fz; mov.f32 c21, fz; mov.f32 c22, fz; mov.f32 c23, fz;\n"
            "mov.f32 c24, fz; mov.f32 c25, fz; mov.f32 c26, fz; mov.f32 c27, fz; mov.f32 c28, fz; mov.f32 c29, fz; mov.f32 c30, fz; mov.f32 c31, fz;\n"
            "mov.f32 c32, fz; mov.f32 c33, fz; mov.f32 c34, fz; mov.f32 c35, fz; mov.f32 c36, fz; mov.f32 c37, fz; mov.f32 c38, fz; mov.f32 c39, fz;\n"
            "mov.f32 c40, fz; mov.f32 c41, fz; mov.f32 c42, fz; mov.f32 c43, fz; mov.f32 c44, fz; mov.f32 c45, fz; mov.f32 c46, fz; mov.f32 c47, fz;\n"
            "mov.f32 c48, fz; mov.f32 c49, fz; mov.f32 c50, fz; mov.f32 c51, fz; mov.f32 c52, fz; mov.f32 c53, fz; mov.f32 c54, fz; mov.f32 c55, fz;\n"
            "mov.f32 c56, fz; mov.f32 c57, fz; mov.f32 c58, fz; mov.f32 c59, fz; mov.f32 c60, fz; mov.f32 c61, fz; mov.f32 c62, fz; mov.f32 c63, fz;\n"
            "mov.f32 c64, fz; mov.f32 c65, fz; mov.f32 c66, fz; mov.f32 c67, fz; mov.f32 c68, fz; mov.f32 c69, fz; mov.f32 c70, fz; mov.f32 c71, fz;\n"
            "mov.f32 c72, fz; mov.f32 c73, fz; mov.f32 c74, fz; mov.f32 c75, fz; mov.f32 c76, fz; mov.f32 c77, fz; mov.f32 c78, fz; mov.f32 c79, fz;\n"
            "mov.f32 c80, fz; mov.f32 c81, fz; mov.f32 c82, fz; mov.f32 c83, fz; mov.f32 c84, fz; mov.f32 c85, fz; mov.f32 c86, fz; mov.f32 c87, fz;\n"
            "mov.f32 c88, fz; mov.f32 c89, fz; mov.f32 c90, fz; mov.f32 c91, fz; mov.f32 c92, fz; mov.f32 c93, fz; mov.f32 c94, fz; mov.f32 c95, fz;\n"
            "mov.f32 c96, fz; mov.f32 c97, fz; mov.f32 c98, fz; mov.f32 c99, fz; mov.f32 c100, fz; mov.f32 c101, fz; mov.f32 c102, fz; mov.f32 c103, fz;\n"
            "mov.f32 c104, fz; mov.f32 c105, fz; mov.f32 c106, fz; mov.f32 c107, fz; mov.f32 c108, fz; mov.f32 c109, fz; mov.f32 c110, fz; mov.f32 c111, fz;\n"
            "mov.f32 c112, fz; mov.f32 c113, fz; mov.f32 c114, fz; mov.f32 c115, fz; mov.f32 c116, fz; mov.f32 c117, fz; mov.f32 c118, fz; mov.f32 c119, fz;\n"
            "mov.f32 c120, fz; mov.f32 c121, fz; mov.f32 c122, fz; mov.f32 c123, fz; mov.f32 c124, fz; mov.f32 c125, fz; mov.f32 c126, fz; mov.f32 c127, fz;\n"
            "mov.f32 c128, fz; mov.f32 c129, fz; mov.f32 c130, fz; mov.f32 c131, fz; mov.f32 c132, fz; mov.f32 c133, fz; mov.f32 c134, fz; mov.f32 c135, fz;\n"
            "mov.f32 c136, fz; mov.f32 c137, fz; mov.f32 c138, fz; mov.f32 c139, fz; mov.f32 c140, fz; mov.f32 c141, fz; mov.f32 c142, fz; mov.f32 c143, fz;\n"
            "mov.f32 c144, fz; mov.f32 c145, fz; mov.f32 c146, fz; mov.f32 c147, fz; mov.f32 c148, fz; mov.f32 c149, fz; mov.f32 c150, fz; mov.f32 c151, fz;\n"
            "mov.f32 c152, fz; mov.f32 c153, fz; mov.f32 c154, fz; mov.f32 c155, fz; mov.f32 c156, fz; mov.f32 c157, fz; mov.f32 c158, fz; mov.f32 c159, fz;\n"
            "mov.b32 x0, 0; mov.b32 x1, 0; mov.b32 x2, 0; mov.b32 x3, 0; mov.b32 x4, 0; mov.b32 x5, 0; mov.b32 x6, 0; mov.b32 x7, 0; mov.b32 x8, 0; mov.b32 x9, 0; mov.b32 x10, 0; mov.b32 x11, 0; mov.b32 x12, 0; mov.b32 x13, 0; mov.b32 x14, 0; mov.b32 x15, 0;\n"
            "mov.b32 a0, 0; mov.b32 a1, 0; mov.b32 a2, 0; mov.b32 a3, 0;\n"
            "elect.sync _|pe, 0xffffffff;\n"
            "mov.pred pr, pe;\n"
            "mov.b32 xa, %1; mov.b32 aa, %2; mov.b32 ea, %4;\n"
            "mov.u32 cnt, 0; and.b32 tmp, aa, 0xffffff80;\n"
            "S0L: mbarrier.try_wait.parity.shared::cta.b64 pw, [tmp+520], 0; @pw bra.uni S0D;\n"
            "add.u32 cnt, cnt, 1; setp.lt.u32 pk, cnt, 1000000; @pk bra.uni S0L; trap;\n"
            "S0D:\n"
            "ld.shared.v2.u32 {e0,e1}, [ea]; ld.shared.u32 mt, [aa+512];\n"
            "mma.sync.aligned.m16n8k16.row.col.f32.bf16.bf16.f32 {h0,h1,h2,h3}, {%7,%8,%9,%10}, {e0,e1}, {fz,fz,fz,fz};\n"
            "mma.sync.aligned.m16n8k16.row.col.f32.bf16.bf16.f32 {h4,h5,h6,h7}, {%11,%12,%13,%14}, {e0,e1}, {fz,fz,fz,fz};\n"
            "mma.sync.aligned.m16n8k16.row.col.f32.bf16.bf16.f32 {h8,h9,h10,h11}, {%15,%16,%17,%18}, {e0,e1}, {fz,fz,fz,fz};\n"
            "mma.sync.aligned.m16n8k16.row.col.f32.bf16.bf16.f32 {h12,h13,h14,h15}, {%19,%20,%21,%22}, {e0,e1}, {fz,fz,fz,fz};\n"
            "or.b32 a0, e0, mt; and.b32 a0, a0, %5;\n"
            "add.u32 xa, xa, 2048; add.u32 aa, aa, 2560; mov.u32 st, 1;\n"
            "mov.u32 cnt, 0; and.b32 tmp, aa, 0xffffff80;\n"
            "S1L: mbarrier.try_wait.parity.shared::cta.b64 pw, [tmp+520], 0; @pw bra.uni S1D;\n"
            "add.u32 cnt, cnt, 1; setp.lt.u32 pk, cnt, 1000000; @pk bra.uni S1L; trap;\n"
            "S1D:\n"
            "B0_0:\n"
            "xor.b32 tmp, mt, %3; and.b32 tmp, tmp, 1536; setp.eq.u32 pm, tmp, 0; selp.b32 ab, aa, %3, pm;\n"
            "and.b32 tmp, mt, 2048; setp.ne.u32 d0, tmp, 0; and.b32 tmp, mt, 4096; setp.ne.u32 d1, tmp, 0; and.b32 tmp, mt, 8192; setp.ne.u32 d2, tmp, 0;\n"
            "mad.lo.u32 cnt, a0, %5, ea; mad.lo.s32 ea, st, 2560, ea;\n"
            "ld.shared.u32 mt, [aa+512];\n"
            "mma.sync.aligned.m16n8k16.row.col.f32.bf16.bf16.f32 {c0,c1,c2,c3}, {a0,a1,a2,a3}, {x0,x1}, {c0,c1,c2,c3};\n"
            "mma.sync.aligned.m16n8k16.row.col.f32.bf16.bf16.f32 {c4,c5,c6,c7}, {a0,a1,a2,a3}, {x2,x3}, {c4,c5,c6,c7};\n"
            "ld.shared.v4.u32 {x0,x1,x2,x3}, [xa+0];\n"
            "tanh.approx.f32 th0, h0;\n"
            "tanh.approx.f32 th1, h2;\n"
            "fma.rn.f32 th0, h0, th0, h0;\n"
            "fma.rn.f32 th1, h2, th1, h2;\n"
            "cvt.rn.bf16x2.f32 r0, th1, th0;\n"
            "mma.sync.aligned.m16n8k16.row.col.f32.bf16.bf16.f32 {c8,c9,c10,c11}, {a0,a1,a2,a3}, {x4,x5}, {c8,c9,c10,c11};\n"
            "mma.sync.aligned.m16n8k16.row.col.f32.bf16.bf16.f32 {c12,c13,c14,c15}, {a0,a1,a2,a3}, {x6,x7}, {c12,c13,c14,c15};\n"
            "ld.shared.v4.u32 {x4,x5,x6,x7}, [xa+128];\n"
            "tanh.approx.f32 th2, h4;\n"
            "tanh.approx.f32 th3, h6;\n"
            "fma.rn.f32 th2, h4, th2, h4;\n"
            "fma.rn.f32 th3, h6, th3, h6;\n"
            "cvt.rn.bf16x2.f32 r1, th3, th2;\n"
            "mma.sync.aligned.m16n8k16.row.col.f32.bf16.bf16.f32 {c16,c17,c18,c19}, {a0,a1,a2,a3}, {x8,x9}, {c16,c17,c18,c19};\n"
            "mma.sync.aligned.m16n8k16.row.col.f32.bf16.bf16.f32 {c20,c21,c22,c23}, {a0,a1,a2,a3}, {x10,x11}, {c20,c21,c22,c23};\n"
            "ld.shared.v4.u32 {x8,x9,x10,x11}, [xa+512];\n"
            "tanh.approx.f32 th4, h8;\n"
            "tanh.approx.f32 th5, h10;\n"
            "fma.rn.f32 th4, h8, th4, h8;\n"
            "fma.rn.f32 th5, h10, th5, h10;\n"
            "cvt.rn.bf16x2.f32 r2, th5, th4;\n"
            "mma.sync.aligned.m16n8k16.row.col.f32.bf16.bf16.f32 {c24,c25,c26,c27}, {a0,a1,a2,a3}, {x12,x13}, {c24,c25,c26,c27};\n"
            "mma.sync.aligned.m16n8k16.row.col.f32.bf16.bf16.f32 {c28,c29,c30,c31}, {a0,a1,a2,a3}, {x14,x15}, {c28,c29,c30,c31};\n"
            "ld.shared.v4.u32 {x12,x13,x14,x15}, [xa+640];\n"
            "tanh.approx.f32 th6, h12;\n"
            "tanh.approx.f32 th7, h14;\n"
            "fma.rn.f32 th6, h12, th6, h12;\n"
            "fma.rn.f32 th7, h14, th7, h14;\n"
            "cvt.rn.bf16x2.f32 r3, th7, th6;\n"
            "ld.shared.v4.u32 {a0,a1,a2,a3}, [ab+0];\n"
            "@pe mbarrier.arrive.shared::cta.b64 _, [cnt+280];\n"
            "mov.b32 {lo,hi}, r0; mov.b32 rl, {lo,lo}; mov.b32 rh, {hi,hi};\n"
            "mul.bf16x2 x0, x0, rl; mul.bf16x2 x1, x1, rl; mul.bf16x2 x2, x2, rh; mul.bf16x2 x3, x3, rh;\n"
            "mov.b32 {lo,hi}, r1; mov.b32 rl, {lo,lo}; mov.b32 rh, {hi,hi};\n"
            "mul.bf16x2 x4, x4, rl; mul.bf16x2 x5, x5, rl; mul.bf16x2 x6, x6, rh; mul.bf16x2 x7, x7, rh;\n"
            "mov.b32 {lo,hi}, r2; mov.b32 rl, {lo,lo}; mov.b32 rh, {hi,hi};\n"
            "mul.bf16x2 x8, x8, rl; mul.bf16x2 x9, x9, rl; mul.bf16x2 x10, x10, rh; mul.bf16x2 x11, x11, rh;\n"
            "mov.b32 {lo,hi}, r3; mov.b32 rl, {lo,lo}; mov.b32 rh, {hi,hi};\n"
            "mul.bf16x2 x12, x12, rl; mul.bf16x2 x13, x13, rl; mul.bf16x2 x14, x14, rh; mul.bf16x2 x15, x15, rh;\n"
            "@d1 bra.uni L1; @d2 bra.uni B1_4; @d0 bra.uni B1_1; bra.uni B1_0;\n"
            "B0_1:\n"
            "xor.b32 tmp, mt, %3; and.b32 tmp, tmp, 1536; setp.eq.u32 pm, tmp, 0; selp.b32 ab, aa, %3, pm;\n"
            "and.b32 tmp, mt, 2048; setp.ne.u32 d0, tmp, 0; and.b32 tmp, mt, 4096; setp.ne.u32 d1, tmp, 0; and.b32 tmp, mt, 8192; setp.ne.u32 d2, tmp, 0;\n"
            "mad.lo.u32 cnt, a0, %5, ea; mad.lo.s32 ea, st, 2560, ea;\n"
            "ld.shared.u32 mt, [aa+512];\n"
            "mma.sync.aligned.m16n8k16.row.col.f32.bf16.bf16.f32 {c32,c33,c34,c35}, {a0,a1,a2,a3}, {x0,x1}, {c32,c33,c34,c35};\n"
            "mma.sync.aligned.m16n8k16.row.col.f32.bf16.bf16.f32 {c36,c37,c38,c39}, {a0,a1,a2,a3}, {x2,x3}, {c36,c37,c38,c39};\n"
            "ld.shared.v4.u32 {x0,x1,x2,x3}, [xa+0];\n"
            "tanh.approx.f32 th0, h0;\n"
            "tanh.approx.f32 th1, h2;\n"
            "fma.rn.f32 th0, h0, th0, h0;\n"
            "fma.rn.f32 th1, h2, th1, h2;\n"
            "cvt.rn.bf16x2.f32 r0, th1, th0;\n"
            "mma.sync.aligned.m16n8k16.row.col.f32.bf16.bf16.f32 {c40,c41,c42,c43}, {a0,a1,a2,a3}, {x4,x5}, {c40,c41,c42,c43};\n"
            "mma.sync.aligned.m16n8k16.row.col.f32.bf16.bf16.f32 {c44,c45,c46,c47}, {a0,a1,a2,a3}, {x6,x7}, {c44,c45,c46,c47};\n"
            "ld.shared.v4.u32 {x4,x5,x6,x7}, [xa+128];\n"
            "tanh.approx.f32 th2, h4;\n"
            "tanh.approx.f32 th3, h6;\n"
            "fma.rn.f32 th2, h4, th2, h4;\n"
            "fma.rn.f32 th3, h6, th3, h6;\n"
            "cvt.rn.bf16x2.f32 r1, th3, th2;\n"
            "mma.sync.aligned.m16n8k16.row.col.f32.bf16.bf16.f32 {c48,c49,c50,c51}, {a0,a1,a2,a3}, {x8,x9}, {c48,c49,c50,c51};\n"
            "mma.sync.aligned.m16n8k16.row.col.f32.bf16.bf16.f32 {c52,c53,c54,c55}, {a0,a1,a2,a3}, {x10,x11}, {c52,c53,c54,c55};\n"
            "ld.shared.v4.u32 {x8,x9,x10,x11}, [xa+512];\n"
            "tanh.approx.f32 th4, h8;\n"
            "tanh.approx.f32 th5, h10;\n"
            "fma.rn.f32 th4, h8, th4, h8;\n"
            "fma.rn.f32 th5, h10, th5, h10;\n"
            "cvt.rn.bf16x2.f32 r2, th5, th4;\n"
            "mma.sync.aligned.m16n8k16.row.col.f32.bf16.bf16.f32 {c56,c57,c58,c59}, {a0,a1,a2,a3}, {x12,x13}, {c56,c57,c58,c59};\n"
            "mma.sync.aligned.m16n8k16.row.col.f32.bf16.bf16.f32 {c60,c61,c62,c63}, {a0,a1,a2,a3}, {x14,x15}, {c60,c61,c62,c63};\n"
            "ld.shared.v4.u32 {x12,x13,x14,x15}, [xa+640];\n"
            "tanh.approx.f32 th6, h12;\n"
            "tanh.approx.f32 th7, h14;\n"
            "fma.rn.f32 th6, h12, th6, h12;\n"
            "fma.rn.f32 th7, h14, th7, h14;\n"
            "cvt.rn.bf16x2.f32 r3, th7, th6;\n"
            "ld.shared.v4.u32 {a0,a1,a2,a3}, [ab+0];\n"
            "@pe mbarrier.arrive.shared::cta.b64 _, [cnt+280];\n"
            "mov.b32 {lo,hi}, r0; mov.b32 rl, {lo,lo}; mov.b32 rh, {hi,hi};\n"
            "mul.bf16x2 x0, x0, rl; mul.bf16x2 x1, x1, rl; mul.bf16x2 x2, x2, rh; mul.bf16x2 x3, x3, rh;\n"
            "mov.b32 {lo,hi}, r1; mov.b32 rl, {lo,lo}; mov.b32 rh, {hi,hi};\n"
            "mul.bf16x2 x4, x4, rl; mul.bf16x2 x5, x5, rl; mul.bf16x2 x6, x6, rh; mul.bf16x2 x7, x7, rh;\n"
            "mov.b32 {lo,hi}, r2; mov.b32 rl, {lo,lo}; mov.b32 rh, {hi,hi};\n"
            "mul.bf16x2 x8, x8, rl; mul.bf16x2 x9, x9, rl; mul.bf16x2 x10, x10, rh; mul.bf16x2 x11, x11, rh;\n"
            "mov.b32 {lo,hi}, r3; mov.b32 rl, {lo,lo}; mov.b32 rh, {hi,hi};\n"
            "mul.bf16x2 x12, x12, rl; mul.bf16x2 x13, x13, rl; mul.bf16x2 x14, x14, rh; mul.bf16x2 x15, x15, rh;\n"
            "@d1 bra.uni L1; @d2 bra.uni B1_4; @d0 bra.uni B1_1; bra.uni B1_0;\n"
            "L0: @d0 bra.uni B0_3;\n"
            "B0_2:\n"
            "xor.b32 tmp, mt, %3; and.b32 tmp, tmp, 1536; setp.eq.u32 pm, tmp, 0; selp.b32 ab, aa, %3, pm;\n"
            "and.b32 tmp, mt, 2048; setp.ne.u32 d0, tmp, 0; and.b32 tmp, mt, 4096; setp.ne.u32 d1, tmp, 0; and.b32 tmp, mt, 8192; setp.ne.u32 d2, tmp, 0;\n"
            "mad.lo.u32 cnt, a0, %5, ea; mad.lo.s32 ea, st, 2560, ea;\n"
            "ld.shared.u32 mt, [aa+512];\n"
            "mma.sync.aligned.m16n8k16.row.col.f32.bf16.bf16.f32 {c64,c65,c66,c67}, {a0,a1,a2,a3}, {x0,x1}, {c64,c65,c66,c67};\n"
            "mma.sync.aligned.m16n8k16.row.col.f32.bf16.bf16.f32 {c68,c69,c70,c71}, {a0,a1,a2,a3}, {x2,x3}, {c68,c69,c70,c71};\n"
            "ld.shared.v4.u32 {x0,x1,x2,x3}, [xa+0];\n"
            "tanh.approx.f32 th0, h0;\n"
            "tanh.approx.f32 th1, h2;\n"
            "fma.rn.f32 th0, h0, th0, h0;\n"
            "fma.rn.f32 th1, h2, th1, h2;\n"
            "cvt.rn.bf16x2.f32 r0, th1, th0;\n"
            "mma.sync.aligned.m16n8k16.row.col.f32.bf16.bf16.f32 {c72,c73,c74,c75}, {a0,a1,a2,a3}, {x4,x5}, {c72,c73,c74,c75};\n"
            "mma.sync.aligned.m16n8k16.row.col.f32.bf16.bf16.f32 {c76,c77,c78,c79}, {a0,a1,a2,a3}, {x6,x7}, {c76,c77,c78,c79};\n"
            "ld.shared.v4.u32 {x4,x5,x6,x7}, [xa+128];\n"
            "tanh.approx.f32 th2, h4;\n"
            "tanh.approx.f32 th3, h6;\n"
            "fma.rn.f32 th2, h4, th2, h4;\n"
            "fma.rn.f32 th3, h6, th3, h6;\n"
            "cvt.rn.bf16x2.f32 r1, th3, th2;\n"
            "mma.sync.aligned.m16n8k16.row.col.f32.bf16.bf16.f32 {c80,c81,c82,c83}, {a0,a1,a2,a3}, {x8,x9}, {c80,c81,c82,c83};\n"
            "mma.sync.aligned.m16n8k16.row.col.f32.bf16.bf16.f32 {c84,c85,c86,c87}, {a0,a1,a2,a3}, {x10,x11}, {c84,c85,c86,c87};\n"
            "ld.shared.v4.u32 {x8,x9,x10,x11}, [xa+512];\n"
            "tanh.approx.f32 th4, h8;\n"
            "tanh.approx.f32 th5, h10;\n"
            "fma.rn.f32 th4, h8, th4, h8;\n"
            "fma.rn.f32 th5, h10, th5, h10;\n"
            "cvt.rn.bf16x2.f32 r2, th5, th4;\n"
            "mma.sync.aligned.m16n8k16.row.col.f32.bf16.bf16.f32 {c88,c89,c90,c91}, {a0,a1,a2,a3}, {x12,x13}, {c88,c89,c90,c91};\n"
            "mma.sync.aligned.m16n8k16.row.col.f32.bf16.bf16.f32 {c92,c93,c94,c95}, {a0,a1,a2,a3}, {x14,x15}, {c92,c93,c94,c95};\n"
            "ld.shared.v4.u32 {x12,x13,x14,x15}, [xa+640];\n"
            "tanh.approx.f32 th6, h12;\n"
            "tanh.approx.f32 th7, h14;\n"
            "fma.rn.f32 th6, h12, th6, h12;\n"
            "fma.rn.f32 th7, h14, th7, h14;\n"
            "cvt.rn.bf16x2.f32 r3, th7, th6;\n"
            "ld.shared.v4.u32 {a0,a1,a2,a3}, [ab+0];\n"
            "@pe mbarrier.arrive.shared::cta.b64 _, [cnt+280];\n"
            "mov.b32 {lo,hi}, r0; mov.b32 rl, {lo,lo}; mov.b32 rh, {hi,hi};\n"
            "mul.bf16x2 x0, x0, rl; mul.bf16x2 x1, x1, rl; mul.bf16x2 x2, x2, rh; mul.bf16x2 x3, x3, rh;\n"
            "mov.b32 {lo,hi}, r1; mov.b32 rl, {lo,lo}; mov.b32 rh, {hi,hi};\n"
            "mul.bf16x2 x4, x4, rl; mul.bf16x2 x5, x5, rl; mul.bf16x2 x6, x6, rh; mul.bf16x2 x7, x7, rh;\n"
            "mov.b32 {lo,hi}, r2; mov.b32 rl, {lo,lo}; mov.b32 rh, {hi,hi};\n"
            "mul.bf16x2 x8, x8, rl; mul.bf16x2 x9, x9, rl; mul.bf16x2 x10, x10, rh; mul.bf16x2 x11, x11, rh;\n"
            "mov.b32 {lo,hi}, r3; mov.b32 rl, {lo,lo}; mov.b32 rh, {hi,hi};\n"
            "mul.bf16x2 x12, x12, rl; mul.bf16x2 x13, x13, rl; mul.bf16x2 x14, x14, rh; mul.bf16x2 x15, x15, rh;\n"
            "@d1 bra.uni L1; @d2 bra.uni B1_4; @d0 bra.uni B1_1; bra.uni B1_0;\n"
            "B0_3:\n"
            "xor.b32 tmp, mt, %3; and.b32 tmp, tmp, 1536; setp.eq.u32 pm, tmp, 0; selp.b32 ab, aa, %3, pm;\n"
            "and.b32 tmp, mt, 2048; setp.ne.u32 d0, tmp, 0; and.b32 tmp, mt, 4096; setp.ne.u32 d1, tmp, 0; and.b32 tmp, mt, 8192; setp.ne.u32 d2, tmp, 0;\n"
            "mad.lo.u32 cnt, a0, %5, ea; mad.lo.s32 ea, st, 2560, ea;\n"
            "ld.shared.u32 mt, [aa+512];\n"
            "mma.sync.aligned.m16n8k16.row.col.f32.bf16.bf16.f32 {c96,c97,c98,c99}, {a0,a1,a2,a3}, {x0,x1}, {c96,c97,c98,c99};\n"
            "mma.sync.aligned.m16n8k16.row.col.f32.bf16.bf16.f32 {c100,c101,c102,c103}, {a0,a1,a2,a3}, {x2,x3}, {c100,c101,c102,c103};\n"
            "ld.shared.v4.u32 {x0,x1,x2,x3}, [xa+0];\n"
            "tanh.approx.f32 th0, h0;\n"
            "tanh.approx.f32 th1, h2;\n"
            "fma.rn.f32 th0, h0, th0, h0;\n"
            "fma.rn.f32 th1, h2, th1, h2;\n"
            "cvt.rn.bf16x2.f32 r0, th1, th0;\n"
            "mma.sync.aligned.m16n8k16.row.col.f32.bf16.bf16.f32 {c104,c105,c106,c107}, {a0,a1,a2,a3}, {x4,x5}, {c104,c105,c106,c107};\n"
            "mma.sync.aligned.m16n8k16.row.col.f32.bf16.bf16.f32 {c108,c109,c110,c111}, {a0,a1,a2,a3}, {x6,x7}, {c108,c109,c110,c111};\n"
            "ld.shared.v4.u32 {x4,x5,x6,x7}, [xa+128];\n"
            "tanh.approx.f32 th2, h4;\n"
            "tanh.approx.f32 th3, h6;\n"
            "fma.rn.f32 th2, h4, th2, h4;\n"
            "fma.rn.f32 th3, h6, th3, h6;\n"
            "cvt.rn.bf16x2.f32 r1, th3, th2;\n"
            "mma.sync.aligned.m16n8k16.row.col.f32.bf16.bf16.f32 {c112,c113,c114,c115}, {a0,a1,a2,a3}, {x8,x9}, {c112,c113,c114,c115};\n"
            "mma.sync.aligned.m16n8k16.row.col.f32.bf16.bf16.f32 {c116,c117,c118,c119}, {a0,a1,a2,a3}, {x10,x11}, {c116,c117,c118,c119};\n"
            "ld.shared.v4.u32 {x8,x9,x10,x11}, [xa+512];\n"
            "tanh.approx.f32 th4, h8;\n"
            "tanh.approx.f32 th5, h10;\n"
            "fma.rn.f32 th4, h8, th4, h8;\n"
            "fma.rn.f32 th5, h10, th5, h10;\n"
            "cvt.rn.bf16x2.f32 r2, th5, th4;\n"
            "mma.sync.aligned.m16n8k16.row.col.f32.bf16.bf16.f32 {c120,c121,c122,c123}, {a0,a1,a2,a3}, {x12,x13}, {c120,c121,c122,c123};\n"
            "mma.sync.aligned.m16n8k16.row.col.f32.bf16.bf16.f32 {c124,c125,c126,c127}, {a0,a1,a2,a3}, {x14,x15}, {c124,c125,c126,c127};\n"
            "ld.shared.v4.u32 {x12,x13,x14,x15}, [xa+640];\n"
            "tanh.approx.f32 th6, h12;\n"
            "tanh.approx.f32 th7, h14;\n"
            "fma.rn.f32 th6, h12, th6, h12;\n"
            "fma.rn.f32 th7, h14, th7, h14;\n"
            "cvt.rn.bf16x2.f32 r3, th7, th6;\n"
            "ld.shared.v4.u32 {a0,a1,a2,a3}, [ab+0];\n"
            "@pe mbarrier.arrive.shared::cta.b64 _, [cnt+280];\n"
            "mov.b32 {lo,hi}, r0; mov.b32 rl, {lo,lo}; mov.b32 rh, {hi,hi};\n"
            "mul.bf16x2 x0, x0, rl; mul.bf16x2 x1, x1, rl; mul.bf16x2 x2, x2, rh; mul.bf16x2 x3, x3, rh;\n"
            "mov.b32 {lo,hi}, r1; mov.b32 rl, {lo,lo}; mov.b32 rh, {hi,hi};\n"
            "mul.bf16x2 x4, x4, rl; mul.bf16x2 x5, x5, rl; mul.bf16x2 x6, x6, rh; mul.bf16x2 x7, x7, rh;\n"
            "mov.b32 {lo,hi}, r2; mov.b32 rl, {lo,lo}; mov.b32 rh, {hi,hi};\n"
            "mul.bf16x2 x8, x8, rl; mul.bf16x2 x9, x9, rl; mul.bf16x2 x10, x10, rh; mul.bf16x2 x11, x11, rh;\n"
            "mov.b32 {lo,hi}, r3; mov.b32 rl, {lo,lo}; mov.b32 rh, {hi,hi};\n"
            "mul.bf16x2 x12, x12, rl; mul.bf16x2 x13, x13, rl; mul.bf16x2 x14, x14, rh; mul.bf16x2 x15, x15, rh;\n"
            "@d1 bra.uni L1; @d2 bra.uni B1_4; @d0 bra.uni B1_1; bra.uni B1_0;\n"
            "B0_4:\n"
            "xor.b32 tmp, mt, %3; and.b32 tmp, tmp, 1536; setp.eq.u32 pm, tmp, 0; selp.b32 ab, aa, %3, pm;\n"
            "and.b32 tmp, mt, 2048; setp.ne.u32 d0, tmp, 0; and.b32 tmp, mt, 4096; setp.ne.u32 d1, tmp, 0; and.b32 tmp, mt, 8192; setp.ne.u32 d2, tmp, 0;\n"
            "mad.lo.u32 cnt, a0, %5, ea; mad.lo.s32 ea, st, 2560, ea;\n"
            "ld.shared.u32 mt, [aa+512];\n"
            "mma.sync.aligned.m16n8k16.row.col.f32.bf16.bf16.f32 {c128,c129,c130,c131}, {a0,a1,a2,a3}, {x0,x1}, {c128,c129,c130,c131};\n"
            "mma.sync.aligned.m16n8k16.row.col.f32.bf16.bf16.f32 {c132,c133,c134,c135}, {a0,a1,a2,a3}, {x2,x3}, {c132,c133,c134,c135};\n"
            "ld.shared.v4.u32 {x0,x1,x2,x3}, [xa+0];\n"
            "tanh.approx.f32 th0, h0;\n"
            "tanh.approx.f32 th1, h2;\n"
            "fma.rn.f32 th0, h0, th0, h0;\n"
            "fma.rn.f32 th1, h2, th1, h2;\n"
            "cvt.rn.bf16x2.f32 r0, th1, th0;\n"
            "mma.sync.aligned.m16n8k16.row.col.f32.bf16.bf16.f32 {c136,c137,c138,c139}, {a0,a1,a2,a3}, {x4,x5}, {c136,c137,c138,c139};\n"
            "mma.sync.aligned.m16n8k16.row.col.f32.bf16.bf16.f32 {c140,c141,c142,c143}, {a0,a1,a2,a3}, {x6,x7}, {c140,c141,c142,c143};\n"
            "ld.shared.v4.u32 {x4,x5,x6,x7}, [xa+128];\n"
            "tanh.approx.f32 th2, h4;\n"
            "tanh.approx.f32 th3, h6;\n"
            "fma.rn.f32 th2, h4, th2, h4;\n"
            "fma.rn.f32 th3, h6, th3, h6;\n"
            "cvt.rn.bf16x2.f32 r1, th3, th2;\n"
            "mma.sync.aligned.m16n8k16.row.col.f32.bf16.bf16.f32 {c144,c145,c146,c147}, {a0,a1,a2,a3}, {x8,x9}, {c144,c145,c146,c147};\n"
            "mma.sync.aligned.m16n8k16.row.col.f32.bf16.bf16.f32 {c148,c149,c150,c151}, {a0,a1,a2,a3}, {x10,x11}, {c148,c149,c150,c151};\n"
            "ld.shared.v4.u32 {x8,x9,x10,x11}, [xa+512];\n"
            "tanh.approx.f32 th4, h8;\n"
            "tanh.approx.f32 th5, h10;\n"
            "fma.rn.f32 th4, h8, th4, h8;\n"
            "fma.rn.f32 th5, h10, th5, h10;\n"
            "cvt.rn.bf16x2.f32 r2, th5, th4;\n"
            "mma.sync.aligned.m16n8k16.row.col.f32.bf16.bf16.f32 {c152,c153,c154,c155}, {a0,a1,a2,a3}, {x12,x13}, {c152,c153,c154,c155};\n"
            "mma.sync.aligned.m16n8k16.row.col.f32.bf16.bf16.f32 {c156,c157,c158,c159}, {a0,a1,a2,a3}, {x14,x15}, {c156,c157,c158,c159};\n"
            "ld.shared.v4.u32 {x12,x13,x14,x15}, [xa+640];\n"
            "tanh.approx.f32 th6, h12;\n"
            "tanh.approx.f32 th7, h14;\n"
            "fma.rn.f32 th6, h12, th6, h12;\n"
            "fma.rn.f32 th7, h14, th7, h14;\n"
            "cvt.rn.bf16x2.f32 r3, th7, th6;\n"
            "ld.shared.v4.u32 {a0,a1,a2,a3}, [ab+0];\n"
            "@pe mbarrier.arrive.shared::cta.b64 _, [cnt+280];\n"
            "mov.b32 {lo,hi}, r0; mov.b32 rl, {lo,lo}; mov.b32 rh, {hi,hi};\n"
            "mul.bf16x2 x0, x0, rl; mul.bf16x2 x1, x1, rl; mul.bf16x2 x2, x2, rh; mul.bf16x2 x3, x3, rh;\n"
            "mov.b32 {lo,hi}, r1; mov.b32 rl, {lo,lo}; mov.b32 rh, {hi,hi};\n"
            "mul.bf16x2 x4, x4, rl; mul.bf16x2 x5, x5, rl; mul.bf16x2 x6, x6, rh; mul.bf16x2 x7, x7, rh;\n"
            "mov.b32 {lo,hi}, r2; mov.b32 rl, {lo,lo}; mov.b32 rh, {hi,hi};\n"
            "mul.bf16x2 x8, x8, rl; mul.bf16x2 x9, x9, rl; mul.bf16x2 x10, x10, rh; mul.bf16x2 x11, x11, rh;\n"
            "mov.b32 {lo,hi}, r3; mov.b32 rl, {lo,lo}; mov.b32 rh, {hi,hi};\n"
            "mul.bf16x2 x12, x12, rl; mul.bf16x2 x13, x13, rl; mul.bf16x2 x14, x14, rh; mul.bf16x2 x15, x15, rh;\n"
            "@d1 bra.uni L1; @d2 bra.uni B1_4; @d0 bra.uni B1_1; bra.uni B1_0;\n"
            "B1_0:\n"
            "xor.b32 tmp, mt, ea; and.b32 tmp, tmp, 192; setp.eq.u32 pm, tmp, 0; selp.b32 ab, aa, %3, pm;\n"
            "and.b32 tmp, mt, 8; setp.ne.u32 d0, tmp, 0; and.b32 tmp, mt, 16; setp.ne.u32 d1, tmp, 0; and.b32 tmp, mt, 32; setp.ne.u32 d2, tmp, 0;\n"
            "ld.shared.v2.u32 {e0,e1}, [ea];\n"
            "shr.s32 st, mt, 24; mad.lo.s32 aa, st, 2560, aa;\n"
            "mma.sync.aligned.m16n8k16.row.col.f32.bf16.bf16.f32 {c0,c1,c2,c3}, {a0,a1,a2,a3}, {x0,x1}, {c0,c1,c2,c3};\n"
            "mma.sync.aligned.m16n8k16.row.col.f32.bf16.bf16.f32 {c4,c5,c6,c7}, {a0,a1,a2,a3}, {x2,x3}, {c4,c5,c6,c7};\n"
            "ld.shared.v4.u32 {x0,x1,x2,x3}, [xa+1024];\n"
            "tanh.approx.f32 th0, h1;\n"
            "tanh.approx.f32 th1, h3;\n"
            "fma.rn.f32 th0, h1, th0, h1;\n"
            "fma.rn.f32 th1, h3, th1, h3;\n"
            "cvt.rn.bf16x2.f32 r0, th1, th0;\n"
            "mma.sync.aligned.m16n8k16.row.col.f32.bf16.bf16.f32 {h0,h1,h2,h3}, {%7,%8,%9,%10}, {e0,e1}, {fz,fz,fz,fz};\n"
            "mma.sync.aligned.m16n8k16.row.col.f32.bf16.bf16.f32 {c8,c9,c10,c11}, {a0,a1,a2,a3}, {x4,x5}, {c8,c9,c10,c11};\n"
            "mma.sync.aligned.m16n8k16.row.col.f32.bf16.bf16.f32 {c12,c13,c14,c15}, {a0,a1,a2,a3}, {x6,x7}, {c12,c13,c14,c15};\n"
            "ld.shared.v4.u32 {x4,x5,x6,x7}, [xa+1152];\n"
            "tanh.approx.f32 th2, h5;\n"
            "tanh.approx.f32 th3, h7;\n"
            "fma.rn.f32 th2, h5, th2, h5;\n"
            "fma.rn.f32 th3, h7, th3, h7;\n"
            "cvt.rn.bf16x2.f32 r1, th3, th2;\n"
            "mma.sync.aligned.m16n8k16.row.col.f32.bf16.bf16.f32 {h4,h5,h6,h7}, {%11,%12,%13,%14}, {e0,e1}, {fz,fz,fz,fz};\n"
            "mma.sync.aligned.m16n8k16.row.col.f32.bf16.bf16.f32 {c16,c17,c18,c19}, {a0,a1,a2,a3}, {x8,x9}, {c16,c17,c18,c19};\n"
            "mma.sync.aligned.m16n8k16.row.col.f32.bf16.bf16.f32 {c20,c21,c22,c23}, {a0,a1,a2,a3}, {x10,x11}, {c20,c21,c22,c23};\n"
            "ld.shared.v4.u32 {x8,x9,x10,x11}, [xa+1536];\n"
            "tanh.approx.f32 th4, h9;\n"
            "tanh.approx.f32 th5, h11;\n"
            "fma.rn.f32 th4, h9, th4, h9;\n"
            "fma.rn.f32 th5, h11, th5, h11;\n"
            "cvt.rn.bf16x2.f32 r2, th5, th4;\n"
            "mma.sync.aligned.m16n8k16.row.col.f32.bf16.bf16.f32 {h8,h9,h10,h11}, {%15,%16,%17,%18}, {e0,e1}, {fz,fz,fz,fz};\n"
            "mma.sync.aligned.m16n8k16.row.col.f32.bf16.bf16.f32 {c24,c25,c26,c27}, {a0,a1,a2,a3}, {x12,x13}, {c24,c25,c26,c27};\n"
            "mma.sync.aligned.m16n8k16.row.col.f32.bf16.bf16.f32 {c28,c29,c30,c31}, {a0,a1,a2,a3}, {x14,x15}, {c28,c29,c30,c31};\n"
            "ld.shared.v4.u32 {x12,x13,x14,x15}, [xa+1664];\n"
            "tanh.approx.f32 th6, h13;\n"
            "tanh.approx.f32 th7, h15;\n"
            "fma.rn.f32 th6, h13, th6, h13;\n"
            "fma.rn.f32 th7, h15, th7, h15;\n"
            "cvt.rn.bf16x2.f32 r3, th7, th6;\n"
            "mma.sync.aligned.m16n8k16.row.col.f32.bf16.bf16.f32 {h12,h13,h14,h15}, {%19,%20,%21,%22}, {e0,e1}, {fz,fz,fz,fz};\n"
            "ld.shared.v4.u32 {a0,a1,a2,a3}, [ab+128];\n"
            "and.b32 tmp, aa, 0xffffff80; mbarrier.test_wait.parity.shared::cta.b64 pw, [tmp+520], mt;\n"
            "mad.lo.s32 xa, st, 2048, xa;\n"
            "mov.b32 {lo,hi}, r0; mov.b32 rl, {lo,lo}; mov.b32 rh, {hi,hi};\n"
            "mul.bf16x2 x0, x0, rl; mul.bf16x2 x1, x1, rl; mul.bf16x2 x2, x2, rh; mul.bf16x2 x3, x3, rh;\n"
            "mov.b32 {lo,hi}, r1; mov.b32 rl, {lo,lo}; mov.b32 rh, {hi,hi};\n"
            "mul.bf16x2 x4, x4, rl; mul.bf16x2 x5, x5, rl; mul.bf16x2 x6, x6, rh; mul.bf16x2 x7, x7, rh;\n"
            "mov.b32 {lo,hi}, r2; mov.b32 rl, {lo,lo}; mov.b32 rh, {hi,hi};\n"
            "mul.bf16x2 x8, x8, rl; mul.bf16x2 x9, x9, rl; mul.bf16x2 x10, x10, rh; mul.bf16x2 x11, x11, rh;\n"
            "mov.b32 {lo,hi}, r3; mov.b32 rl, {lo,lo}; mov.b32 rh, {hi,hi};\n"
            "mul.bf16x2 x12, x12, rl; mul.bf16x2 x13, x13, rl; mul.bf16x2 x14, x14, rh; mul.bf16x2 x15, x15, rh;\n"
            "@!pw bra.uni W1;\n"
            "@d2 bra.uni B0_4; @d1 bra.uni L0; @d0 bra.uni B0_1; bra.uni B0_0;\n"
            "B1_1:\n"
            "xor.b32 tmp, mt, ea; and.b32 tmp, tmp, 192; setp.eq.u32 pm, tmp, 0; selp.b32 ab, aa, %3, pm;\n"
            "and.b32 tmp, mt, 8; setp.ne.u32 d0, tmp, 0; and.b32 tmp, mt, 16; setp.ne.u32 d1, tmp, 0; and.b32 tmp, mt, 32; setp.ne.u32 d2, tmp, 0;\n"
            "ld.shared.v2.u32 {e0,e1}, [ea];\n"
            "shr.s32 st, mt, 24; mad.lo.s32 aa, st, 2560, aa;\n"
            "mma.sync.aligned.m16n8k16.row.col.f32.bf16.bf16.f32 {c32,c33,c34,c35}, {a0,a1,a2,a3}, {x0,x1}, {c32,c33,c34,c35};\n"
            "mma.sync.aligned.m16n8k16.row.col.f32.bf16.bf16.f32 {c36,c37,c38,c39}, {a0,a1,a2,a3}, {x2,x3}, {c36,c37,c38,c39};\n"
            "ld.shared.v4.u32 {x0,x1,x2,x3}, [xa+1024];\n"
            "tanh.approx.f32 th0, h1;\n"
            "tanh.approx.f32 th1, h3;\n"
            "fma.rn.f32 th0, h1, th0, h1;\n"
            "fma.rn.f32 th1, h3, th1, h3;\n"
            "cvt.rn.bf16x2.f32 r0, th1, th0;\n"
            "mma.sync.aligned.m16n8k16.row.col.f32.bf16.bf16.f32 {h0,h1,h2,h3}, {%7,%8,%9,%10}, {e0,e1}, {fz,fz,fz,fz};\n"
            "mma.sync.aligned.m16n8k16.row.col.f32.bf16.bf16.f32 {c40,c41,c42,c43}, {a0,a1,a2,a3}, {x4,x5}, {c40,c41,c42,c43};\n"
            "mma.sync.aligned.m16n8k16.row.col.f32.bf16.bf16.f32 {c44,c45,c46,c47}, {a0,a1,a2,a3}, {x6,x7}, {c44,c45,c46,c47};\n"
            "ld.shared.v4.u32 {x4,x5,x6,x7}, [xa+1152];\n"
            "tanh.approx.f32 th2, h5;\n"
            "tanh.approx.f32 th3, h7;\n"
            "fma.rn.f32 th2, h5, th2, h5;\n"
            "fma.rn.f32 th3, h7, th3, h7;\n"
            "cvt.rn.bf16x2.f32 r1, th3, th2;\n"
            "mma.sync.aligned.m16n8k16.row.col.f32.bf16.bf16.f32 {h4,h5,h6,h7}, {%11,%12,%13,%14}, {e0,e1}, {fz,fz,fz,fz};\n"
            "mma.sync.aligned.m16n8k16.row.col.f32.bf16.bf16.f32 {c48,c49,c50,c51}, {a0,a1,a2,a3}, {x8,x9}, {c48,c49,c50,c51};\n"
            "mma.sync.aligned.m16n8k16.row.col.f32.bf16.bf16.f32 {c52,c53,c54,c55}, {a0,a1,a2,a3}, {x10,x11}, {c52,c53,c54,c55};\n"
            "ld.shared.v4.u32 {x8,x9,x10,x11}, [xa+1536];\n"
            "tanh.approx.f32 th4, h9;\n"
            "tanh.approx.f32 th5, h11;\n"
            "fma.rn.f32 th4, h9, th4, h9;\n"
            "fma.rn.f32 th5, h11, th5, h11;\n"
            "cvt.rn.bf16x2.f32 r2, th5, th4;\n"
            "mma.sync.aligned.m16n8k16.row.col.f32.bf16.bf16.f32 {h8,h9,h10,h11}, {%15,%16,%17,%18}, {e0,e1}, {fz,fz,fz,fz};\n"
            "mma.sync.aligned.m16n8k16.row.col.f32.bf16.bf16.f32 {c56,c57,c58,c59}, {a0,a1,a2,a3}, {x12,x13}, {c56,c57,c58,c59};\n"
            "mma.sync.aligned.m16n8k16.row.col.f32.bf16.bf16.f32 {c60,c61,c62,c63}, {a0,a1,a2,a3}, {x14,x15}, {c60,c61,c62,c63};\n"
            "ld.shared.v4.u32 {x12,x13,x14,x15}, [xa+1664];\n"
            "tanh.approx.f32 th6, h13;\n"
            "tanh.approx.f32 th7, h15;\n"
            "fma.rn.f32 th6, h13, th6, h13;\n"
            "fma.rn.f32 th7, h15, th7, h15;\n"
            "cvt.rn.bf16x2.f32 r3, th7, th6;\n"
            "mma.sync.aligned.m16n8k16.row.col.f32.bf16.bf16.f32 {h12,h13,h14,h15}, {%19,%20,%21,%22}, {e0,e1}, {fz,fz,fz,fz};\n"
            "ld.shared.v4.u32 {a0,a1,a2,a3}, [ab+128];\n"
            "and.b32 tmp, aa, 0xffffff80; mbarrier.test_wait.parity.shared::cta.b64 pw, [tmp+520], mt;\n"
            "mad.lo.s32 xa, st, 2048, xa;\n"
            "mov.b32 {lo,hi}, r0; mov.b32 rl, {lo,lo}; mov.b32 rh, {hi,hi};\n"
            "mul.bf16x2 x0, x0, rl; mul.bf16x2 x1, x1, rl; mul.bf16x2 x2, x2, rh; mul.bf16x2 x3, x3, rh;\n"
            "mov.b32 {lo,hi}, r1; mov.b32 rl, {lo,lo}; mov.b32 rh, {hi,hi};\n"
            "mul.bf16x2 x4, x4, rl; mul.bf16x2 x5, x5, rl; mul.bf16x2 x6, x6, rh; mul.bf16x2 x7, x7, rh;\n"
            "mov.b32 {lo,hi}, r2; mov.b32 rl, {lo,lo}; mov.b32 rh, {hi,hi};\n"
            "mul.bf16x2 x8, x8, rl; mul.bf16x2 x9, x9, rl; mul.bf16x2 x10, x10, rh; mul.bf16x2 x11, x11, rh;\n"
            "mov.b32 {lo,hi}, r3; mov.b32 rl, {lo,lo}; mov.b32 rh, {hi,hi};\n"
            "mul.bf16x2 x12, x12, rl; mul.bf16x2 x13, x13, rl; mul.bf16x2 x14, x14, rh; mul.bf16x2 x15, x15, rh;\n"
            "@!pw bra.uni W1;\n"
            "@d2 bra.uni B0_4; @d1 bra.uni L0; @d0 bra.uni B0_1; bra.uni B0_0;\n"
            "L1: @d2 bra.uni END; @d0 bra.uni B1_3;\n"
            "B1_2:\n"
            "xor.b32 tmp, mt, ea; and.b32 tmp, tmp, 192; setp.eq.u32 pm, tmp, 0; selp.b32 ab, aa, %3, pm;\n"
            "and.b32 tmp, mt, 8; setp.ne.u32 d0, tmp, 0; and.b32 tmp, mt, 16; setp.ne.u32 d1, tmp, 0; and.b32 tmp, mt, 32; setp.ne.u32 d2, tmp, 0;\n"
            "ld.shared.v2.u32 {e0,e1}, [ea];\n"
            "shr.s32 st, mt, 24; mad.lo.s32 aa, st, 2560, aa;\n"
            "mma.sync.aligned.m16n8k16.row.col.f32.bf16.bf16.f32 {c64,c65,c66,c67}, {a0,a1,a2,a3}, {x0,x1}, {c64,c65,c66,c67};\n"
            "mma.sync.aligned.m16n8k16.row.col.f32.bf16.bf16.f32 {c68,c69,c70,c71}, {a0,a1,a2,a3}, {x2,x3}, {c68,c69,c70,c71};\n"
            "ld.shared.v4.u32 {x0,x1,x2,x3}, [xa+1024];\n"
            "tanh.approx.f32 th0, h1;\n"
            "tanh.approx.f32 th1, h3;\n"
            "fma.rn.f32 th0, h1, th0, h1;\n"
            "fma.rn.f32 th1, h3, th1, h3;\n"
            "cvt.rn.bf16x2.f32 r0, th1, th0;\n"
            "mma.sync.aligned.m16n8k16.row.col.f32.bf16.bf16.f32 {h0,h1,h2,h3}, {%7,%8,%9,%10}, {e0,e1}, {fz,fz,fz,fz};\n"
            "mma.sync.aligned.m16n8k16.row.col.f32.bf16.bf16.f32 {c72,c73,c74,c75}, {a0,a1,a2,a3}, {x4,x5}, {c72,c73,c74,c75};\n"
            "mma.sync.aligned.m16n8k16.row.col.f32.bf16.bf16.f32 {c76,c77,c78,c79}, {a0,a1,a2,a3}, {x6,x7}, {c76,c77,c78,c79};\n"
            "ld.shared.v4.u32 {x4,x5,x6,x7}, [xa+1152];\n"
            "tanh.approx.f32 th2, h5;\n"
            "tanh.approx.f32 th3, h7;\n"
            "fma.rn.f32 th2, h5, th2, h5;\n"
            "fma.rn.f32 th3, h7, th3, h7;\n"
            "cvt.rn.bf16x2.f32 r1, th3, th2;\n"
            "mma.sync.aligned.m16n8k16.row.col.f32.bf16.bf16.f32 {h4,h5,h6,h7}, {%11,%12,%13,%14}, {e0,e1}, {fz,fz,fz,fz};\n"
            "mma.sync.aligned.m16n8k16.row.col.f32.bf16.bf16.f32 {c80,c81,c82,c83}, {a0,a1,a2,a3}, {x8,x9}, {c80,c81,c82,c83};\n"
            "mma.sync.aligned.m16n8k16.row.col.f32.bf16.bf16.f32 {c84,c85,c86,c87}, {a0,a1,a2,a3}, {x10,x11}, {c84,c85,c86,c87};\n"
            "ld.shared.v4.u32 {x8,x9,x10,x11}, [xa+1536];\n"
            "tanh.approx.f32 th4, h9;\n"
            "tanh.approx.f32 th5, h11;\n"
            "fma.rn.f32 th4, h9, th4, h9;\n"
            "fma.rn.f32 th5, h11, th5, h11;\n"
            "cvt.rn.bf16x2.f32 r2, th5, th4;\n"
            "mma.sync.aligned.m16n8k16.row.col.f32.bf16.bf16.f32 {h8,h9,h10,h11}, {%15,%16,%17,%18}, {e0,e1}, {fz,fz,fz,fz};\n"
            "mma.sync.aligned.m16n8k16.row.col.f32.bf16.bf16.f32 {c88,c89,c90,c91}, {a0,a1,a2,a3}, {x12,x13}, {c88,c89,c90,c91};\n"
            "mma.sync.aligned.m16n8k16.row.col.f32.bf16.bf16.f32 {c92,c93,c94,c95}, {a0,a1,a2,a3}, {x14,x15}, {c92,c93,c94,c95};\n"
            "ld.shared.v4.u32 {x12,x13,x14,x15}, [xa+1664];\n"
            "tanh.approx.f32 th6, h13;\n"
            "tanh.approx.f32 th7, h15;\n"
            "fma.rn.f32 th6, h13, th6, h13;\n"
            "fma.rn.f32 th7, h15, th7, h15;\n"
            "cvt.rn.bf16x2.f32 r3, th7, th6;\n"
            "mma.sync.aligned.m16n8k16.row.col.f32.bf16.bf16.f32 {h12,h13,h14,h15}, {%19,%20,%21,%22}, {e0,e1}, {fz,fz,fz,fz};\n"
            "ld.shared.v4.u32 {a0,a1,a2,a3}, [ab+128];\n"
            "and.b32 tmp, aa, 0xffffff80; mbarrier.test_wait.parity.shared::cta.b64 pw, [tmp+520], mt;\n"
            "mad.lo.s32 xa, st, 2048, xa;\n"
            "mov.b32 {lo,hi}, r0; mov.b32 rl, {lo,lo}; mov.b32 rh, {hi,hi};\n"
            "mul.bf16x2 x0, x0, rl; mul.bf16x2 x1, x1, rl; mul.bf16x2 x2, x2, rh; mul.bf16x2 x3, x3, rh;\n"
            "mov.b32 {lo,hi}, r1; mov.b32 rl, {lo,lo}; mov.b32 rh, {hi,hi};\n"
            "mul.bf16x2 x4, x4, rl; mul.bf16x2 x5, x5, rl; mul.bf16x2 x6, x6, rh; mul.bf16x2 x7, x7, rh;\n"
            "mov.b32 {lo,hi}, r2; mov.b32 rl, {lo,lo}; mov.b32 rh, {hi,hi};\n"
            "mul.bf16x2 x8, x8, rl; mul.bf16x2 x9, x9, rl; mul.bf16x2 x10, x10, rh; mul.bf16x2 x11, x11, rh;\n"
            "mov.b32 {lo,hi}, r3; mov.b32 rl, {lo,lo}; mov.b32 rh, {hi,hi};\n"
            "mul.bf16x2 x12, x12, rl; mul.bf16x2 x13, x13, rl; mul.bf16x2 x14, x14, rh; mul.bf16x2 x15, x15, rh;\n"
            "@!pw bra.uni W1;\n"
            "@d2 bra.uni B0_4; @d1 bra.uni L0; @d0 bra.uni B0_1; bra.uni B0_0;\n"
            "B1_3:\n"
            "xor.b32 tmp, mt, ea; and.b32 tmp, tmp, 192; setp.eq.u32 pm, tmp, 0; selp.b32 ab, aa, %3, pm;\n"
            "and.b32 tmp, mt, 8; setp.ne.u32 d0, tmp, 0; and.b32 tmp, mt, 16; setp.ne.u32 d1, tmp, 0; and.b32 tmp, mt, 32; setp.ne.u32 d2, tmp, 0;\n"
            "ld.shared.v2.u32 {e0,e1}, [ea];\n"
            "shr.s32 st, mt, 24; mad.lo.s32 aa, st, 2560, aa;\n"
            "mma.sync.aligned.m16n8k16.row.col.f32.bf16.bf16.f32 {c96,c97,c98,c99}, {a0,a1,a2,a3}, {x0,x1}, {c96,c97,c98,c99};\n"
            "mma.sync.aligned.m16n8k16.row.col.f32.bf16.bf16.f32 {c100,c101,c102,c103}, {a0,a1,a2,a3}, {x2,x3}, {c100,c101,c102,c103};\n"
            "ld.shared.v4.u32 {x0,x1,x2,x3}, [xa+1024];\n"
            "tanh.approx.f32 th0, h1;\n"
            "tanh.approx.f32 th1, h3;\n"
            "fma.rn.f32 th0, h1, th0, h1;\n"
            "fma.rn.f32 th1, h3, th1, h3;\n"
            "cvt.rn.bf16x2.f32 r0, th1, th0;\n"
            "mma.sync.aligned.m16n8k16.row.col.f32.bf16.bf16.f32 {h0,h1,h2,h3}, {%7,%8,%9,%10}, {e0,e1}, {fz,fz,fz,fz};\n"
            "mma.sync.aligned.m16n8k16.row.col.f32.bf16.bf16.f32 {c104,c105,c106,c107}, {a0,a1,a2,a3}, {x4,x5}, {c104,c105,c106,c107};\n"
            "mma.sync.aligned.m16n8k16.row.col.f32.bf16.bf16.f32 {c108,c109,c110,c111}, {a0,a1,a2,a3}, {x6,x7}, {c108,c109,c110,c111};\n"
            "ld.shared.v4.u32 {x4,x5,x6,x7}, [xa+1152];\n"
            "tanh.approx.f32 th2, h5;\n"
            "tanh.approx.f32 th3, h7;\n"
            "fma.rn.f32 th2, h5, th2, h5;\n"
            "fma.rn.f32 th3, h7, th3, h7;\n"
            "cvt.rn.bf16x2.f32 r1, th3, th2;\n"
            "mma.sync.aligned.m16n8k16.row.col.f32.bf16.bf16.f32 {h4,h5,h6,h7}, {%11,%12,%13,%14}, {e0,e1}, {fz,fz,fz,fz};\n"
            "mma.sync.aligned.m16n8k16.row.col.f32.bf16.bf16.f32 {c112,c113,c114,c115}, {a0,a1,a2,a3}, {x8,x9}, {c112,c113,c114,c115};\n"
            "mma.sync.aligned.m16n8k16.row.col.f32.bf16.bf16.f32 {c116,c117,c118,c119}, {a0,a1,a2,a3}, {x10,x11}, {c116,c117,c118,c119};\n"
            "ld.shared.v4.u32 {x8,x9,x10,x11}, [xa+1536];\n"
            "tanh.approx.f32 th4, h9;\n"
            "tanh.approx.f32 th5, h11;\n"
            "fma.rn.f32 th4, h9, th4, h9;\n"
            "fma.rn.f32 th5, h11, th5, h11;\n"
            "cvt.rn.bf16x2.f32 r2, th5, th4;\n"
            "mma.sync.aligned.m16n8k16.row.col.f32.bf16.bf16.f32 {h8,h9,h10,h11}, {%15,%16,%17,%18}, {e0,e1}, {fz,fz,fz,fz};\n"
            "mma.sync.aligned.m16n8k16.row.col.f32.bf16.bf16.f32 {c120,c121,c122,c123}, {a0,a1,a2,a3}, {x12,x13}, {c120,c121,c122,c123};\n"
            "mma.sync.aligned.m16n8k16.row.col.f32.bf16.bf16.f32 {c124,c125,c126,c127}, {a0,a1,a2,a3}, {x14,x15}, {c124,c125,c126,c127};\n"
            "ld.shared.v4.u32 {x12,x13,x14,x15}, [xa+1664];\n"
            "tanh.approx.f32 th6, h13;\n"
            "tanh.approx.f32 th7, h15;\n"
            "fma.rn.f32 th6, h13, th6, h13;\n"
            "fma.rn.f32 th7, h15, th7, h15;\n"
            "cvt.rn.bf16x2.f32 r3, th7, th6;\n"
            "mma.sync.aligned.m16n8k16.row.col.f32.bf16.bf16.f32 {h12,h13,h14,h15}, {%19,%20,%21,%22}, {e0,e1}, {fz,fz,fz,fz};\n"
            "ld.shared.v4.u32 {a0,a1,a2,a3}, [ab+128];\n"
            "and.b32 tmp, aa, 0xffffff80; mbarrier.test_wait.parity.shared::cta.b64 pw, [tmp+520], mt;\n"
            "mad.lo.s32 xa, st, 2048, xa;\n"
            "mov.b32 {lo,hi}, r0; mov.b32 rl, {lo,lo}; mov.b32 rh, {hi,hi};\n"
            "mul.bf16x2 x0, x0, rl; mul.bf16x2 x1, x1, rl; mul.bf16x2 x2, x2, rh; mul.bf16x2 x3, x3, rh;\n"
            "mov.b32 {lo,hi}, r1; mov.b32 rl, {lo,lo}; mov.b32 rh, {hi,hi};\n"
            "mul.bf16x2 x4, x4, rl; mul.bf16x2 x5, x5, rl; mul.bf16x2 x6, x6, rh; mul.bf16x2 x7, x7, rh;\n"
            "mov.b32 {lo,hi}, r2; mov.b32 rl, {lo,lo}; mov.b32 rh, {hi,hi};\n"
            "mul.bf16x2 x8, x8, rl; mul.bf16x2 x9, x9, rl; mul.bf16x2 x10, x10, rh; mul.bf16x2 x11, x11, rh;\n"
            "mov.b32 {lo,hi}, r3; mov.b32 rl, {lo,lo}; mov.b32 rh, {hi,hi};\n"
            "mul.bf16x2 x12, x12, rl; mul.bf16x2 x13, x13, rl; mul.bf16x2 x14, x14, rh; mul.bf16x2 x15, x15, rh;\n"
            "@!pw bra.uni W1;\n"
            "@d2 bra.uni B0_4; @d1 bra.uni L0; @d0 bra.uni B0_1; bra.uni B0_0;\n"
            "B1_4:\n"
            "xor.b32 tmp, mt, ea; and.b32 tmp, tmp, 192; setp.eq.u32 pm, tmp, 0; selp.b32 ab, aa, %3, pm;\n"
            "and.b32 tmp, mt, 8; setp.ne.u32 d0, tmp, 0; and.b32 tmp, mt, 16; setp.ne.u32 d1, tmp, 0; and.b32 tmp, mt, 32; setp.ne.u32 d2, tmp, 0;\n"
            "ld.shared.v2.u32 {e0,e1}, [ea];\n"
            "shr.s32 st, mt, 24; mad.lo.s32 aa, st, 2560, aa;\n"
            "mma.sync.aligned.m16n8k16.row.col.f32.bf16.bf16.f32 {c128,c129,c130,c131}, {a0,a1,a2,a3}, {x0,x1}, {c128,c129,c130,c131};\n"
            "mma.sync.aligned.m16n8k16.row.col.f32.bf16.bf16.f32 {c132,c133,c134,c135}, {a0,a1,a2,a3}, {x2,x3}, {c132,c133,c134,c135};\n"
            "ld.shared.v4.u32 {x0,x1,x2,x3}, [xa+1024];\n"
            "tanh.approx.f32 th0, h1;\n"
            "tanh.approx.f32 th1, h3;\n"
            "fma.rn.f32 th0, h1, th0, h1;\n"
            "fma.rn.f32 th1, h3, th1, h3;\n"
            "cvt.rn.bf16x2.f32 r0, th1, th0;\n"
            "mma.sync.aligned.m16n8k16.row.col.f32.bf16.bf16.f32 {h0,h1,h2,h3}, {%7,%8,%9,%10}, {e0,e1}, {fz,fz,fz,fz};\n"
            "mma.sync.aligned.m16n8k16.row.col.f32.bf16.bf16.f32 {c136,c137,c138,c139}, {a0,a1,a2,a3}, {x4,x5}, {c136,c137,c138,c139};\n"
            "mma.sync.aligned.m16n8k16.row.col.f32.bf16.bf16.f32 {c140,c141,c142,c143}, {a0,a1,a2,a3}, {x6,x7}, {c140,c141,c142,c143};\n"
            "ld.shared.v4.u32 {x4,x5,x6,x7}, [xa+1152];\n"
            "tanh.approx.f32 th2, h5;\n"
            "tanh.approx.f32 th3, h7;\n"
            "fma.rn.f32 th2, h5, th2, h5;\n"
            "fma.rn.f32 th3, h7, th3, h7;\n"
            "cvt.rn.bf16x2.f32 r1, th3, th2;\n"
            "mma.sync.aligned.m16n8k16.row.col.f32.bf16.bf16.f32 {h4,h5,h6,h7}, {%11,%12,%13,%14}, {e0,e1}, {fz,fz,fz,fz};\n"
            "mma.sync.aligned.m16n8k16.row.col.f32.bf16.bf16.f32 {c144,c145,c146,c147}, {a0,a1,a2,a3}, {x8,x9}, {c144,c145,c146,c147};\n"
            "mma.sync.aligned.m16n8k16.row.col.f32.bf16.bf16.f32 {c148,c149,c150,c151}, {a0,a1,a2,a3}, {x10,x11}, {c148,c149,c150,c151};\n"
            "ld.shared.v4.u32 {x8,x9,x10,x11}, [xa+1536];\n"
            "tanh.approx.f32 th4, h9;\n"
            "tanh.approx.f32 th5, h11;\n"
            "fma.rn.f32 th4, h9, th4, h9;\n"
            "fma.rn.f32 th5, h11, th5, h11;\n"
            "cvt.rn.bf16x2.f32 r2, th5, th4;\n"
            "mma.sync.aligned.m16n8k16.row.col.f32.bf16.bf16.f32 {h8,h9,h10,h11}, {%15,%16,%17,%18}, {e0,e1}, {fz,fz,fz,fz};\n"
            "mma.sync.aligned.m16n8k16.row.col.f32.bf16.bf16.f32 {c152,c153,c154,c155}, {a0,a1,a2,a3}, {x12,x13}, {c152,c153,c154,c155};\n"
            "mma.sync.aligned.m16n8k16.row.col.f32.bf16.bf16.f32 {c156,c157,c158,c159}, {a0,a1,a2,a3}, {x14,x15}, {c156,c157,c158,c159};\n"
            "ld.shared.v4.u32 {x12,x13,x14,x15}, [xa+1664];\n"
            "tanh.approx.f32 th6, h13;\n"
            "tanh.approx.f32 th7, h15;\n"
            "fma.rn.f32 th6, h13, th6, h13;\n"
            "fma.rn.f32 th7, h15, th7, h15;\n"
            "cvt.rn.bf16x2.f32 r3, th7, th6;\n"
            "mma.sync.aligned.m16n8k16.row.col.f32.bf16.bf16.f32 {h12,h13,h14,h15}, {%19,%20,%21,%22}, {e0,e1}, {fz,fz,fz,fz};\n"
            "ld.shared.v4.u32 {a0,a1,a2,a3}, [ab+128];\n"
            "and.b32 tmp, aa, 0xffffff80; mbarrier.test_wait.parity.shared::cta.b64 pw, [tmp+520], mt;\n"
            "mad.lo.s32 xa, st, 2048, xa;\n"
            "mov.b32 {lo,hi}, r0; mov.b32 rl, {lo,lo}; mov.b32 rh, {hi,hi};\n"
            "mul.bf16x2 x0, x0, rl; mul.bf16x2 x1, x1, rl; mul.bf16x2 x2, x2, rh; mul.bf16x2 x3, x3, rh;\n"
            "mov.b32 {lo,hi}, r1; mov.b32 rl, {lo,lo}; mov.b32 rh, {hi,hi};\n"
            "mul.bf16x2 x4, x4, rl; mul.bf16x2 x5, x5, rl; mul.bf16x2 x6, x6, rh; mul.bf16x2 x7, x7, rh;\n"
            "mov.b32 {lo,hi}, r2; mov.b32 rl, {lo,lo}; mov.b32 rh, {hi,hi};\n"
            "mul.bf16x2 x8, x8, rl; mul.bf16x2 x9, x9, rl; mul.bf16x2 x10, x10, rh; mul.bf16x2 x11, x11, rh;\n"
            "mov.b32 {lo,hi}, r3; mov.b32 rl, {lo,lo}; mov.b32 rh, {hi,hi};\n"
            "mul.bf16x2 x12, x12, rl; mul.bf16x2 x13, x13, rl; mul.bf16x2 x14, x14, rh; mul.bf16x2 x15, x15, rh;\n"
            "@!pw bra.uni W1;\n"
            "@d2 bra.uni B0_4; @d1 bra.uni L0; @d0 bra.uni B0_1; bra.uni B0_0;\n"
            "W1:\n"
            "mov.u32 cnt, 0; and.b32 tmp, aa, 0xffffff80;\n"
            "W1L: mbarrier.try_wait.parity.shared::cta.b64 pw, [tmp+520], mt; @pw bra.uni W1D;\n"
            "add.u32 cnt, cnt, 1; setp.lt.u32 pk, cnt, 1000000; @pk bra.uni W1L; trap;\n"
            "W1D:\n"
            "@d2 bra.uni B0_4; @d1 bra.uni L0; @d0 bra.uni B0_1; bra.uni B0_0;\n"
            "END:\n"
            "cvt.rn.bf16x2.f32 p0, c1, c0; cvt.rn.bf16x2.f32 p1, c5, c4; cvt.rn.bf16x2.f32 p2, c9, c8; cvt.rn.bf16x2.f32 p3, c13, c12; cvt.rn.bf16x2.f32 p4, c17, c16; cvt.rn.bf16x2.f32 p5, c21, c20; cvt.rn.bf16x2.f32 p6, c25, c24; cvt.rn.bf16x2.f32 p7, c29, c28;\n"
            "cvt.rn.bf16x2.f32 p8, c3, c2; cvt.rn.bf16x2.f32 p9, c7, c6; cvt.rn.bf16x2.f32 p10, c11, c10; cvt.rn.bf16x2.f32 p11, c15, c14; cvt.rn.bf16x2.f32 p12, c19, c18; cvt.rn.bf16x2.f32 p13, c23, c22; cvt.rn.bf16x2.f32 p14, c27, c26; cvt.rn.bf16x2.f32 p15, c31, c30;\n"
            "cvt.rn.bf16x2.f32 p16, c33, c32; cvt.rn.bf16x2.f32 p17, c37, c36; cvt.rn.bf16x2.f32 p18, c41, c40; cvt.rn.bf16x2.f32 p19, c45, c44; cvt.rn.bf16x2.f32 p20, c49, c48; cvt.rn.bf16x2.f32 p21, c53, c52; cvt.rn.bf16x2.f32 p22, c57, c56; cvt.rn.bf16x2.f32 p23, c61, c60;\n"
            "cvt.rn.bf16x2.f32 p24, c35, c34; cvt.rn.bf16x2.f32 p25, c39, c38; cvt.rn.bf16x2.f32 p26, c43, c42; cvt.rn.bf16x2.f32 p27, c47, c46; cvt.rn.bf16x2.f32 p28, c51, c50; cvt.rn.bf16x2.f32 p29, c55, c54; cvt.rn.bf16x2.f32 p30, c59, c58; cvt.rn.bf16x2.f32 p31, c63, c62;\n"
            "cvt.rn.bf16x2.f32 p32, c65, c64; cvt.rn.bf16x2.f32 p33, c69, c68; cvt.rn.bf16x2.f32 p34, c73, c72; cvt.rn.bf16x2.f32 p35, c77, c76; cvt.rn.bf16x2.f32 p36, c81, c80; cvt.rn.bf16x2.f32 p37, c85, c84; cvt.rn.bf16x2.f32 p38, c89, c88; cvt.rn.bf16x2.f32 p39, c93, c92;\n"
            "cvt.rn.bf16x2.f32 p40, c67, c66; cvt.rn.bf16x2.f32 p41, c71, c70; cvt.rn.bf16x2.f32 p42, c75, c74; cvt.rn.bf16x2.f32 p43, c79, c78; cvt.rn.bf16x2.f32 p44, c83, c82; cvt.rn.bf16x2.f32 p45, c87, c86; cvt.rn.bf16x2.f32 p46, c91, c90; cvt.rn.bf16x2.f32 p47, c95, c94;\n"
            "cvt.rn.bf16x2.f32 p48, c97, c96; cvt.rn.bf16x2.f32 p49, c101, c100; cvt.rn.bf16x2.f32 p50, c105, c104; cvt.rn.bf16x2.f32 p51, c109, c108; cvt.rn.bf16x2.f32 p52, c113, c112; cvt.rn.bf16x2.f32 p53, c117, c116; cvt.rn.bf16x2.f32 p54, c121, c120; cvt.rn.bf16x2.f32 p55, c125, c124;\n"
            "cvt.rn.bf16x2.f32 p56, c99, c98; cvt.rn.bf16x2.f32 p57, c103, c102; cvt.rn.bf16x2.f32 p58, c107, c106; cvt.rn.bf16x2.f32 p59, c111, c110; cvt.rn.bf16x2.f32 p60, c115, c114; cvt.rn.bf16x2.f32 p61, c119, c118; cvt.rn.bf16x2.f32 p62, c123, c122; cvt.rn.bf16x2.f32 p63, c127, c126;\n"
            "cvt.rn.bf16x2.f32 p64, c129, c128; cvt.rn.bf16x2.f32 p65, c133, c132; cvt.rn.bf16x2.f32 p66, c137, c136; cvt.rn.bf16x2.f32 p67, c141, c140; cvt.rn.bf16x2.f32 p68, c145, c144; cvt.rn.bf16x2.f32 p69, c149, c148; cvt.rn.bf16x2.f32 p70, c153, c152; cvt.rn.bf16x2.f32 p71, c157, c156;\n"
            "cvt.rn.bf16x2.f32 p72, c131, c130; cvt.rn.bf16x2.f32 p73, c135, c134; cvt.rn.bf16x2.f32 p74, c139, c138; cvt.rn.bf16x2.f32 p75, c143, c142; cvt.rn.bf16x2.f32 p76, c147, c146; cvt.rn.bf16x2.f32 p77, c151, c150; cvt.rn.bf16x2.f32 p78, c155, c154; cvt.rn.bf16x2.f32 p79, c159, c158;\n"
            "and.b32 aa, %3, 0xfffff980; sub.u32 aa, aa, %6; mov.u32 mt, %%tid.x; shr.u32 st, mt, 7; shr.u32 cnt, mt, 5; add.u32 cnt, cnt, st; and.b32 cnt, cnt, 3;\n"
            "and.b32 mt, mt, 31; mad.lo.u32 tmp, mt, 16, aa; mad.lo.u32 tmp, st, 82432, tmp; mad.lo.u32 tmp, cnt, 10240, tmp; add.u32 cnt, cnt, 5;\n"
            "bar.sync cnt, 64;\n"
            "stmatrix.sync.aligned.m8n8.x4.shared.b16 [tmp+0], {p0,p1,p2,p3};\n"
            "stmatrix.sync.aligned.m8n8.x4.shared.b16 [tmp+41216], {p4,p5,p6,p7};\n"
            "stmatrix.sync.aligned.m8n8.x4.shared.b16 [tmp+1024], {p8,p9,p10,p11};\n"
            "stmatrix.sync.aligned.m8n8.x4.shared.b16 [tmp+42240], {p12,p13,p14,p15};\n"
            "stmatrix.sync.aligned.m8n8.x4.shared.b16 [tmp+2048], {p16,p17,p18,p19};\n"
            "stmatrix.sync.aligned.m8n8.x4.shared.b16 [tmp+43264], {p20,p21,p22,p23};\n"
            "stmatrix.sync.aligned.m8n8.x4.shared.b16 [tmp+3072], {p24,p25,p26,p27};\n"
            "stmatrix.sync.aligned.m8n8.x4.shared.b16 [tmp+44288], {p28,p29,p30,p31};\n"
            "stmatrix.sync.aligned.m8n8.x4.shared.b16 [tmp+4096], {p32,p33,p34,p35};\n"
            "stmatrix.sync.aligned.m8n8.x4.shared.b16 [tmp+45312], {p36,p37,p38,p39};\n"
            "stmatrix.sync.aligned.m8n8.x4.shared.b16 [tmp+5120], {p40,p41,p42,p43};\n"
            "stmatrix.sync.aligned.m8n8.x4.shared.b16 [tmp+46336], {p44,p45,p46,p47};\n"
            "stmatrix.sync.aligned.m8n8.x4.shared.b16 [tmp+6144], {p48,p49,p50,p51};\n"
            "stmatrix.sync.aligned.m8n8.x4.shared.b16 [tmp+47360], {p52,p53,p54,p55};\n"
            "stmatrix.sync.aligned.m8n8.x4.shared.b16 [tmp+7168], {p56,p57,p58,p59};\n"
            "stmatrix.sync.aligned.m8n8.x4.shared.b16 [tmp+48384], {p60,p61,p62,p63};\n"
            "stmatrix.sync.aligned.m8n8.x4.shared.b16 [tmp+8192], {p64,p65,p66,p67};\n"
            "stmatrix.sync.aligned.m8n8.x4.shared.b16 [tmp+49408], {p68,p69,p70,p71};\n"
            "stmatrix.sync.aligned.m8n8.x4.shared.b16 [tmp+9216], {p72,p73,p74,p75};\n"
            "stmatrix.sync.aligned.m8n8.x4.shared.b16 [tmp+50432], {p76,p77,p78,p79};\n"
            "mov.b32 %0, aa;\n"
            "}\n"
            : "=r"(sb2)
            : "r"(sb + t * XREG + grp * (NST * 2048) + half * 256 + ((g ^ ((2 * t + 2 * half) & 7)) << 4)),
              "r"(sb + AUX_OFF + grp * AUX_GR + t * 32 + (g & 1) * 16), "r"(az),
              "r"(sb + AUX_OFF + grp * AUX_GR + 256 + lane * 8), "r"(zero), "n"(ZERO_OFF),
              "r"(wr[0][0]), "r"(wr[0][1]), "r"(wr[0][2]), "r"(wr[0][3]), "r"(wr[1][0]), "r"(wr[1][1]), "r"(wr[1][2]), "r"(wr[1][3]),
              "r"(wr[2][0]), "r"(wr[2][1]), "r"(wr[2][2]), "r"(wr[2][3]), "r"(wr[3][0]), "r"(wr[3][1]), "r"(wr[3][2]), "r"(wr[3][3])
            : "memory");
        const int tid2 = threadIdx.x;
        sb2 = __shfl_sync(0xffffffffu, sb2, 0);
        const uint2 own = lds64(sb2 + MISC_OFF + 8);
        asm volatile("fence.proxy.async.shared::cta;" ::: "memory");
        mbar_wait(sb2 + MISC_OFF, 0);
        uint32_t da[8][4];
        {
            const uint32_t n = tid2 & 7, mb = ((tid2 >> 4) & 6) + ((tid2 >> 3) & 1);
            const uint32_t a = sb2 + WM_OFF + (tid2 >> 7) * 16384 + ((tid2 >> 4) & 1) * 1024 + n * 128 + ((mb ^ n) << 4);
#pragma unroll
            for (int ks = 0; ks < 8; ks++)
                asm volatile("ldmatrix.sync.aligned.m8n8.x4.trans.shared.b16 {%0,%1,%2,%3}, [%4];"
                             : "=r"(da[ks][0]), "=r"(da[ks][1]), "=r"(da[ks][2]), "=r"(da[ks][3]) : "r"(a + ks * 2048) : "memory");
        }
        asm volatile("bar.sync 1, 256;" ::: "memory");
        const uint32_t wg = __shfl_sync(0xffffffffu, tid2 >> 7, 0);
        const uint64_t db = (uint64_t)(sb2 >> 4) | (8ull << 16) | (64ull << 32);
        const int left = (int)own.y - 4 * (tid2 & 3);
        uint32_t* op = out + (size_t)(own.x + 4 * (tid2 & 3)) * 256 + ((tid2 >> 5) * 16 + ((tid2 & 31) >> 2)) * 2;
        float d0[32], d1[32], d2[32], d3[32], d4[32], d5[32];
        mix_tiles<2, 0, 0, 8>(d0, da, db);
        mix_tiles<2, 2, 0, 4>(d1, da, db);
        wait_tiles<2, 1>(d0);
        store_tiles<0, 0, 1, true>(d0, op, left, 3 + wg);
        mix_tiles<2, 2, 4, 8>(d1, da, db);
        store_tiles<0, 1, 2, true>(d0, op, left, 3 + wg);
        mix_tiles<4, 4, 0, 4>(d2, da, db);
        wait_tiles<2, 1>(d1);
        store_tiles<2, 0, 1, true>(d1, op, left, 3 + wg);
        mix_tiles<4, 4, 4, 8>(d2, da, db);
        store_tiles<2, 1, 2, true>(d1, op, left, 3 + wg);
        mix_tiles<4, 8, 0, 2>(d3, da, db);
        wait_tiles<4, 1>(d2);
        store_tiles<4, 0, 1, true>(d2, op, left, 3 + wg);
        mix_tiles<4, 8, 2, 4>(d3, da, db);
        store_tiles<4, 1, 2, true>(d2, op, left, 3 + wg);
        mix_tiles<4, 8, 4, 6>(d3, da, db);
        store_tiles<4, 2, 3, true>(d2, op, left, 3 + wg);
        mix_tiles<4, 8, 6, 8>(d3, da, db);
        store_tiles<4, 3, 4, true>(d2, op, left, 3 + wg);
        mix_tiles<4, 12, 0, 2>(d4, da, db);
        wait_tiles<4, 1>(d3);
        store_tiles<8, 0, 1, true>(d3, op, left, 3 + wg);
        mix_tiles<4, 12, 2, 4>(d4, da, db);
        store_tiles<8, 1, 2, true>(d3, op, left, 3 + wg);
        mix_tiles<4, 12, 4, 6>(d4, da, db);
        store_tiles<8, 2, 3, true>(d3, op, left, 3 + wg);
        mix_tiles<4, 12, 6, 8>(d4, da, db);
        store_tiles<8, 3, 4, true>(d3, op, left, 3 + wg);
        mix_tiles<4, 16, 0, 2>(d5, da, db);
        wait_tiles<4, 1>(d4);
        store_tiles<12, 0, 1, true>(d4, op, left, 3 + wg);
        mix_tiles<4, 16, 2, 4>(d5, da, db);
        store_tiles<12, 1, 2, true>(d4, op, left, 3 + wg);
        mix_tiles<4, 16, 4, 6>(d5, da, db);
        store_tiles<12, 2, 3, true>(d4, op, left, 3 + wg);
        mix_tiles<4, 16, 6, 8>(d5, da, db);
        store_tiles<12, 3, 4, true>(d4, op, left, 3 + wg);
        wait_tiles<4, 0>(d5);
        store_tiles<16, 0, 4, false>(d5, op, left, 0);
    } else {
        asm volatile("setmaxnreg.dec.sync.aligned.u32 40;");
        const uint64_t map = ((uint64_t)maphi << 32) | maplo, efl = ((uint64_t)efhi << 32) | eflo;
        const uint32_t ab = s0 + AUX_OFF + pgrp * AUX_GR, xb = s0 + pgrp * (NST * 2048);
        uint32_t yp = s0 + SY_OFF + pgrp * GCAP * 4 - 32;
        uint32_t par = 0, prev = 0;
        uint32_t parv = keep((lane & zero) + (pgrp & 1) * 128);
        auto ahead = [&](int st, uint32_t ev) {
            asm volatile("cp.async.ca.shared.global [%0], [%1], 8;" ::"r"(w_l + st * AUX_ST + 256), "l"(efl + (ev & 0x1ffffe0u)) : "memory");
            cp_async_arrive(ab + st * AUX_ST + BAR_F0);
            if (st == NST - 1) parv ^= 1u;
            sts8(f_l + st * AUX_ST, (__byte_perm(ev, prev, fsel) & 0xfeu) ^ parv);
            prev = ev;
        };
        if (lds32(yp + 32 + 7 * 4) > (uint32_t)N) pc = 0;
        uint32_t wn0, wn1;
        uint32_t efo = blockIdx.x * EPC * 32u + pgrp * PFE;
        const uint32_t efend = min((blockIdx.x + 1) * EPC, E) * 32u;
        uint32_t pfo = (4u * (PFA * gridDim.x + blockIdx.x) + pgrp) * pfb;
        const uint32_t pfend = (uint32_t)N * 1024u - pfb;
        auto step = [&](int st, int WM) {
            if (left < st) return true;
            const uint4 y0 = lds128(yp + st * 32), y1 = lds128(yp + st * 32 + 16);
            const uint32_t ev = lds32(yp + st * 32 + 32 + e_l);
            uint32_t wa = wn0, wb = wn1;
            if (WM) {
                const uint32_t h0 = lds32(h_l + st * 64), h1 = lds32(h_l + st * 64 + 64);
                float w0[4], w1[4];
                mma1688_z(w0, h0, h1, cgb0);
                mma1688_z(w1, h0, h1, cgb1);
                wa = pack_bf16(w0[0], w0[1]); wb = pack_bf16(w1[0], w1[1]);
                if (WM == 2) { wn0 = pack_bf16(w0[2], w0[3]); wn1 = pack_bf16(w1[2], w1[3]); }
            }
            const uint32_t ys = y0.y + y0.z + y1.y + y1.z;
            const uint32_t tq = T0 + ((ys * pc) >> 13);
            const int sg = st % NST;
            mbar_wait(ab + sg * AUX_ST + BAR_EM, par ^ 1u);
            int rem = (int)(tq - (uint32_t)clock64());
            ahead(sg, ev);
            sts64(w_l + sg * AUX_ST, wa, wb);
            __syncwarp();
            asm volatile("{\n\t.reg .pred P;\n\tsetp.ne.u32 P, %1, 0;\n\t@P mbarrier.arrive.expect_tx.shared::cta.b64 _, [%0], %1;\n\t}"
                         ::"r"(ab + sg * AUX_ST + BAR_F0), "r"(bytes) : "memory");
#pragma unroll 1
            while (rem > 0) {
                __nanosleep(SLEEP);
                rem = (int)(tq - (uint32_t)clock64());
            }
            fetch_quad(xb + sg * 2048, ab + sg * AUX_ST + BAR_F0, y0, map);
            fetch_quad(xb + sg * 2048 + 1024, ab + sg * AUX_ST + BAR_F0, y1, map);
            return false;
        };
        ahead(0, lds32(yp + 32 + e_l));
        __syncwarp();
        if (lane == 0) asm volatile("mbarrier.arrive.shared::cta.b64 _, [%0], %1;" ::"r"(ab + BAR_F0), "n"(F0_COUNT - 32) : "memory");
#pragma unroll 1
        for (;;) {
            if (step(1, 2)) break;
            if (step(2, 0)) break;
            if (efo < efend) prefetch_bulk(ef + efo, min(PFE, efend - efo));
            efo += 4u * PFE;
            if (step(3, 2)) break;
            if (step(4, 0)) break;
            par ^= 1u;
            if (step(5, 1)) break;
            if (pfo <= pfend) prefetch_bulk(x + pfo, pfb);
            pfo += 4u * gridDim.x * pfb;
            yp += NST * 32;
            left -= NST;
            h_l += NST * 64;
        }
        const int ln = threadIdx.x & 31, n = (threadIdx.x >> 4) & 7;
        const uint32_t wd = s0 + WM_OFF + ((ln >> 3) & 1) * 16384 + n * 128 + (((ln & 7) ^ n) << 4);
        const __nv_bfloat16* wp[4];
#pragma unroll
        for (int j = 0; j < 4; j++) wp[j] = w_mix + 2 * (n ^ ((j & 1) + 4 * (j >> 1))) * 128 + (ln & 15) * 8;
        const uint32_t fin = left == NST - 1 ? 0 : left + 1;
        mbar_wait(ab + fin * AUX_ST + BAR_EM, par ^ 1u);
        if (lane == 0) asm volatile("mbarrier.arrive.shared::cta.b64 _, [%0], %1;" ::"r"(ab + fin * AUX_ST + BAR_F0), "n"(F0_COUNT) : "memory");
        asm volatile("bar.sync 2, 128;" ::: "memory");
#pragma unroll
        for (int i = 0; i < 16; i++)
            asm volatile("cp.async.cg.shared.global [%0], [%1], 16;" ::"r"(wd + i * 1024),
                         "l"(wp[(i >> 1) & 3] + (16 * (2 * (i >> 3) + ((i >> 1) & 1) + (i & 4)) + (i & 1)) * 128) : "memory");
        cp_async_arrive(s0 + MISC_OFF);
        asm volatile("cp.async.wait_all;" ::: "memory");
    }
}

typedef CUresult (*EncodeFn)(CUtensorMap*, CUtensorMapDataType, cuuint32_t, void*, const cuuint64_t*, const cuuint64_t*,
                             const cuuint32_t*, const cuuint32_t*, CUtensorMapInterleave, CUtensorMapSwizzle,
                             CUtensorMapL2promotion, CUtensorMapFloatOOBfill);

}

#define WALK 45800
#define LEAD 6300

extern "C" void kernel_launch(void* const* d_in, const int* in_sizes, int n_in, void* d_out, int out_size) {
    const char* x = (const char*)d_in[0];
    const int* src = (const int*)d_in[1];
    const int* dst = (const int*)d_in[2];
    const uint2* Y = (const uint2*)d_in[3];
    const char* ef = (const char*)d_in[4];
    const __nv_bfloat16* w_rad = (const __nv_bfloat16*)d_in[5];
    const __nv_bfloat16* cg = (const __nv_bfloat16*)d_in[6];
    const __nv_bfloat16* w_mix = (const __nv_bfloat16*)d_in[7];
    const int N = in_sizes[0] / 512;
    const int E = in_sizes[1];

    static int num_cta = 0;
    static EncodeFn encode = nullptr;
    if (num_cta == 0) {
        int dev = 0, sms = 0;
        cudaGetDevice(&dev);
        cudaDeviceGetAttribute(&sms, cudaDevAttrMultiProcessorCount, dev);
        num_cta = sms < MAXCTA ? sms : MAXCTA;
        cudaFuncSetAttribute(tfn_kernel, cudaFuncAttributeMaxDynamicSharedMemorySize, SMEM_BYTES);
        void* fn = nullptr;
        cudaDriverEntryPointQueryResult qr;
        cudaGetDriverEntryPoint("cuTensorMapEncodeTiled", &fn, cudaEnableDefault, &qr);
        encode = (EncodeFn)fn;
    }
    int S = (N + num_cta - 1) / num_cta;
    if (S < 2) S = 2;
    const int EPC = ((E + num_cta - 1) / num_cta + 3) & ~3;
    if (S > SMAX || (E + 127) / 128 > 2 * NWARP * num_cta || N < 128 || N > 16384 || E <= 0 || E > (1 << 20) || encode == nullptr) return;
    CUtensorMap xmap;
    const cuuint64_t gd[2] = {64, (cuuint64_t)N * 8}, gs[1] = {128};
    const cuuint32_t bx[2] = {64, BOX_LINES}, es[2] = {1, 1};
    if (encode(&xmap, CU_TENSOR_MAP_DATA_TYPE_BFLOAT16, 2, (void*)x, gd, gs, bx, es, CU_TENSOR_MAP_INTERLEAVE_NONE,
               CU_TENSOR_MAP_SWIZZLE_128B, CU_TENSOR_MAP_L2_PROMOTION_NONE, CU_TENSOR_MAP_FLOAT_OOB_FILL_NONE) != CUDA_SUCCESS)
        return;
    const uint32_t magicS = (uint32_t)((0x100000000ull + S - 1) / S);
    uint32_t magicB = (uint32_t)(((unsigned long long)NB << 32) / N);
    int walk = WALK, lead = LEAD;
    double pc = (double)walk * ((double)E / N * S / 2432.0) / (16.0 * N);
    if (pc > 0.99) pc = 0.99;
    uint32_t pace = (uint32_t)(pc * 4096.0 + 0.5), curve = 0;
    const uint32_t pfb = ((uint32_t)(1024.0 * N / E * 40.0) + 127u) & ~127u;
    tfn_kernel<<<num_cta, NT, SMEM_BYTES, cudaStreamPerThread>>>(xmap, x, src, dst, Y, ef, w_rad, cg, w_mix, (uint32_t*)d_out, N, E, S,
                                                                 EPC, magicS, 0u - S, magicB, 0u, pace, lead, pfb, curve);
}
```
